```python
import torch

def _softmax(x, axis=-1):
    return torch.softmax(x, dim=axis)
def _gelu(x):
    return torch.nn.functional.gelu(x, approximate="tanh")
def _silu(x):
    return torch.nn.functional.silu(x)
def _sigmoid(x):
    return torch.sigmoid(x)
def _layernorm(x, axis=-1, eps=1e-5):
    m = x.mean(dim=axis, keepdim=True)
    v = x.var(dim=axis, keepdim=True, unbiased=False)
    return (x - m) / torch.sqrt(v + eps)
def _scatter_add(tgt, idx, src, axis=0):
    return tgt.clone().index_add_(axis, idx, src)
def _segment_sum(src, seg, n):
    out = torch.zeros((n,) + src.shape[1:], dtype=src.dtype)
    return out.index_add_(0, seg, src)
def _pad(x, pw):
    flat = tuple(v for pair in reversed(pw) for v in pair)
    return torch.nn.functional.pad(x, flat)

kernel_name = 'gather_scatter__edge_featured_mpnn_gatedgcn__graph'

def setup_inputs():

    _w = (lambda a: (lambda t: t.to(torch.bfloat16) if t.is_floating_point() else t)(torch.as_tensor(a)))
    N, deg, D, De = 10000, 32, 128, max(0, 1)
    E = N * deg
    return {
        "x": _w((lambda *s: torch.randn(*s, dtype=torch.bfloat16) * 0.4)(N, D)),
        "e_attr": _w((lambda *s: torch.randn(*s, dtype=torch.bfloat16) * 1.6)(E, De)),
        "src": _w((lambda lo, hi, *s: torch.randint(lo, hi, s))(0, N, E).to(torch.int64)),
        "dst": _w((lambda lo, hi, *s: torch.randint(lo, hi, s))(0, N, E).to(torch.int64)),
        "w_a": _w((lambda *s: torch.randn(*s, dtype=torch.bfloat16) * 0.4)(D, D)),
        "w_b": _w((lambda *s: torch.randn(*s, dtype=torch.bfloat16) * 0.4)(D, D)),
        "w_c": _w((lambda *s: torch.randn(*s, dtype=torch.bfloat16) * 1.6)(De, D)),
        "w_u": _w((lambda *s: torch.randn(*s, dtype=torch.bfloat16) * 0.05)(D, D)),
        "w_v": _w((lambda *s: torch.randn(*s, dtype=torch.bfloat16) * 0.05)(D, D)),
    }

def reference(x, e_attr, src, dst, w_a, w_b, w_c, w_u, w_v):
    N, D = x.shape
    hv = x @ w_v
    g = x[dst] @ w_a + x[src] @ w_b + e_attr @ w_c
    eta = _sigmoid(g)
    denom = _segment_sum(eta, dst, N) + 1e-6
    eta_n = eta / denom[dst]
    agg = _segment_sum(eta_n * hv[src], dst, N)
    z = x @ w_u + agg
    relu_z = torch.where(z > 0, z, 0 * z)
    return x + relu_z
```

```cpp
#include <cuda_runtime.h>
#include <cuda_bf16.h>
#include <stdint.h>

#define D_FEAT 128
#define MAX_N 16384
#define MAX_E (1 << 20)
#define CAP 64
#define LOG2E 1.4426950408889634f

__device__ uint4 g_T[MAX_N * 32];
__device__ uint4 g_AU[MAX_N * 32];
__device__ int g_cnt[MAX_N];
__device__ uint32_t g_bucket[MAX_N * CAP];
__device__ int g_ovf[MAX_E];
__device__ int g_ovf_cnt;
__device__ int g_done;

__device__ __forceinline__ float ex2_approx(float x) {
    float y; asm("ex2.approx.ftz.f32 %0, %1;" : "=f"(y) : "f"(x)); return y;
}
__device__ __forceinline__ float rcp_approx(float x) {
    float y; asm("rcp.approx.ftz.f32 %0, %1;" : "=f"(y) : "f"(x)); return y;
}
__device__ __forceinline__ uint32_t pack_bf16(float lo, float hi) {
    __nv_bfloat162 t = __floats2bfloat162_rn(lo, hi);
    return *reinterpret_cast<uint32_t*>(&t);
}
__device__ __forceinline__ float bf_lo(uint32_t v) { return __uint_as_float(v << 16); }
__device__ __forceinline__ float bf_hi(uint32_t v) { return __uint_as_float(v & 0xffff0000u); }
__device__ __forceinline__ float round_bf16(float x) { return __bfloat162float(__float2bfloat16_rn(x)); }

__device__ __forceinline__ void mma_bf16(float c[4], uint32_t a0, uint32_t a1, uint32_t a2, uint32_t a3,
                                         uint32_t b0, uint32_t b1) {
    asm volatile("mma.sync.aligned.m16n8k16.row.col.f32.bf16.bf16.f32 "
                 "{%0,%1,%2,%3}, {%4,%5,%6,%7}, {%8,%9}, {%0,%1,%2,%3};"
                 : "+f"(c[0]), "+f"(c[1]), "+f"(c[2]), "+f"(c[3])
                 : "r"(a0), "r"(a1), "r"(a2), "r"(a3), "r"(b0), "r"(b1));
}
__device__ __forceinline__ void ldmatrix_x4_trans(uint32_t& r0, uint32_t& r1, uint32_t& r2, uint32_t& r3, uint32_t addr) {
    asm volatile("ldmatrix.sync.aligned.m8n8.x4.trans.shared.b16 {%0,%1,%2,%3}, [%4];"
                 : "=r"(r0), "=r"(r1), "=r"(r2), "=r"(r3) : "r"(addr));
}

#define K1_ROWS 64
#define K1_EPT 8

__global__ void __launch_bounds__(256) k1_kernel(
    const __nv_bfloat16* __restrict__ x, const __nv_bfloat16* __restrict__ e_attr,
    const int* __restrict__ src, const int* __restrict__ dst,
    const __nv_bfloat16* __restrict__ w_a, const __nv_bfloat16* __restrict__ w_b,
    const __nv_bfloat16* __restrict__ w_u, const __nv_bfloat16* __restrict__ w_v,
    int N, int E, int n_row_tiles)
{
    extern __shared__ __align__(128) uint8_t smem[];
    asm volatile("griddepcontrol.launch_dependents;");

    const int tid = threadIdx.x;
    const int warp = tid >> 5, lane = tid & 31;
    const int type = blockIdx.x >= n_row_tiles ? 1 : 0;
    const int tile = type ? blockIdx.x - n_row_tiles : blockIdx.x;

    uint4 X0[4], X1[4];
    const int q = lane & 3;
    const int r0 = tile * K1_ROWS + (warp & 3) * 16 + (lane >> 2);
    if (warp < 4) {
        const uint4* xr0 = reinterpret_cast<const uint4*>(x) + (size_t)r0 * 16 + q;
        const uint4* xr1 = xr0 + 8 * 16;
        #pragma unroll
        for (int c = 0; c < 4; c++) {
            X0[c] = (r0 < N) ? __ldg(xr0 + c * 4) : make_uint4(0, 0, 0, 0);
            X1[c] = (r0 + 8 < N) ? __ldg(xr1 + c * 4) : make_uint4(0, 0, 0, 0);
        }
    }

    {
        const uint4* W0 = reinterpret_cast<const uint4*>(type ? w_a : w_b);
        const uint4* W1 = reinterpret_cast<const uint4*>(type ? w_u : w_v);
        #pragma unroll
        for (int it = 0; it < 8; it++) {
            int u = it * 256 + tid;
            int mtx = u >> 10, k = (u >> 3) & 127, m = u & 7;
            const uint4* p = (mtx ? W1 : W0) + k * 16 + m * 2;
            uint4 lo = __ldg(p), hi = __ldg(p + 1);
            uint4 c0 = make_uint4(lo.x, lo.z, hi.x, hi.z);
            uint4 c1 = make_uint4(lo.y, lo.w, hi.y, hi.w);
            int f = (((k >> 3) & 3) << 1) | (k & 1);
            uint8_t* row = smem + mtx * 32768 + k * 256;
            *reinterpret_cast<uint4*>(row + (((2 * m) ^ f) << 4)) = c0;
            *reinterpret_cast<uint4*>(row + (((2 * m + 1) ^ f) << 4)) = c1;
        }
    }
    __syncthreads();

    if (warp < 4) {
        const uint32_t sbase = (uint32_t)__cvta_generic_to_shared(smem);
        const int mi = lane >> 3, ii = lane & 7;
        const int hh = mi & 1, tj = mi >> 1;
        uint4* outp = (type ? g_AU : g_T);
        #pragma unroll 1
        for (int m = 0; m < 8; m++) {
            float acc[4][4];
            #pragma unroll
            for (int t = 0; t < 4; t++) { acc[t][0] = acc[t][1] = acc[t][2] = acc[t][3] = 0.f; }
            #pragma unroll
            for (int c = 0; c < 4; c++) {
                #pragma unroll
                for (int s = 0; s < 2; s++) {
                    int k = 32 * c + 8 * (ii >> 1) + 4 * s + 2 * hh + (ii & 1);
                    int f = (((k >> 3) & 3) << 1) | (k & 1);
                    uint32_t addr = sbase + k * 256 + (((2 * m + tj) ^ f) << 4);
                    uint32_t b0, b1, b2, b3, h0, h1, h2, h3;
                    ldmatrix_x4_trans(b0, b1, b2, b3, addr);
                    ldmatrix_x4_trans(h0, h1, h2, h3, addr + 32768);
                    uint32_t a0 = s ? X0[c].z : X0[c].x, a1 = s ? X1[c].z : X1[c].x;
                    uint32_t a2 = s ? X0[c].w : X0[c].y, a3 = s ? X1[c].w : X1[c].y;
                    mma_bf16(acc[0], a0, a1, a2, a3, b0, b1);
                    mma_bf16(acc[1], a0, a1, a2, a3, b2, b3);
                    mma_bf16(acc[2], a0, a1, a2, a3, h0, h1);
                    mma_bf16(acc[3], a0, a1, a2, a3, h2, h3);
                }
            }
            uint4 o0 = make_uint4(pack_bf16(acc[0][0], acc[0][1]), pack_bf16(acc[1][0], acc[1][1]),
                                  pack_bf16(acc[2][0], acc[2][1]), pack_bf16(acc[3][0], acc[3][1]));
            uint4 o1 = make_uint4(pack_bf16(acc[0][2], acc[0][3]), pack_bf16(acc[1][2], acc[1][3]),
                                  pack_bf16(acc[2][2], acc[2][3]), pack_bf16(acc[3][2], acc[3][3]));
            if (r0 < N) outp[(size_t)r0 * 32 + 4 * m + q] = o0;
            if (r0 + 8 < N) outp[(size_t)(r0 + 8) * 32 + 4 * m + q] = o1;
        }
    } else {
        const int bt = tid - 128;
        const int per_cta = (E + gridDim.x - 1) / gridDim.x;
        const int beg = blockIdx.x * per_cta;
        const int end = min(E, beg + per_cta);
        for (int base = beg + bt; base < end; base += 128 * K1_EPT) {
            int d[K1_EPT]; uint32_t rec[K1_EPT]; int rk[K1_EPT];
            #pragma unroll
            for (int i = 0; i < K1_EPT; i++) {
                int e = base + i * 128;
                if (e < end) {
                    d[i] = __ldg(dst + e);
                    uint32_t s = (uint32_t)__ldg(src + e);
                    uint32_t ev = (uint32_t)__ldg(reinterpret_cast<const unsigned short*>(e_attr) + e);
                    rec[i] = (ev << 16) | s;
                } else d[i] = -1;
            }
            #pragma unroll
            for (int i = 0; i < K1_EPT; i++) if (d[i] >= 0) rk[i] = atomicAdd(&g_cnt[d[i]], 1);
            #pragma unroll
            for (int i = 0; i < K1_EPT; i++) {
                if (d[i] >= 0) {
                    if (rk[i] < CAP) g_bucket[d[i] * CAP + rk[i]] = rec[i];
                    else { int p = atomicAdd(&g_ovf_cnt, 1); g_ovf[p] = base + i * 128; }
                }
            }
        }
    }
}

__device__ __forceinline__ void edge_accum(const uint4 v, const float e, const float a[4], const float cc[4],
                                           float num[4], float den[4]) {
    float y0 = fmaf(bf_lo(v.x), -LOG2E, fmaf(e, cc[0], a[0]));
    float y1 = fmaf(bf_hi(v.x), -LOG2E, fmaf(e, cc[1], a[1]));
    float y2 = fmaf(bf_lo(v.y), -LOG2E, fmaf(e, cc[2], a[2]));
    float y3 = fmaf(bf_hi(v.y), -LOG2E, fmaf(e, cc[3], a[3]));
    float s0 = rcp_approx(1.f + ex2_approx(y0));
    float s1 = rcp_approx(1.f + ex2_approx(y1));
    float s2 = rcp_approx(1.f + ex2_approx(y2));
    float s3 = rcp_approx(1.f + ex2_approx(y3));
    den[0] += s0; den[1] += s1; den[2] += s2; den[3] += s3;
    num[0] = fmaf(s0, bf_lo(v.z), num[0]);
    num[1] = fmaf(s1, bf_hi(v.z), num[1]);
    num[2] = fmaf(s2, bf_lo(v.w), num[2]);
    num[3] = fmaf(s3, bf_hi(v.w), num[3]);
}

#define K2_WARPS 8
__global__ void __launch_bounds__(K2_WARPS * 32) k2_kernel(
    const __nv_bfloat16* __restrict__ x, const __nv_bfloat16* __restrict__ e_attr,
    const int* __restrict__ src, const int* __restrict__ dst,
    const __nv_bfloat16* __restrict__ w_c, __nv_bfloat16* __restrict__ out, int N, int E)
{
    const int lane = threadIdx.x & 31;
    const int n = blockIdx.x * K2_WARPS + (threadIdx.x >> 5);

    const uint2 wc = __ldg(reinterpret_cast<const uint2*>(w_c) + lane);
    uint2 xv = make_uint2(0, 0);
    if (n < N) xv = __ldg(reinterpret_cast<const uint2*>(x) + (size_t)n * 32 + lane);
    float cc[4] = { -LOG2E * bf_lo(wc.x), -LOG2E * bf_hi(wc.x), -LOG2E * bf_lo(wc.y), -LOG2E * bf_hi(wc.y) };

    asm volatile("griddepcontrol.wait;" ::: "memory");

    int ovf_n = 0;
    if (n < N) {
        const int cnt = g_cnt[n];
        const uint4 au = g_AU[(size_t)n * 32 + lane];
        float a[4] = { -LOG2E * bf_lo(au.x), -LOG2E * bf_hi(au.x), -LOG2E * bf_lo(au.y), -LOG2E * bf_hi(au.y) };
        float num[4] = {0.f, 0.f, 0.f, 0.f}, den[4] = {0.f, 0.f, 0.f, 0.f};
        const uint4* Tl = g_T + lane;
        const int m = min(cnt, CAP);
        for (int base = 0; base < m; base += 32) {
            const uint32_t rec = (base + lane < m) ? g_bucket[n * CAP + base + lane] : 0u;
            const int k = min(32, m - base);
            int j = 0;
            for (; j + 4 <= k; j += 4) {
                uint32_t r[4]; uint4 v[4];
                #pragma unroll
                for (int u = 0; u < 4; u++) {
                    r[u] = __shfl_sync(0xffffffffu, rec, j + u);
                    v[u] = __ldg(Tl + (size_t)(r[u] & 0xffffu) * 32);
                }
                #pragma unroll
                for (int u = 0; u < 4; u++) edge_accum(v[u], bf_hi(r[u]), a, cc, num, den);
            }
            for (; j < k; j++) {
                uint32_t r = __shfl_sync(0xffffffffu, rec, j);
                uint4 v = __ldg(Tl + (size_t)(r & 0xffffu) * 32);
                edge_accum(v, bf_hi(r), a, cc, num, den);
            }
        }
        if (cnt > CAP) {
            const int on = *(volatile int*)&g_ovf_cnt;
            for (int base = 0; base < on; base += 32) {
                int eid = (base + lane < on) ? g_ovf[base + lane] : -1;
                bool mine = (eid >= 0) && (__ldg(dst + eid) == n);
                unsigned msk = __ballot_sync(0xffffffffu, mine);
                while (msk) {
                    int l = __ffs(msk) - 1; msk &= msk - 1;
                    int e = __shfl_sync(0xffffffffu, eid, l);
                    int s = __ldg(src + e);
                    float ev = __bfloat162float(e_attr[e]);
                    uint4 v = __ldg(Tl + (size_t)s * 32);
                    edge_accum(v, ev, a, cc, num, den);
                }
            }
        }
        if (lane == 0) g_cnt[n] = 0;

        float o[4];
        const float u4[4] = { bf_lo(au.z), bf_hi(au.z), bf_lo(au.w), bf_hi(au.w) };
        const float x4[4] = { bf_lo(xv.x), bf_hi(xv.x), bf_lo(xv.y), bf_hi(xv.y) };
        #pragma unroll
        for (int i = 0; i < 4; i++) {
            float agg = round_bf16(__fdividef(num[i], den[i] + 1e-6f));
            float z = round_bf16(u4[i] + agg);
            float rz = (z > 0.f) ? z : 0.f * z;
            o[i] = x4[i] + rz;
        }
        uint2 ov = make_uint2(pack_bf16(o[0], o[1]), pack_bf16(o[2], o[3]));
        reinterpret_cast<uint2*>(out)[(size_t)n * 32 + lane] = ov;
    }
    ovf_n = *(volatile int*)&g_ovf_cnt;
    if (ovf_n != 0) {
        __syncthreads();
        if (threadIdx.x == 0) {
            __threadfence();
            int t = atomicAdd(&g_done, 1);
            if (t == (int)gridDim.x - 1) { g_done = 0; __threadfence(); g_ovf_cnt = 0; }
        }
    }
}

extern "C" void kernel_launch(void* const* d_in, const int* in_sizes, int n_in,
                              void* d_out, int out_size) {
    const __nv_bfloat16* x      = (const __nv_bfloat16*)d_in[0];
    const __nv_bfloat16* e_attr = (const __nv_bfloat16*)d_in[1];
    const int* src = (const int*)d_in[2];
    const int* dst = (const int*)d_in[3];
    const __nv_bfloat16* w_a = (const __nv_bfloat16*)d_in[4];
    const __nv_bfloat16* w_b = (const __nv_bfloat16*)d_in[5];
    const __nv_bfloat16* w_c = (const __nv_bfloat16*)d_in[6];
    const __nv_bfloat16* w_u = (const __nv_bfloat16*)d_in[7];
    const __nv_bfloat16* w_v = (const __nv_bfloat16*)d_in[8];
    __nv_bfloat16* out = (__nv_bfloat16*)d_out;
    const int N = in_sizes[0] / D_FEAT;
    const int E = in_sizes[2];
    if (N > MAX_N || E > MAX_E || N <= 0) return;

    static bool attr_set = false;
    if (!attr_set) {
        cudaFuncSetAttribute(k1_kernel, cudaFuncAttributeMaxDynamicSharedMemorySize, 65536);
        attr_set = true;
    }
    cudaStream_t st = cudaStreamPerThread;
    const int n_row_tiles = (N + K1_ROWS - 1) / K1_ROWS;
    k1_kernel<<<2 * n_row_tiles, 256, 65536, st>>>(x, e_attr, src, dst, w_a, w_b, w_u, w_v, N, E, n_row_tiles);

    cudaLaunchConfig_t cfg = {};
    cfg.gridDim = dim3((N + K2_WARPS - 1) / K2_WARPS);
    cfg.blockDim = dim3(K2_WARPS * 32);
    cfg.dynamicSmemBytes = 0;
    cfg.stream = st;
    cudaLaunchAttribute at[1];
    at[0].id = cudaLaunchAttributeProgrammaticStreamSerialization;
    at[0].val.programmaticStreamSerializationAllowed = 1;
    cfg.attrs = at; cfg.numAttrs = 1;
    cudaLaunchKernelEx(&cfg, k2_kernel, x, e_attr, src, dst, w_c, out, N, E);
}
```

```cpp
#include <cuda_runtime.h>
#include <cuda_bf16.h>
#include <stdint.h>

#define D_FEAT 128
#define MAX_N 16384
#define MAX_E (1 << 20)
#define LOG2E 1.4426950408889634f

#define MAXBINS 256
#define MAXNB 128
#define BINCAP 3072
__device__ uint4 g_T[MAX_N * 32];
__device__ uint4 g_AU[MAX_N * 32];
__device__ int g_bin_cnt[MAXBINS];
__device__ uint2 g_bins[MAXBINS * BINCAP];
__device__ int g_ovf[MAX_E];
__device__ int g_ovf_cnt;
__device__ int g_done;

__device__ __forceinline__ float ex2_approx(float x) {
    float y; asm("ex2.approx.ftz.f32 %0, %1;" : "=f"(y) : "f"(x)); return y;
}
__device__ __forceinline__ float rcp_approx(float x) {
    float y; asm("rcp.approx.ftz.f32 %0, %1;" : "=f"(y) : "f"(x)); return y;
}
__device__ __forceinline__ uint32_t pack_bf16(float lo, float hi) {
    __nv_bfloat162 t = __floats2bfloat162_rn(lo, hi);
    return *reinterpret_cast<uint32_t*>(&t);
}
__device__ __forceinline__ float bf_lo(uint32_t v) { return __uint_as_float(v << 16); }
__device__ __forceinline__ float bf_hi(uint32_t v) { return __uint_as_float(v & 0xffff0000u); }
__device__ __forceinline__ float round_bf16(float x) { return __bfloat162float(__float2bfloat16_rn(x)); }

__device__ __forceinline__ void mma_bf16(float c[4], uint32_t a0, uint32_t a1, uint32_t a2, uint32_t a3,
                                         uint32_t b0, uint32_t b1) {
    asm volatile("mma.sync.aligned.m16n8k16.row.col.f32.bf16.bf16.f32 "
                 "{%0,%1,%2,%3}, {%4,%5,%6,%7}, {%8,%9}, {%0,%1,%2,%3};"
                 : "+f"(c[0]), "+f"(c[1]), "+f"(c[2]), "+f"(c[3])
                 : "r"(a0), "r"(a1), "r"(a2), "r"(a3), "r"(b0), "r"(b1));
}
__device__ __forceinline__ void ldmatrix_x4_trans(uint32_t& r0, uint32_t& r1, uint32_t& r2, uint32_t& r3, uint32_t addr) {
    asm volatile("ldmatrix.sync.aligned.m8n8.x4.trans.shared.b16 {%0,%1,%2,%3}, [%4];"
                 : "=r"(r0), "=r"(r1), "=r"(r2), "=r"(r3) : "r"(addr));
}

#define K1_ROWS 128
#define P1_EPT 10
#define P1_CHUNK (256 * P1_EPT)

__global__ void __launch_bounds__(256) k1_kernel(
    const __nv_bfloat16* __restrict__ x, const __nv_bfloat16* __restrict__ e_attr,
    const int* __restrict__ src, const int* __restrict__ dst,
    const __nv_bfloat16* __restrict__ w_a, const __nv_bfloat16* __restrict__ w_b,
    const __nv_bfloat16* __restrict__ w_u, const __nv_bfloat16* __restrict__ w_v,
    int N, int E, int n_row_tiles, int P, int chunk, int NB, int nbins, uint32_t magic)
{
    extern __shared__ __align__(128) uint8_t smem[];
    asm volatile("griddepcontrol.launch_dependents;");

    const int tid = threadIdx.x;
    const int warp = tid >> 5, lane = tid & 31;

    if ((int)blockIdx.x < P) {
        int* hist = reinterpret_cast<int*>(smem);
        int* loff = hist + MAXBINS;
        int* gbase = loff + MAXBINS;
        uint2* sorted = reinterpret_cast<uint2*>(smem + 3 * MAXBINS * 4);
        for (int beg = blockIdx.x * chunk; beg < E; beg += P * chunk) {
            const int end = min(E, beg + chunk);
            int d[P1_EPT]; uint32_t rec[P1_EPT]; int rk[P1_EPT]; int bn[P1_EPT];
            #pragma unroll
            for (int i = 0; i < P1_EPT; i++) {
                int e = beg + i * 256 + tid;
                d[i] = -1;
                if (e < end) {
                    d[i] = __ldg(dst + e);
                    uint32_t s = (uint32_t)__ldg(src + e);
                    uint32_t ev = (uint32_t)__ldg(reinterpret_cast<const unsigned short*>(e_attr) + e);
                    rec[i] = (ev << 16) | s;
                }
            }
            hist[tid] = 0;
            __syncthreads();
            #pragma unroll
            for (int i = 0; i < P1_EPT; i++) {
                if (d[i] >= 0) {
                    bn[i] = (int)(((uint64_t)(uint32_t)d[i] * magic) >> 24);
                    rk[i] = atomicAdd(&hist[bn[i]], 1);
                }
            }
            __syncthreads();
            {
                int h = hist[tid];
                if (tid < nbins && h > 0) gbase[tid] = atomicAdd(&g_bin_cnt[tid], h);
                if (warp == 0) {
                    int v[8]; int sum = 0;
                    #pragma unroll
                    for (int i = 0; i < 8; i++) { v[i] = hist[lane * 8 + i]; sum += v[i]; }
                    int inc = sum;
                    #pragma unroll
                    for (int o = 1; o < 32; o <<= 1) { int t = __shfl_up_sync(0xffffffffu, inc, o); if (lane >= o) inc += t; }
                    int run = inc - sum;
                    #pragma unroll
                    for (int i = 0; i < 8; i++) { loff[lane * 8 + i] = run; run += v[i]; }
                }
            }
            __syncthreads();
            #pragma unroll
            for (int i = 0; i < P1_EPT; i++) {
                if (d[i] >= 0) sorted[loff[bn[i]] + rk[i]] = make_uint2(rec[i], (uint32_t)d[i]);
            }
            __syncthreads();
            const int cnt = end - beg;
            for (int i = tid; i < cnt; i += 256) {
                uint2 r = sorted[i];
                int b = (int)(((uint64_t)r.y * magic) >> 24);
                int pos = gbase[b] + (i - loff[b]);
                if (pos < BINCAP) {
                    g_bins[b * BINCAP + pos] = make_uint2(r.x, r.y - (uint32_t)(b * NB));
                } else {
                    int p = atomicAdd(&g_ovf_cnt, 2);
                    g_ovf[p] = (int)r.y; g_ovf[p + 1] = (int)r.x;
                }
            }
            __syncthreads();
        }
        return;
    }

    const int gb = blockIdx.x - P;
    const int type = gb >= n_row_tiles ? 1 : 0;
    const int tile = type ? gb - n_row_tiles : gb;

    uint4 X0[4], X1[4];
    const int q = lane & 3;
    const int r0 = tile * K1_ROWS + warp * 16 + (lane >> 2);
    {
        const uint4* xr0 = reinterpret_cast<const uint4*>(x) + (size_t)r0 * 16 + q;
        const uint4* xr1 = xr0 + 8 * 16;
        #pragma unroll
        for (int c = 0; c < 4; c++) {
            X0[c] = (r0 < N) ? __ldg(xr0 + c * 4) : make_uint4(0, 0, 0, 0);
            X1[c] = (r0 + 8 < N) ? __ldg(xr1 + c * 4) : make_uint4(0, 0, 0, 0);
        }
    }
    {
        const uint4* W0 = reinterpret_cast<const uint4*>(type ? w_a : w_b);
        const uint4* W1 = reinterpret_cast<const uint4*>(type ? w_u : w_v);
        #pragma unroll
        for (int it = 0; it < 8; it++) {
            int u = it * 256 + tid;
            int mtx = u >> 10, k = (u >> 3) & 127, m = u & 7;
            const uint4* p = (mtx ? W1 : W0) + k * 16 + m * 2;
            uint4 lo = __ldg(p), hi = __ldg(p + 1);
            uint4 c0 = make_uint4(lo.x, lo.z, hi.x, hi.z);
            uint4 c1 = make_uint4(lo.y, lo.w, hi.y, hi.w);
            int f = (((k >> 3) & 3) << 1) | (k & 1);
            uint8_t* row = smem + mtx * 32768 + k * 256;
            *reinterpret_cast<uint4*>(row + (((2 * m) ^ f) << 4)) = c0;
            *reinterpret_cast<uint4*>(row + (((2 * m + 1) ^ f) << 4)) = c1;
        }
    }
    __syncthreads();
    {
        const uint32_t sbase = (uint32_t)__cvta_generic_to_shared(smem);
        const int mi = lane >> 3, ii = lane & 7;
        const int hh = mi & 1, tj = mi >> 1;
        uint4* outp = (type ? g_AU : g_T);
        #pragma unroll 1
        for (int m = 0; m < 8; m++) {
            float acc[4][4];
            #pragma unroll
            for (int t = 0; t < 4; t++) { acc[t][0] = acc[t][1] = acc[t][2] = acc[t][3] = 0.f; }
            #pragma unroll
            for (int c = 0; c < 4; c++) {
                #pragma unroll
                for (int s = 0; s < 2; s++) {
                    int k = 32 * c + 8 * (ii >> 1) + 4 * s + 2 * hh + (ii & 1);
                    int f = (((k >> 3) & 3) << 1) | (k & 1);
                    uint32_t addr = sbase + k * 256 + (((2 * m + tj) ^ f) << 4);
                    uint32_t b0, b1, b2, b3, h0, h1, h2, h3;
                    ldmatrix_x4_trans(b0, b1, b2, b3, addr);
                    ldmatrix_x4_trans(h0, h1, h2, h3, addr + 32768);
                    uint32_t a0 = s ? X0[c].z : X0[c].x, a1 = s ? X1[c].z : X1[c].x;
                    uint32_t a2 = s ? X0[c].w : X0[c].y, a3 = s ? X1[c].w : X1[c].y;
                    mma_bf16(acc[0], a0, a1, a2, a3, b0, b1);
                    mma_bf16(acc[1], a0, a1, a2, a3, b2, b3);
                    mma_bf16(acc[2], a0, a1, a2, a3, h0, h1);
                    mma_bf16(acc[3], a0, a1, a2, a3, h2, h3);
                }
            }
            uint4 o0 = make_uint4(pack_bf16(acc[0][0], acc[0][1]), pack_bf16(acc[1][0], acc[1][1]),
                                  pack_bf16(acc[2][0], acc[2][1]), pack_bf16(acc[3][0], acc[3][1]));
            uint4 o1 = make_uint4(pack_bf16(acc[0][2], acc[0][3]), pack_bf16(acc[1][2], acc[1][3]),
                                  pack_bf16(acc[2][2], acc[2][3]), pack_bf16(acc[3][2], acc[3][3]));
            if (r0 < N) outp[(size_t)r0 * 32 + 4 * m + q] = o0;
            if (r0 + 8 < N) outp[(size_t)(r0 + 8) * 32 + 4 * m + q] = o1;
        }
    }
}

__device__ __forceinline__ void edge_accum(const uint4 v, const float e, const float a[4], const float cc[4],
                                           float num[4], float den[4]) {
    float y0 = fmaf(bf_lo(v.x), -LOG2E, fmaf(e, cc[0], a[0]));
    float y1 = fmaf(bf_hi(v.x), -LOG2E, fmaf(e, cc[1], a[1]));
    float y2 = fmaf(bf_lo(v.y), -LOG2E, fmaf(e, cc[2], a[2]));
    float y3 = fmaf(bf_hi(v.y), -LOG2E, fmaf(e, cc[3], a[3]));
    float s0 = rcp_approx(1.f + ex2_approx(y0));
    float s1 = rcp_approx(1.f + ex2_approx(y1));
    float s2 = rcp_approx(1.f + ex2_approx(y2));
    float s3 = rcp_approx(1.f + ex2_approx(y3));
    den[0] += s0; den[1] += s1; den[2] += s2; den[3] += s3;
    num[0] = fmaf(s0, bf_lo(v.z), num[0]);
    num[1] = fmaf(s1, bf_hi(v.z), num[1]);
    num[2] = fmaf(s2, bf_lo(v.w), num[2]);
    num[3] = fmaf(s3, bf_hi(v.w), num[3]);
}

#define K2_THREADS 512
#define K2_DYN_SMEM (100*1024)
#define K2_RPT (BINCAP / K2_THREADS)

__global__ void __launch_bounds__(K2_THREADS) k2_kernel(
    const __nv_bfloat16* __restrict__ x, const __nv_bfloat16* __restrict__ w_c,
    __nv_bfloat16* __restrict__ out, int N, int NB)
{
    __shared__ __align__(16) uint32_t s_sorted[BINCAP + 4 * MAXNB];
    __shared__ int s_hist[MAXNB];
    __shared__ int s_off[MAXNB];
    __shared__ int s_next;

    const int tid = threadIdx.x;
    const int lane = tid & 31, warp = tid >> 5;
    const int bin = blockIdx.x;
    const int node0 = bin * NB;
    const int nn = min(NB, N - node0);

    const uint2 wc = __ldg(reinterpret_cast<const uint2*>(w_c) + lane);
    const float cc[4] = { -LOG2E * bf_lo(wc.x), -LOG2E * bf_hi(wc.x), -LOG2E * bf_lo(wc.y), -LOG2E * bf_hi(wc.y) };
    if (tid < MAXNB) s_hist[tid] = 0;
    if (tid == 0) s_next = K2_THREADS / 32;
    __syncthreads();

    asm volatile("griddepcontrol.wait;" ::: "memory");

    const int cnt = min(g_bin_cnt[bin], BINCAP);
    const int ovf_n = g_ovf_cnt;
    {
        uint2 r[K2_RPT]; int rk[K2_RPT];
        #pragma unroll
        for (int i = 0; i < K2_RPT; i++) {
            int idx = i * K2_THREADS + tid;
            if (idx < cnt) r[i] = g_bins[bin * BINCAP + idx];
        }
        #pragma unroll
        for (int i = 0; i < K2_RPT; i++) {
            int idx = i * K2_THREADS + tid;
            if (idx < cnt) rk[i] = atomicAdd(&s_hist[r[i].y], 1);
        }
        __syncthreads();
        if (warp == 0) {
            int v[4]; int sum = 0;
            #pragma unroll
            for (int i = 0; i < 4; i++) { v[i] = (s_hist[lane * 4 + i] + 3) & ~3; sum += v[i]; }
            int inc = sum;
            #pragma unroll
            for (int o = 1; o < 32; o <<= 1) { int t = __shfl_up_sync(0xffffffffu, inc, o); if (lane >= o) inc += t; }
            int run = inc - sum;
            #pragma unroll
            for (int i = 0; i < 4; i++) { s_off[lane * 4 + i] = run; run += v[i]; }
        }
        if (tid == 32) g_bin_cnt[bin] = 0;
        __syncthreads();
        #pragma unroll
        for (int i = 0; i < K2_RPT; i++) {
            int idx = i * K2_THREADS + tid;
            if (idx < cnt) s_sorted[s_off[r[i].y] + rk[i]] = r[i].x;
        }
        __syncthreads();
    }

    const uint4* Tl = g_T + lane;
    int ln = warp;
    while (ln < nn) {
        const int n = node0 + ln;
        const uint4 au = g_AU[(size_t)n * 32 + lane];
        const uint2 xv = __ldg(reinterpret_cast<const uint2*>(x) + (size_t)n * 32 + lane);
        const int c = s_hist[ln];
        const uint32_t* sp = s_sorted + s_off[ln];
        const float a[4] = { -LOG2E * bf_lo(au.x), -LOG2E * bf_hi(au.x), -LOG2E * bf_lo(au.y), -LOG2E * bf_hi(au.y) };
        float num[4] = {0.f, 0.f, 0.f, 0.f}, den[4] = {0.f, 0.f, 0.f, 0.f};
        int j = 0;
        for (; j + 8 <= c; j += 8) {
            const uint4 ra = *reinterpret_cast<const uint4*>(sp + j);
            const uint4 rb = *reinterpret_cast<const uint4*>(sp + j + 4);
            const uint32_t r[8] = { ra.x, ra.y, ra.z, ra.w, rb.x, rb.y, rb.z, rb.w };
            uint4 v[8];
            #pragma unroll
            for (int u = 0; u < 8; u++) v[u] = __ldg(Tl + (size_t)(r[u] & 0xffffu) * 32);
            #pragma unroll
            for (int u = 0; u < 8; u++) edge_accum(v[u], bf_hi(r[u]), a, cc, num, den);
        }
        if (j + 4 <= c) {
            const uint4 ra = *reinterpret_cast<const uint4*>(sp + j);
            const uint32_t r[4] = { ra.x, ra.y, ra.z, ra.w };
            uint4 v[4];
            #pragma unroll
            for (int u = 0; u < 4; u++) v[u] = __ldg(Tl + (size_t)(r[u] & 0xffffu) * 32);
            #pragma unroll
            for (int u = 0; u < 4; u++) edge_accum(v[u], bf_hi(r[u]), a, cc, num, den);
            j += 4;
        }
        if (j < c) {
            const uint4 ra = *reinterpret_cast<const uint4*>(sp + j);
            const uint32_t r[3] = { ra.x, ra.y, ra.z };
            uint4 v[3];
            #pragma unroll
            for (int u = 0; u < 3; u++) if (j + u < c) v[u] = __ldg(Tl + (size_t)(r[u] & 0xffffu) * 32);
            #pragma unroll
            for (int u = 0; u < 3; u++) if (j + u < c) edge_accum(v[u], bf_hi(r[u]), a, cc, num, den);
        }
        if (ovf_n != 0) {
            for (int base = 0; base < ovf_n; base += 64) {
                int i2 = base + 2 * lane;
                int od = (i2 < ovf_n) ? g_ovf[i2] : -1;
                uint32_t orec = (i2 < ovf_n) ? (uint32_t)g_ovf[i2 + 1] : 0u;
                unsigned msk = __ballot_sync(0xffffffffu, od == n);
                while (msk) {
                    int l = __ffs(msk) - 1; msk &= msk - 1;
                    uint32_t r = __shfl_sync(0xffffffffu, orec, l);
                    uint4 v = __ldg(Tl + (size_t)(r & 0xffffu) * 32);
                    edge_accum(v, bf_hi(r), a, cc, num, den);
                }
            }
        }
        float o[4];
        const float u4[4] = { bf_lo(au.z), bf_hi(au.z), bf_lo(au.w), bf_hi(au.w) };
        const float x4[4] = { bf_lo(xv.x), bf_hi(xv.x), bf_lo(xv.y), bf_hi(xv.y) };
        #pragma unroll
        for (int i = 0; i < 4; i++) {
            float agg = round_bf16(__fdividef(num[i], den[i] + 1e-6f));
            float z = round_bf16(u4[i] + agg);
            float rz = (z > 0.f) ? z : 0.f * z;
            o[i] = x4[i] + rz;
        }
        uint2 ov = make_uint2(pack_bf16(o[0], o[1]), pack_bf16(o[2], o[3]));
        reinterpret_cast<uint2*>(out)[(size_t)n * 32 + lane] = ov;

        int nx = 0;
        if (lane == 0) nx = atomicAdd(&s_next, 1);
        ln = __shfl_sync(0xffffffffu, nx, 0);
    }
    if (ovf_n != 0) {
        __syncthreads();
        if (tid == 0) {
            __threadfence();
            int t = atomicAdd(&g_done, 1);
            if (t == (int)gridDim.x - 1) { g_done = 0; __threadfence(); g_ovf_cnt = 0; }
        }
    }
}

extern "C" void kernel_launch(void* const* d_in, const int* in_sizes, int n_in,
                              void* d_out, int out_size) {
    const __nv_bfloat16* x      = (const __nv_bfloat16*)d_in[0];
    const __nv_bfloat16* e_attr = (const __nv_bfloat16*)d_in[1];
    const int* src = (const int*)d_in[2];
    const int* dst = (const int*)d_in[3];
    const __nv_bfloat16* w_a = (const __nv_bfloat16*)d_in[4];
    const __nv_bfloat16* w_b = (const __nv_bfloat16*)d_in[5];
    const __nv_bfloat16* w_c = (const __nv_bfloat16*)d_in[6];
    const __nv_bfloat16* w_u = (const __nv_bfloat16*)d_in[7];
    const __nv_bfloat16* w_v = (const __nv_bfloat16*)d_in[8];
    __nv_bfloat16* out = (__nv_bfloat16*)d_out;
    const int N = in_sizes[0] / D_FEAT;
    const int E = in_sizes[2];
    if (N > MAX_N || 2 * E > MAX_E || N <= 0) return;

    static int num_sms = 0;
    if (num_sms == 0) {
        int dev = 0;
        cudaGetDevice(&dev);
        cudaDeviceGetAttribute(&num_sms, cudaDevAttrMultiProcessorCount, dev);
        if (num_sms <= 0 || num_sms > MAXBINS) num_sms = 132;
        cudaFuncSetAttribute(k1_kernel, cudaFuncAttributeMaxDynamicSharedMemorySize, 65536);
        cudaFuncSetAttribute(k2_kernel, cudaFuncAttributeMaxDynamicSharedMemorySize, K2_DYN_SMEM);
    }
    cudaStream_t st = cudaStreamPerThread;
    int NB = (N + num_sms - 1) / num_sms;
    if (NB > MAXNB) NB = MAXNB;
    const int nbins = (N + NB - 1) / NB;
    const uint32_t magic = (uint32_t)(((1u << 24) + NB - 1) / NB);
    const int P = num_sms;
    int chunk = (E + P - 1) / P;
    if (chunk > P1_CHUNK) chunk = P1_CHUNK;
    if (chunk < 1) chunk = 1;
    const int n_row_tiles = (N + K1_ROWS - 1) / K1_ROWS;
    k1_kernel<<<P + 2 * n_row_tiles, 256, 65536, st>>>(x, e_attr, src, dst, w_a, w_b, w_u, w_v,
                                                        N, E, n_row_tiles, P, chunk, NB, nbins, magic);

    cudaLaunchConfig_t cfg = {};
    cfg.gridDim = dim3(nbins);
    cfg.blockDim = dim3(K2_THREADS);
    cfg.dynamicSmemBytes = K2_DYN_SMEM;
    cfg.stream = st;
    cudaLaunchAttribute at[1];
    at[0].id = cudaLaunchAttributeProgrammaticStreamSerialization;
    at[0].val.programmaticStreamSerializationAllowed = 1;
    cfg.attrs = at; cfg.numAttrs = 1;
    cudaLaunchKernelEx(&cfg, k2_kernel, x, w_c, out, N, NB);
}
```

```cpp
#include <cuda_runtime.h>
#include <cuda_bf16.h>
#include <stdint.h>

#define D_FEAT 128
#define MAX_N 16384
#define MAX_E (1 << 20)
#define LOG2E 1.4426950408889634f

#define MAXBINS 256
#define MAXNB 128
#define BINCAP 3072
__device__ uint4 g_T[MAX_N * 32];
__device__ uint4 g_AU[MAX_N * 32];
__device__ int g_bin_cnt[MAXBINS];
__device__ uint2 g_bins[MAXBINS * BINCAP];
__device__ int g_ovf[MAX_E];
__device__ int g_ovf_cnt;
__device__ int g_done;

__device__ __forceinline__ float ex2_approx(float x) {
    float y; asm("ex2.approx.ftz.f32 %0, %1;" : "=f"(y) : "f"(x)); return y;
}
__device__ __forceinline__ float rcp_approx(float x) {
    float y; asm("rcp.approx.ftz.f32 %0, %1;" : "=f"(y) : "f"(x)); return y;
}
__device__ __forceinline__ uint32_t pack_bf16(float lo, float hi) {
    __nv_bfloat162 t = __floats2bfloat162_rn(lo, hi);
    return *reinterpret_cast<uint32_t*>(&t);
}
__device__ __forceinline__ float bf_lo(uint32_t v) { return __uint_as_float(v << 16); }
__device__ __forceinline__ float bf_hi(uint32_t v) { return __uint_as_float(v & 0xffff0000u); }
__device__ __forceinline__ float round_bf16(float x) { return __bfloat162float(__float2bfloat16_rn(x)); }

__device__ __forceinline__ void mma_bf16(float c[4], uint32_t a0, uint32_t a1, uint32_t a2, uint32_t a3,
                                         uint32_t b0, uint32_t b1) {
    asm volatile("mma.sync.aligned.m16n8k16.row.col.f32.bf16.bf16.f32 "
                 "{%0,%1,%2,%3}, {%4,%5,%6,%7}, {%8,%9}, {%0,%1,%2,%3};"
                 : "+f"(c[0]), "+f"(c[1]), "+f"(c[2]), "+f"(c[3])
                 : "r"(a0), "r"(a1), "r"(a2), "r"(a3), "r"(b0), "r"(b1));
}
__device__ __forceinline__ void ldmatrix_x4_trans(uint32_t& r0, uint32_t& r1, uint32_t& r2, uint32_t& r3, uint32_t addr) {
    asm volatile("ldmatrix.sync.aligned.m8n8.x4.trans.shared.b16 {%0,%1,%2,%3}, [%4];"
                 : "=r"(r0), "=r"(r1), "=r"(r2), "=r"(r3) : "r"(addr));
}

#define K1_ROWS 128
#define P1_EPT 10
#define P1_CHUNK (256 * P1_EPT)

__global__ void __launch_bounds__(256) k1_kernel(
    const __nv_bfloat16* __restrict__ x, const __nv_bfloat16* __restrict__ e_attr,
    const int* __restrict__ src, const int* __restrict__ dst,
    const __nv_bfloat16* __restrict__ w_a, const __nv_bfloat16* __restrict__ w_b,
    const __nv_bfloat16* __restrict__ w_u, const __nv_bfloat16* __restrict__ w_v,
    int N, int E, int n_row_tiles, int P, int chunk, int NB, int nbins, uint32_t magic)
{
    extern __shared__ __align__(128) uint8_t smem[];
    asm volatile("griddepcontrol.launch_dependents;");

    const int tid = threadIdx.x;
    const int warp = tid >> 5, lane = tid & 31;

    if ((int)blockIdx.x < P) {
        int* hist = reinterpret_cast<int*>(smem);
        int* loff = hist + MAXBINS;
        int* gbase = loff + MAXBINS;
        uint2* sorted = reinterpret_cast<uint2*>(smem + 3 * MAXBINS * 4);
        for (int beg = blockIdx.x * chunk; beg < E; beg += P * chunk) {
            const int end = min(E, beg + chunk);
            int d[P1_EPT]; uint32_t rec[P1_EPT]; int rk[P1_EPT]; int bn[P1_EPT];
            #pragma unroll
            for (int i = 0; i < P1_EPT; i++) {
                int e = beg + i * 256 + tid;
                d[i] = -1;
                if (e < end) {
                    d[i] = __ldg(dst + e);
                    uint32_t s = (uint32_t)__ldg(src + e);
                    uint32_t ev = (uint32_t)__ldg(reinterpret_cast<const unsigned short*>(e_attr) + e);
                    rec[i] = (ev << 16) | s;
                }
            }
            hist[tid] = 0;
            __syncthreads();
            #pragma unroll
            for (int i = 0; i < P1_EPT; i++) {
                if (d[i] >= 0) {
                    bn[i] = (int)(((uint64_t)(uint32_t)d[i] * magic) >> 24);
                    rk[i] = atomicAdd(&hist[bn[i]], 1);
                }
            }
            __syncthreads();
            {
                int h = hist[tid];
                if (tid < nbins && h > 0) gbase[tid] = atomicAdd(&g_bin_cnt[tid], h);
                if (warp == 0) {
                    int v[8]; int sum = 0;
                    #pragma unroll
                    for (int i = 0; i < 8; i++) { v[i] = hist[lane * 8 + i]; sum += v[i]; }
                    int inc = sum;
                    #pragma unroll
                    for (int o = 1; o < 32; o <<= 1) { int t = __shfl_up_sync(0xffffffffu, inc, o); if (lane >= o) inc += t; }
                    int run = inc - sum;
                    #pragma unroll
                    for (int i = 0; i < 8; i++) { loff[lane * 8 + i] = run; run += v[i]; }
                }
            }
            __syncthreads();
            #pragma unroll
            for (int i = 0; i < P1_EPT; i++) {
                if (d[i] >= 0) sorted[loff[bn[i]] + rk[i]] = make_uint2(rec[i], (uint32_t)d[i]);
            }
            __syncthreads();
            const int cnt = end - beg;
            for (int i = tid; i < cnt; i += 256) {
                uint2 r = sorted[i];
                int b = (int)(((uint64_t)r.y * magic) >> 24);
                int pos = gbase[b] + (i - loff[b]);
                if (pos < BINCAP) {
                    g_bins[b * BINCAP + pos] = make_uint2(r.x, r.y - (uint32_t)(b * NB));
                } else {
                    int p = atomicAdd(&g_ovf_cnt, 2);
                    g_ovf[p] = (int)r.y; g_ovf[p + 1] = (int)r.x;
                }
            }
            __syncthreads();
        }
        return;
    }

    const int gb = blockIdx.x - P;
    const int type = gb >= n_row_tiles ? 1 : 0;
    const int tile = type ? gb - n_row_tiles : gb;

    uint4 X0[4], X1[4];
    const int q = lane & 3;
    const int r0 = tile * K1_ROWS + warp * 16 + (lane >> 2);
    {
        const uint4* xr0 = reinterpret_cast<const uint4*>(x) + (size_t)r0 * 16 + q;
        const uint4* xr1 = xr0 + 8 * 16;
        #pragma unroll
        for (int c = 0; c < 4; c++) {
            X0[c] = (r0 < N) ? __ldg(xr0 + c * 4) : make_uint4(0, 0, 0, 0);
            X1[c] = (r0 + 8 < N) ? __ldg(xr1 + c * 4) : make_uint4(0, 0, 0, 0);
        }
    }
    {
        const uint4* W0 = reinterpret_cast<const uint4*>(type ? w_a : w_b);
        const uint4* W1 = reinterpret_cast<const uint4*>(type ? w_u : w_v);
        #pragma unroll
        for (int it = 0; it < 8; it++) {
            int u = it * 256 + tid;
            int mtx = u >> 10, k = (u >> 3) & 127, m = u & 7;
            const uint4* p = (mtx ? W1 : W0) + k * 16 + m * 2;
            uint4 lo = __ldg(p), hi = __ldg(p + 1);
            uint4 c0 = make_uint4(lo.x, lo.z, hi.x, hi.z);
            uint4 c1 = make_uint4(lo.y, lo.w, hi.y, hi.w);
            int f = (((k >> 3) & 3) << 1) | (k & 1);
            uint8_t* row = smem + mtx * 32768 + k * 256;
            *reinterpret_cast<uint4*>(row + (((2 * m) ^ f) << 4)) = c0;
            *reinterpret_cast<uint4*>(row + (((2 * m + 1) ^ f) << 4)) = c1;
        }
    }
    __syncthreads();
    {
        const uint32_t sbase = (uint32_t)__cvta_generic_to_shared(smem);
        const int mi = lane >> 3, ii = lane & 7;
        const int hh = mi & 1, tj = mi >> 1;
        uint4* outp = (type ? g_AU : g_T);
        #pragma unroll 1
        for (int m = 0; m < 8; m++) {
            float acc[4][4];
            #pragma unroll
            for (int t = 0; t < 4; t++) { acc[t][0] = acc[t][1] = acc[t][2] = acc[t][3] = 0.f; }
            #pragma unroll
            for (int c = 0; c < 4; c++) {
                #pragma unroll
                for (int s = 0; s < 2; s++) {
                    int k = 32 * c + 8 * (ii >> 1) + 4 * s + 2 * hh + (ii & 1);
                    int f = (((k >> 3) & 3) << 1) | (k & 1);
                    uint32_t addr = sbase + k * 256 + (((2 * m + tj) ^ f) << 4);
                    uint32_t b0, b1, b2, b3, h0, h1, h2, h3;
                    ldmatrix_x4_trans(b0, b1, b2, b3, addr);
                    ldmatrix_x4_trans(h0, h1, h2, h3, addr + 32768);
                    uint32_t a0 = s ? X0[c].z : X0[c].x, a1 = s ? X1[c].z : X1[c].x;
                    uint32_t a2 = s ? X0[c].w : X0[c].y, a3 = s ? X1[c].w : X1[c].y;
                    mma_bf16(acc[0], a0, a1, a2, a3, b0, b1);
                    mma_bf16(acc[1], a0, a1, a2, a3, b2, b3);
                    mma_bf16(acc[2], a0, a1, a2, a3, h0, h1);
                    mma_bf16(acc[3], a0, a1, a2, a3, h2, h3);
                }
            }
            uint4 o0 = make_uint4(pack_bf16(acc[0][0], acc[0][1]), pack_bf16(acc[1][0], acc[1][1]),
                                  pack_bf16(acc[2][0], acc[2][1]), pack_bf16(acc[3][0], acc[3][1]));
            uint4 o1 = make_uint4(pack_bf16(acc[0][2], acc[0][3]), pack_bf16(acc[1][2], acc[1][3]),
                                  pack_bf16(acc[2][2], acc[2][3]), pack_bf16(acc[3][2], acc[3][3]));
            if (r0 < N) outp[(size_t)r0 * 32 + 4 * m + q] = o0;
            if (r0 + 8 < N) outp[(size_t)(r0 + 8) * 32 + 4 * m + q] = o1;
        }
    }
}

__device__ __forceinline__ void edge_accum(const uint4 v, const float e, const float a[4], const float cc[4],
                                           float num[4], float den[4]) {
    float y0 = fmaf(bf_lo(v.x), -LOG2E, fmaf(e, cc[0], a[0]));
    float y1 = fmaf(bf_hi(v.x), -LOG2E, fmaf(e, cc[1], a[1]));
    float y2 = fmaf(bf_lo(v.y), -LOG2E, fmaf(e, cc[2], a[2]));
    float y3 = fmaf(bf_hi(v.y), -LOG2E, fmaf(e, cc[3], a[3]));
    float s0 = rcp_approx(1.f + ex2_approx(y0));
    float s1 = rcp_approx(1.f + ex2_approx(y1));
    float s2 = rcp_approx(1.f + ex2_approx(y2));
    float s3 = rcp_approx(1.f + ex2_approx(y3));
    den[0] += s0; den[1] += s1; den[2] += s2; den[3] += s3;
    num[0] = fmaf(s0, bf_lo(v.z), num[0]);
    num[1] = fmaf(s1, bf_hi(v.z), num[1]);
    num[2] = fmaf(s2, bf_lo(v.w), num[2]);
    num[3] = fmaf(s3, bf_hi(v.w), num[3]);
}

#define K2_THREADS 512
#define K2_DYN_SMEM (100*1024)
#define K2_G 8
#define K2_RPT (BINCAP / K2_THREADS)

__global__ void __launch_bounds__(K2_THREADS, 1) k2_kernel(
    const __nv_bfloat16* __restrict__ x, const __nv_bfloat16* __restrict__ w_c,
    __nv_bfloat16* __restrict__ out, int N, int NB)
{
    __shared__ __align__(16) uint32_t s_sorted[BINCAP + 4 * MAXNB];
    __shared__ int s_hist[MAXNB];
    __shared__ int s_off[MAXNB];
    __shared__ int s_next;

    const int tid = threadIdx.x;
    const int lane = tid & 31, warp = tid >> 5;
    const int bin = blockIdx.x;
    const int node0 = bin * NB;
    const int nn = min(NB, N - node0);

    const uint2 wc = __ldg(reinterpret_cast<const uint2*>(w_c) + lane);
    const float cc[4] = { -LOG2E * bf_lo(wc.x), -LOG2E * bf_hi(wc.x), -LOG2E * bf_lo(wc.y), -LOG2E * bf_hi(wc.y) };
    if (tid < MAXNB) s_hist[tid] = 0;
    if (tid == 0) s_next = K2_THREADS / 32;
    __syncthreads();

    asm volatile("griddepcontrol.wait;" ::: "memory");

    const int cnt = min(g_bin_cnt[bin], BINCAP);
    const int ovf_n = g_ovf_cnt;
    {
        uint2 r[K2_RPT]; int rk[K2_RPT];
        #pragma unroll
        for (int i = 0; i < K2_RPT; i++) {
            int idx = i * K2_THREADS + tid;
            if (idx < cnt) r[i] = g_bins[bin * BINCAP + idx];
        }
        #pragma unroll
        for (int i = 0; i < K2_RPT; i++) {
            int idx = i * K2_THREADS + tid;
            if (idx < cnt) rk[i] = atomicAdd(&s_hist[r[i].y], 1);
        }
        __syncthreads();
        if (warp == 0) {
            int v[4]; int sum = 0;
            #pragma unroll
            for (int i = 0; i < 4; i++) { v[i] = (s_hist[lane * 4 + i] + 3) & ~3; sum += v[i]; }
            int inc = sum;
            #pragma unroll
            for (int o = 1; o < 32; o <<= 1) { int t = __shfl_up_sync(0xffffffffu, inc, o); if (lane >= o) inc += t; }
            int run = inc - sum;
            #pragma unroll
            for (int i = 0; i < 4; i++) { s_off[lane * 4 + i] = run; run += v[i]; }
        }
        if (tid == 32) g_bin_cnt[bin] = 0;
        __syncthreads();
        #pragma unroll
        for (int i = 0; i < K2_RPT; i++) {
            int idx = i * K2_THREADS + tid;
            if (idx < cnt) s_sorted[s_off[r[i].y] + rk[i]] = r[i].x;
        }
        __syncthreads();
    }

    const uint4* Tl = g_T + lane;
    int ln = warp;
    while (ln < nn) {
        const int n = node0 + ln;
        const uint4 au = g_AU[(size_t)n * 32 + lane];
        const uint2 xv = __ldg(reinterpret_cast<const uint2*>(x) + (size_t)n * 32 + lane);
        const int c = s_hist[ln];
        const uint32_t* sp = s_sorted + s_off[ln];
        const float a[4] = { -LOG2E * bf_lo(au.x), -LOG2E * bf_hi(au.x), -LOG2E * bf_lo(au.y), -LOG2E * bf_hi(au.y) };
        float num[4] = {0.f, 0.f, 0.f, 0.f}, den[4] = {0.f, 0.f, 0.f, 0.f};
        {
            uint4 va[K2_G], vb[K2_G];
            uint32_t ra[K2_G], rb[K2_G];
            #define LOAD_GROUP(V, R, J) { \
                _Pragma("unroll") for (int u4_ = 0; u4_ < K2_G / 4; u4_++) { \
                    if ((J) + 4 * u4_ < c) { \
                        const uint4 t_ = *reinterpret_cast<const uint4*>(sp + (J) + 4 * u4_); \
                        R[4 * u4_] = t_.x; R[4 * u4_ + 1] = t_.y; R[4 * u4_ + 2] = t_.z; R[4 * u4_ + 3] = t_.w; \
                    } } \
                _Pragma("unroll") for (int u = 0; u < K2_G; u++) \
                    if ((J) + u < c) V[u] = __ldg(Tl + (size_t)(R[u] & 0xffffu) * 32); }
            #define CONSUME_GROUP(V, R, J) { \
                _Pragma("unroll") for (int u = 0; u < K2_G; u++) \
                    if ((J) + u < c) edge_accum(V[u], bf_hi(R[u]), a, cc, num, den); }
            LOAD_GROUP(va, ra, 0);
            for (int j = 0; j < c; j += 2 * K2_G) {
                LOAD_GROUP(vb, rb, j + K2_G);
                CONSUME_GROUP(va, ra, j);
                LOAD_GROUP(va, ra, j + 2 * K2_G);
                CONSUME_GROUP(vb, rb, j + K2_G);
            }
        }
        if (ovf_n != 0) {
            for (int base = 0; base < ovf_n; base += 64) {
                int i2 = base + 2 * lane;
                int od = (i2 < ovf_n) ? g_ovf[i2] : -1;
                uint32_t orec = (i2 < ovf_n) ? (uint32_t)g_ovf[i2 + 1] : 0u;
                unsigned msk = __ballot_sync(0xffffffffu, od == n);
                while (msk) {
                    int l = __ffs(msk) - 1; msk &= msk - 1;
                    uint32_t r = __shfl_sync(0xffffffffu, orec, l);
                    uint4 v = __ldg(Tl + (size_t)(r & 0xffffu) * 32);
                    edge_accum(v, bf_hi(r), a, cc, num, den);
                }
            }
        }
        float o[4];
        const float u4[4] = { bf_lo(au.z), bf_hi(au.z), bf_lo(au.w), bf_hi(au.w) };
        const float x4[4] = { bf_lo(xv.x), bf_hi(xv.x), bf_lo(xv.y), bf_hi(xv.y) };
        #pragma unroll
        for (int i = 0; i < 4; i++) {
            float agg = round_bf16(__fdividef(num[i], den[i] + 1e-6f));
            float z = round_bf16(u4[i] + agg);
            float rz = (z > 0.f) ? z : 0.f * z;
            o[i] = x4[i] + rz;
        }
        uint2 ov = make_uint2(pack_bf16(o[0], o[1]), pack_bf16(o[2], o[3]));
        reinterpret_cast<uint2*>(out)[(size_t)n * 32 + lane] = ov;

        int nx = 0;
        if (lane == 0) nx = atomicAdd(&s_next, 1);
        ln = __shfl_sync(0xffffffffu, nx, 0);
    }
    if (ovf_n != 0) {
        __syncthreads();
        if (tid == 0) {
            __threadfence();
            int t = atomicAdd(&g_done, 1);
            if (t == (int)gridDim.x - 1) { g_done = 0; __threadfence(); g_ovf_cnt = 0; }
        }
    }
}

extern "C" void kernel_launch(void* const* d_in, const int* in_sizes, int n_in,
                              void* d_out, int out_size) {
    const __nv_bfloat16* x      = (const __nv_bfloat16*)d_in[0];
    const __nv_bfloat16* e_attr = (const __nv_bfloat16*)d_in[1];
    const int* src = (const int*)d_in[2];
    const int* dst = (const int*)d_in[3];
    const __nv_bfloat16* w_a = (const __nv_bfloat16*)d_in[4];
    const __nv_bfloat16* w_b = (const __nv_bfloat16*)d_in[5];
    const __nv_bfloat16* w_c = (const __nv_bfloat16*)d_in[6];
    const __nv_bfloat16* w_u = (const __nv_bfloat16*)d_in[7];
    const __nv_bfloat16* w_v = (const __nv_bfloat16*)d_in[8];
    __nv_bfloat16* out = (__nv_bfloat16*)d_out;
    const int N = in_sizes[0] / D_FEAT;
    const int E = in_sizes[2];
    if (N > MAX_N || 2 * E > MAX_E || N <= 0) return;

    static int num_sms = 0;
    if (num_sms == 0) {
        int dev = 0;
        cudaGetDevice(&dev);
        cudaDeviceGetAttribute(&num_sms, cudaDevAttrMultiProcessorCount, dev);
        if (num_sms <= 0 || num_sms > MAXBINS) num_sms = 132;
        cudaFuncSetAttribute(k1_kernel, cudaFuncAttributeMaxDynamicSharedMemorySize, 65536);
        cudaFuncSetAttribute(k2_kernel, cudaFuncAttributeMaxDynamicSharedMemorySize, K2_DYN_SMEM);
    }
    cudaStream_t st = cudaStreamPerThread;
    int NB = (N + num_sms - 1) / num_sms;
    if (NB > MAXNB) NB = MAXNB;
    const int nbins = (N + NB - 1) / NB;
    const uint32_t magic = (uint32_t)(((1u << 24) + NB - 1) / NB);
    const int P = num_sms;
    int chunk = (E + P - 1) / P;
    if (chunk > P1_CHUNK) chunk = P1_CHUNK;
    if (chunk < 1) chunk = 1;
    const int n_row_tiles = (N + K1_ROWS - 1) / K1_ROWS;
    k1_kernel<<<P + 2 * n_row_tiles, 256, 65536, st>>>(x, e_attr, src, dst, w_a, w_b, w_u, w_v,
                                                        N, E, n_row_tiles, P, chunk, NB, nbins, magic);

    cudaLaunchConfig_t cfg = {};
    cfg.gridDim = dim3(nbins);
    cfg.blockDim = dim3(K2_THREADS);
    cfg.dynamicSmemBytes = K2_DYN_SMEM;
    cfg.stream = st;
    cudaLaunchAttribute at[1];
    at[0].id = cudaLaunchAttributeProgrammaticStreamSerialization;
    at[0].val.programmaticStreamSerializationAllowed = 1;
    cfg.attrs = at; cfg.numAttrs = 1;
    cudaLaunchKernelEx(&cfg, k2_kernel, x, w_c, out, N, NB);
}
```

```cpp
#include <cuda_runtime.h>
#include <cuda_bf16.h>
#include <stdint.h>

#define D_FEAT 128
#define MAX_N 16384
#define MAX_E (1 << 20)
#define LOG2E 1.4426950408889634f

#define MAXBINS 256
#define MAXNB 128
#define BINCAP 3072
__device__ uint4 g_T[(MAX_N + 1) * 32];
__device__ uint4 g_AU[MAX_N * 32];
__device__ int g_bin_cnt[MAXBINS];
__device__ uint2 g_bins[MAXBINS * BINCAP];
__device__ int g_ovf[MAX_E];
__device__ int g_ovf_cnt;
__device__ int g_done;

__device__ __forceinline__ float ex2_approx(float x) {
    float y; asm("ex2.approx.ftz.f32 %0, %1;" : "=f"(y) : "f"(x)); return y;
}
__device__ __forceinline__ float rcp_approx(float x) {
    float y; asm("rcp.approx.ftz.f32 %0, %1;" : "=f"(y) : "f"(x)); return y;
}
__device__ __forceinline__ uint32_t pack_bf16(float lo, float hi) {
    __nv_bfloat162 t = __floats2bfloat162_rn(lo, hi);
    return *reinterpret_cast<uint32_t*>(&t);
}
__device__ __forceinline__ float bf_lo(uint32_t v) { return __uint_as_float(v << 16); }
__device__ __forceinline__ float bf_hi(uint32_t v) { return __uint_as_float(v & 0xffff0000u); }
__device__ __forceinline__ float round_bf16(float x) { return __bfloat162float(__float2bfloat16_rn(x)); }

__device__ __forceinline__ void mma_bf16(float c[4], uint32_t a0, uint32_t a1, uint32_t a2, uint32_t a3,
                                         uint32_t b0, uint32_t b1) {
    asm volatile("mma.sync.aligned.m16n8k16.row.col.f32.bf16.bf16.f32 "
                 "{%0,%1,%2,%3}, {%4,%5,%6,%7}, {%8,%9}, {%0,%1,%2,%3};"
                 : "+f"(c[0]), "+f"(c[1]), "+f"(c[2]), "+f"(c[3])
                 : "r"(a0), "r"(a1), "r"(a2), "r"(a3), "r"(b0), "r"(b1));
}
__device__ __forceinline__ void ldmatrix_x4_trans(uint32_t& r0, uint32_t& r1, uint32_t& r2, uint32_t& r3, uint32_t addr) {
    asm volatile("ldmatrix.sync.aligned.m8n8.x4.trans.shared.b16 {%0,%1,%2,%3}, [%4];"
                 : "=r"(r0), "=r"(r1), "=r"(r2), "=r"(r3) : "r"(addr));
}

#define K1_ROWS 128
#define P1_EPT 10
#define P1_CHUNK (256 * P1_EPT)

__global__ void __launch_bounds__(256) k1_kernel(
    const __nv_bfloat16* __restrict__ x, const __nv_bfloat16* __restrict__ e_attr,
    const int* __restrict__ src, const int* __restrict__ dst,
    const __nv_bfloat16* __restrict__ w_a, const __nv_bfloat16* __restrict__ w_b,
    const __nv_bfloat16* __restrict__ w_u, const __nv_bfloat16* __restrict__ w_v,
    int N, int E, int n_row_tiles, int P, int chunk, int NB, int nbins, uint32_t magic)
{
    extern __shared__ __align__(128) uint8_t smem[];
    asm volatile("griddepcontrol.launch_dependents;");

    const int tid = threadIdx.x;
    const int warp = tid >> 5, lane = tid & 31;

    if ((int)blockIdx.x < P) {
        if (blockIdx.x == 0 && tid < 32) g_T[(size_t)N * 32 + tid] = make_uint4(0xff80ff80u, 0xff80ff80u, 0u, 0u);
        int* hist = reinterpret_cast<int*>(smem);
        int* loff = hist + MAXBINS;
        int* gbase = loff + MAXBINS;
        uint2* sorted = reinterpret_cast<uint2*>(smem + 3 * MAXBINS * 4);
        for (int beg = blockIdx.x * chunk; beg < E; beg += P * chunk) {
            const int end = min(E, beg + chunk);
            int d[P1_EPT]; uint32_t rec[P1_EPT]; int rk[P1_EPT]; int bn[P1_EPT];
            #pragma unroll
            for (int i = 0; i < P1_EPT; i++) {
                int e = beg + i * 256 + tid;
                d[i] = -1;
                if (e < end) {
                    d[i] = __ldg(dst + e);
                    uint32_t s = (uint32_t)__ldg(src + e);
                    uint32_t ev = (uint32_t)__ldg(reinterpret_cast<const unsigned short*>(e_attr) + e);
                    rec[i] = (ev << 16) | s;
                }
            }
            hist[tid] = 0;
            __syncthreads();
            #pragma unroll
            for (int i = 0; i < P1_EPT; i++) {
                if (d[i] >= 0) {
                    bn[i] = (int)(((uint64_t)(uint32_t)d[i] * magic) >> 24);
                    rk[i] = atomicAdd(&hist[bn[i]], 1);
                }
            }
            __syncthreads();
            {
                int h = hist[tid];
                if (tid < nbins && h > 0) gbase[tid] = atomicAdd(&g_bin_cnt[tid], h);
                if (warp == 0) {
                    int v[8]; int sum = 0;
                    #pragma unroll
                    for (int i = 0; i < 8; i++) { v[i] = hist[lane * 8 + i]; sum += v[i]; }
                    int inc = sum;
                    #pragma unroll
                    for (int o = 1; o < 32; o <<= 1) { int t = __shfl_up_sync(0xffffffffu, inc, o); if (lane >= o) inc += t; }
                    int run = inc - sum;
                    #pragma unroll
                    for (int i = 0; i < 8; i++) { loff[lane * 8 + i] = run; run += v[i]; }
                }
            }
            __syncthreads();
            #pragma unroll
            for (int i = 0; i < P1_EPT; i++) {
                if (d[i] >= 0) sorted[loff[bn[i]] + rk[i]] = make_uint2(rec[i], (uint32_t)d[i]);
            }
            __syncthreads();
            const int cnt = end - beg;
            for (int i = tid; i < cnt; i += 256) {
                uint2 r = sorted[i];
                int b = (int)(((uint64_t)r.y * magic) >> 24);
                int pos = gbase[b] + (i - loff[b]);
                if (pos < BINCAP) {
                    g_bins[b * BINCAP + pos] = make_uint2(r.x, r.y - (uint32_t)(b * NB));
                } else {
                    int p = atomicAdd(&g_ovf_cnt, 2);
                    g_ovf[p] = (int)r.y; g_ovf[p + 1] = (int)r.x;
                }
            }
            __syncthreads();
        }
        return;
    }

    const int gb = blockIdx.x - P;
    const int type = gb >= n_row_tiles ? 1 : 0;
    const int tile = type ? gb - n_row_tiles : gb;

    uint4 X0[4], X1[4];
    const int q = lane & 3;
    const int r0 = tile * K1_ROWS + warp * 16 + (lane >> 2);
    {
        const uint4* xr0 = reinterpret_cast<const uint4*>(x) + (size_t)r0 * 16 + q;
        const uint4* xr1 = xr0 + 8 * 16;
        #pragma unroll
        for (int c = 0; c < 4; c++) {
            X0[c] = (r0 < N) ? __ldg(xr0 + c * 4) : make_uint4(0, 0, 0, 0);
            X1[c] = (r0 + 8 < N) ? __ldg(xr1 + c * 4) : make_uint4(0, 0, 0, 0);
        }
    }
    {
        const uint4* W0 = reinterpret_cast<const uint4*>(type ? w_a : w_b);
        const uint4* W1 = reinterpret_cast<const uint4*>(type ? w_u : w_v);
        #pragma unroll
        for (int it = 0; it < 8; it++) {
            int u = it * 256 + tid;
            int mtx = u >> 10, k = (u >> 3) & 127, m = u & 7;
            const uint4* p = (mtx ? W1 : W0) + k * 16 + m * 2;
            uint4 lo = __ldg(p), hi = __ldg(p + 1);
            uint4 c0 = make_uint4(lo.x, lo.z, hi.x, hi.z);
            uint4 c1 = make_uint4(lo.y, lo.w, hi.y, hi.w);
            int f = (((k >> 3) & 3) << 1) | (k & 1);
            uint8_t* row = smem + mtx * 32768 + k * 256;
            *reinterpret_cast<uint4*>(row + (((2 * m) ^ f) << 4)) = c0;
            *reinterpret_cast<uint4*>(row + (((2 * m + 1) ^ f) << 4)) = c1;
        }
    }
    __syncthreads();
    {
        const uint32_t sbase = (uint32_t)__cvta_generic_to_shared(smem);
        const int mi = lane >> 3, ii = lane & 7;
        const int hh = mi & 1, tj = mi >> 1;
        uint4* outp = (type ? g_AU : g_T);
        #pragma unroll 1
        for (int m = 0; m < 8; m++) {
            float acc[4][4];
            #pragma unroll
            for (int t = 0; t < 4; t++) { acc[t][0] = acc[t][1] = acc[t][2] = acc[t][3] = 0.f; }
            #pragma unroll
            for (int c = 0; c < 4; c++) {
                #pragma unroll
                for (int s = 0; s < 2; s++) {
                    int k = 32 * c + 8 * (ii >> 1) + 4 * s + 2 * hh + (ii & 1);
                    int f = (((k >> 3) & 3) << 1) | (k & 1);
                    uint32_t addr = sbase + k * 256 + (((2 * m + tj) ^ f) << 4);
                    uint32_t b0, b1, b2, b3, h0, h1, h2, h3;
                    ldmatrix_x4_trans(b0, b1, b2, b3, addr);
                    ldmatrix_x4_trans(h0, h1, h2, h3, addr + 32768);
                    uint32_t a0 = s ? X0[c].z : X0[c].x, a1 = s ? X1[c].z : X1[c].x;
                    uint32_t a2 = s ? X0[c].w : X0[c].y, a3 = s ? X1[c].w : X1[c].y;
                    mma_bf16(acc[0], a0, a1, a2, a3, b0, b1);
                    mma_bf16(acc[1], a0, a1, a2, a3, b2, b3);
                    mma_bf16(acc[2], a0, a1, a2, a3, h0, h1);
                    mma_bf16(acc[3], a0, a1, a2, a3, h2, h3);
                }
            }
            uint4 o0 = make_uint4(pack_bf16(acc[0][0], acc[0][1]), pack_bf16(acc[1][0], acc[1][1]),
                                  pack_bf16(acc[2][0], acc[2][1]), pack_bf16(acc[3][0], acc[3][1]));
            uint4 o1 = make_uint4(pack_bf16(acc[0][2], acc[0][3]), pack_bf16(acc[1][2], acc[1][3]),
                                  pack_bf16(acc[2][2], acc[2][3]), pack_bf16(acc[3][2], acc[3][3]));
            if (r0 < N) outp[(size_t)r0 * 32 + 4 * m + q] = o0;
            if (r0 + 8 < N) outp[(size_t)(r0 + 8) * 32 + 4 * m + q] = o1;
        }
    }
}

__device__ __forceinline__ void edge_accum(const uint4 v, const float e, const float a[4], const float cc[4],
                                           float num[4], float den[4]) {
    float y0 = fmaf(bf_lo(v.x), -LOG2E, fmaf(e, cc[0], a[0]));
    float y1 = fmaf(bf_hi(v.x), -LOG2E, fmaf(e, cc[1], a[1]));
    float y2 = fmaf(bf_lo(v.y), -LOG2E, fmaf(e, cc[2], a[2]));
    float y3 = fmaf(bf_hi(v.y), -LOG2E, fmaf(e, cc[3], a[3]));
    float s0 = rcp_approx(1.f + ex2_approx(y0));
    float s1 = rcp_approx(1.f + ex2_approx(y1));
    float s2 = rcp_approx(1.f + ex2_approx(y2));
    float s3 = rcp_approx(1.f + ex2_approx(y3));
    den[0] += s0; den[1] += s1; den[2] += s2; den[3] += s3;
    num[0] = fmaf(s0, bf_lo(v.z), num[0]);
    num[1] = fmaf(s1, bf_hi(v.z), num[1]);
    num[2] = fmaf(s2, bf_lo(v.w), num[2]);
    num[3] = fmaf(s3, bf_hi(v.w), num[3]);
}

#define K2_THREADS 512
#define K2_DYN_SMEM (100*1024)
#define K2_RPT (BINCAP / K2_THREADS)
#define K2_NW (K2_THREADS / 32)
#define SORT_WORDS (BINCAP + 4 * MAXNB)

struct Grp { uint4 v[4]; uint32_t r[4]; };

__device__ __forceinline__ void grp_load(Grp& g, const uint32_t* sp, const uint4* Tl) {
    const uint4 t = *reinterpret_cast<const uint4*>(sp);
    g.r[0] = t.x; g.r[1] = t.y; g.r[2] = t.z; g.r[3] = t.w;
    #pragma unroll
    for (int u = 0; u < 4; u++) g.v[u] = __ldg(Tl + (size_t)(g.r[u] & 0xffffu) * 32);
}
__device__ __forceinline__ void grp_consume(const Grp& g, const float a[4], const float cc[4], float num[4], float den[4]) {
    #pragma unroll
    for (int u = 0; u < 4; u++) edge_accum(g.v[u], bf_hi(g.r[u]), a, cc, num, den);
}

__global__ void __launch_bounds__(K2_THREADS, 1) k2_kernel(
    const __nv_bfloat16* __restrict__ x, const __nv_bfloat16* __restrict__ w_c,
    __nv_bfloat16* __restrict__ out, int N, int NB)
{
    __shared__ __align__(16) uint32_t s_sorted[SORT_WORDS];
    __shared__ int s_hist[MAXNB];
    __shared__ int s_off[MAXNB + 1];

    const int tid = threadIdx.x;
    const int lane = tid & 31, warp = tid >> 5;
    const int bin = blockIdx.x;
    const int node0 = bin * NB;
    const int nn = min(NB, N - node0);

    const uint2 wc = __ldg(reinterpret_cast<const uint2*>(w_c) + lane);
    const float cc[4] = { -LOG2E * bf_lo(wc.x), -LOG2E * bf_hi(wc.x), -LOG2E * bf_lo(wc.y), -LOG2E * bf_hi(wc.y) };
    if (tid < MAXNB) s_hist[tid] = 0;
    for (int i = tid; i < SORT_WORDS; i += K2_THREADS) s_sorted[i] = (uint32_t)N;
    __syncthreads();

    asm volatile("griddepcontrol.wait;" ::: "memory");

    const int cnt = min(g_bin_cnt[bin], BINCAP);
    const int ovf_n = g_ovf_cnt;
    {
        uint2 r[K2_RPT]; int rk[K2_RPT];
        #pragma unroll
        for (int i = 0; i < K2_RPT; i++) {
            int idx = i * K2_THREADS + tid;
            if (idx < cnt) r[i] = g_bins[bin * BINCAP + idx];
        }
        #pragma unroll
        for (int i = 0; i < K2_RPT; i++) {
            int idx = i * K2_THREADS + tid;
            if (idx < cnt) rk[i] = atomicAdd(&s_hist[r[i].y], 1);
        }
        __syncthreads();
        if (warp == 0) {
            int v[4]; int sum = 0;
            #pragma unroll
            for (int i = 0; i < 4; i++) { v[i] = (s_hist[lane * 4 + i] + 3) & ~3; sum += v[i]; }
            int inc = sum;
            #pragma unroll
            for (int o = 1; o < 32; o <<= 1) { int t = __shfl_up_sync(0xffffffffu, inc, o); if (lane >= o) inc += t; }
            int run = inc - sum;
            #pragma unroll
            for (int i = 0; i < 4; i++) { s_off[lane * 4 + i] = run; run += v[i]; }
            if (lane == 31) s_off[MAXNB] = run;
        }
        if (tid == 32) g_bin_cnt[bin] = 0;
        __syncthreads();
        #pragma unroll
        for (int i = 0; i < K2_RPT; i++) {
            int idx = i * K2_THREADS + tid;
            if (idx < cnt) s_sorted[s_off[r[i].y] + rk[i]] = r[i].x;
        }
        __syncthreads();
    }

    const uint4* Tl = g_T + lane;
    int ln, ln_end;
    {
        const int total = s_off[MAXNB];
        const int lo = (int)(((long long)total * warp) / K2_NW);
        const int hi = (int)(((long long)total * (warp + 1)) / K2_NW);
        int c_lo = 0, c_hi = 0;
        #pragma unroll
        for (int i = 0; i < 4; i++) {
            int node = i * 32 + lane;
            int o = (node < nn) ? s_off[node] : 0x7fffffff;
            c_lo += __popc(__ballot_sync(0xffffffffu, o < lo));
            c_hi += __popc(__ballot_sync(0xffffffffu, o < hi));
        }
        ln = c_lo; ln_end = (warp == K2_NW - 1) ? nn : c_hi;
        if (warp == 0) ln = 0;
    }
    if (ln < ln_end) {
        int g = s_off[ln] >> 2;
        const int g_end = s_off[ln_end] >> 2;
        Grp b0, b1, b2;
        if (g < g_end) grp_load(b0, s_sorted + 4 * g, Tl);
        if (g + 1 < g_end) grp_load(b1, s_sorted + 4 * (g + 1), Tl);
        if (g + 2 < g_end) grp_load(b2, s_sorted + 4 * (g + 2), Tl);
        uint4 au = g_AU[(size_t)(node0 + ln) * 32 + lane];
        uint2 xv = __ldg(reinterpret_cast<const uint2*>(x) + (size_t)(node0 + ln) * 32 + lane);
        uint4 au_n; uint2 xv_n;
        if (ln + 1 < ln_end) {
            au_n = g_AU[(size_t)(node0 + ln + 1) * 32 + lane];
            xv_n = __ldg(reinterpret_cast<const uint2*>(x) + (size_t)(node0 + ln + 1) * 32 + lane);
        }
        float a[4] = { -LOG2E * bf_lo(au.x), -LOG2E * bf_hi(au.x), -LOG2E * bf_lo(au.y), -LOG2E * bf_hi(au.y) };
        float num[4] = {0.f, 0.f, 0.f, 0.f}, den[4] = {0.f, 0.f, 0.f, 0.f};
        int node_end = s_off[ln + 1] >> 2;

        #define FINISH_NODES() \
        while (g == node_end) { \
            const int n = node0 + ln; \
            if (ovf_n != 0) { \
                for (int base = 0; base < ovf_n; base += 64) { \
                    int i2 = base + 2 * lane; \
                    int od = (i2 < ovf_n) ? g_ovf[i2] : -1; \
                    uint32_t orec = (i2 < ovf_n) ? (uint32_t)g_ovf[i2 + 1] : 0u; \
                    unsigned msk = __ballot_sync(0xffffffffu, od == n); \
                    while (msk) { \
                        int l = __ffs(msk) - 1; msk &= msk - 1; \
                        uint32_t r = __shfl_sync(0xffffffffu, orec, l); \
                        uint4 v = __ldg(Tl + (size_t)(r & 0xffffu) * 32); \
                        edge_accum(v, bf_hi(r), a, cc, num, den); \
                    } \
                } \
            } \
            { \
                const float u4[4] = { bf_lo(au.z), bf_hi(au.z), bf_lo(au.w), bf_hi(au.w) }; \
                const float x4[4] = { bf_lo(xv.x), bf_hi(xv.x), bf_lo(xv.y), bf_hi(xv.y) }; \
                float o[4]; \
                _Pragma("unroll") for (int i = 0; i < 4; i++) { \
                    float agg = round_bf16(__fdividef(num[i], den[i] + 1e-6f)); \
                    float z = round_bf16(u4[i] + agg); \
                    float rz = (z > 0.f) ? z : 0.f * z; \
                    o[i] = x4[i] + rz; \
                    num[i] = 0.f; den[i] = 0.f; \
                } \
                reinterpret_cast<uint2*>(out)[(size_t)n * 32 + lane] = make_uint2(pack_bf16(o[0], o[1]), pack_bf16(o[2], o[3])); \
            } \
            ln++; \
            if (ln >= ln_end) goto done; \
            au = au_n; xv = xv_n; \
            if (ln + 1 < ln_end) { \
                au_n = g_AU[(size_t)(node0 + ln + 1) * 32 + lane]; \
                xv_n = __ldg(reinterpret_cast<const uint2*>(x) + (size_t)(node0 + ln + 1) * 32 + lane); \
            } \
            a[0] = -LOG2E * bf_lo(au.x); a[1] = -LOG2E * bf_hi(au.x); a[2] = -LOG2E * bf_lo(au.y); a[3] = -LOG2E * bf_hi(au.y); \
            node_end = s_off[ln + 1] >> 2; \
        }
        #define STEP(B) \
            FINISH_NODES(); \
            grp_consume(B, a, cc, num, den); \
            if (g + 3 < g_end) grp_load(B, s_sorted + 4 * (g + 3), Tl); \
            g++;
        while (true) {
            STEP(b0);
            STEP(b1);
            STEP(b2);
        }
        done:;
    }
    if (ovf_n != 0) {
        __syncthreads();
        if (tid == 0) {
            __threadfence();
            int t = atomicAdd(&g_done, 1);
            if (t == (int)gridDim.x - 1) { g_done = 0; __threadfence(); g_ovf_cnt = 0; }
        }
    }
}

extern "C" void kernel_launch(void* const* d_in, const int* in_sizes, int n_in,
                              void* d_out, int out_size) {
    const __nv_bfloat16* x      = (const __nv_bfloat16*)d_in[0];
    const __nv_bfloat16* e_attr = (const __nv_bfloat16*)d_in[1];
    const int* src = (const int*)d_in[2];
    const int* dst = (const int*)d_in[3];
    const __nv_bfloat16* w_a = (const __nv_bfloat16*)d_in[4];
    const __nv_bfloat16* w_b = (const __nv_bfloat16*)d_in[5];
    const __nv_bfloat16* w_c = (const __nv_bfloat16*)d_in[6];
    const __nv_bfloat16* w_u = (const __nv_bfloat16*)d_in[7];
    const __nv_bfloat16* w_v = (const __nv_bfloat16*)d_in[8];
    __nv_bfloat16* out = (__nv_bfloat16*)d_out;
    const int N = in_sizes[0] / D_FEAT;
    const int E = in_sizes[2];
    if (N > MAX_N || 2 * E > MAX_E || N <= 0) return;

    static int num_sms = 0;
    if (num_sms == 0) {
        int dev = 0;
        cudaGetDevice(&dev);
        cudaDeviceGetAttribute(&num_sms, cudaDevAttrMultiProcessorCount, dev);
        if (num_sms <= 0 || num_sms > MAXBINS) num_sms = 132;
        cudaFuncSetAttribute(k1_kernel, cudaFuncAttributeMaxDynamicSharedMemorySize, 65536);
        cudaFuncSetAttribute(k2_kernel, cudaFuncAttributeMaxDynamicSharedMemorySize, K2_DYN_SMEM);
    }
    cudaStream_t st = cudaStreamPerThread;
    int NB = (N + num_sms - 1) / num_sms;
    if (NB > MAXNB) NB = MAXNB;
    const int nbins = (N + NB - 1) / NB;
    const uint32_t magic = (uint32_t)(((1u << 24) + NB - 1) / NB);
    const int P = num_sms;
    int chunk = (E + P - 1) / P;
    if (chunk > P1_CHUNK) chunk = P1_CHUNK;
    if (chunk < 1) chunk = 1;
    const int n_row_tiles = (N + K1_ROWS - 1) / K1_ROWS;
    k1_kernel<<<P + 2 * n_row_tiles, 256, 65536, st>>>(x, e_attr, src, dst, w_a, w_b, w_u, w_v,
                                                        N, E, n_row_tiles, P, chunk, NB, nbins, magic);

    cudaLaunchConfig_t cfg = {};
    cfg.gridDim = dim3(nbins);
    cfg.blockDim = dim3(K2_THREADS);
    cfg.dynamicSmemBytes = K2_DYN_SMEM;
    cfg.stream = st;
    cudaLaunchAttribute at[1];
    at[0].id = cudaLaunchAttributeProgrammaticStreamSerialization;
    at[0].val.programmaticStreamSerializationAllowed = 1;
    cfg.attrs = at; cfg.numAttrs = 1;
    cudaLaunchKernelEx(&cfg, k2_kernel, x, w_c, out, N, NB);
}
```

```cpp
#include <cuda_runtime.h>
#include <cuda_bf16.h>
#include <stdint.h>

#define D_FEAT 128
#define MAX_N 16384
#define MAX_E (1 << 20)
#define LOG2E 1.4426950408889634f

#define MAXBINS 256
#define MAXNB 128
#define BINCAP 3072
__device__ uint4 g_T[(MAX_N + 1) * 32];
__device__ uint4 g_AU[MAX_N * 32];
__device__ int g_bin_cnt[MAXBINS];
__device__ uint2 g_bins[MAXBINS * BINCAP];
__device__ int g_ovf[MAX_E];
__device__ int g_ovf_cnt;
__device__ int g_done;

__device__ __forceinline__ float ex2_approx(float x) {
    float y; asm("ex2.approx.ftz.f32 %0, %1;" : "=f"(y) : "f"(x)); return y;
}
__device__ __forceinline__ float rcp_approx(float x) {
    float y; asm("rcp.approx.ftz.f32 %0, %1;" : "=f"(y) : "f"(x)); return y;
}
__device__ __forceinline__ uint32_t pack_bf16(float lo, float hi) {
    __nv_bfloat162 t = __floats2bfloat162_rn(lo, hi);
    return *reinterpret_cast<uint32_t*>(&t);
}
__device__ __forceinline__ float bf_lo(uint32_t v) { return __uint_as_float(v << 16); }
__device__ __forceinline__ float bf_hi(uint32_t v) { return __uint_as_float(v & 0xffff0000u); }
__device__ __forceinline__ float round_bf16(float x) { return __bfloat162float(__float2bfloat16_rn(x)); }

__device__ __forceinline__ void mma_bf16(float c[4], uint32_t a0, uint32_t a1, uint32_t a2, uint32_t a3,
                                         uint32_t b0, uint32_t b1) {
    asm volatile("mma.sync.aligned.m16n8k16.row.col.f32.bf16.bf16.f32 "
                 "{%0,%1,%2,%3}, {%4,%5,%6,%7}, {%8,%9}, {%0,%1,%2,%3};"
                 : "+f"(c[0]), "+f"(c[1]), "+f"(c[2]), "+f"(c[3])
                 : "r"(a0), "r"(a1), "r"(a2), "r"(a3), "r"(b0), "r"(b1));
}
__device__ __forceinline__ void ldmatrix_x4_trans(uint32_t& r0, uint32_t& r1, uint32_t& r2, uint32_t& r3, uint32_t addr) {
    asm volatile("ldmatrix.sync.aligned.m8n8.x4.trans.shared.b16 {%0,%1,%2,%3}, [%4];"
                 : "=r"(r0), "=r"(r1), "=r"(r2), "=r"(r3) : "r"(addr));
}

#define K1_ROWS 128
#define P1_EPT 10
#define P1_CHUNK (256 * P1_EPT)

__global__ void __launch_bounds__(256) k1_kernel(
    const __nv_bfloat16* __restrict__ x, const __nv_bfloat16* __restrict__ e_attr,
    const int* __restrict__ src, const int* __restrict__ dst,
    const __nv_bfloat16* __restrict__ w_a, const __nv_bfloat16* __restrict__ w_b,
    const __nv_bfloat16* __restrict__ w_u, const __nv_bfloat16* __restrict__ w_v,
    int N, int E, int n_row_tiles, int P, int chunk, int NB, int nbins, uint32_t magic)
{
    extern __shared__ __align__(128) uint8_t smem[];
    asm volatile("griddepcontrol.launch_dependents;");

    const int tid = threadIdx.x;
    const int warp = tid >> 5, lane = tid & 31;

    if ((int)blockIdx.x < P) {
        if (blockIdx.x == 0 && tid < 32) g_T[(size_t)N * 32 + tid] = make_uint4(0xff80ff80u, 0xff80ff80u, 0u, 0u);
        int* hist = reinterpret_cast<int*>(smem);
        int* loff = hist + MAXBINS;
        int* gbase = loff + MAXBINS;
        uint2* sorted = reinterpret_cast<uint2*>(smem + 3 * MAXBINS * 4);
        for (int beg = blockIdx.x * chunk; beg < E; beg += P * chunk) {
            const int end = min(E, beg + chunk);
            int d[P1_EPT]; uint32_t rec[P1_EPT]; int rk[P1_EPT]; int bn[P1_EPT];
            #pragma unroll
            for (int i = 0; i < P1_EPT; i++) {
                int e = beg + i * 256 + tid;
                d[i] = -1;
                if (e < end) {
                    d[i] = __ldg(dst + e);
                    uint32_t s = (uint32_t)__ldg(src + e);
                    uint32_t ev = (uint32_t)__ldg(reinterpret_cast<const unsigned short*>(e_attr) + e);
                    rec[i] = (ev << 16) | s;
                }
            }
            hist[tid] = 0;
            __syncthreads();
            #pragma unroll
            for (int i = 0; i < P1_EPT; i++) {
                if (d[i] >= 0) {
                    bn[i] = (int)(((uint64_t)(uint32_t)d[i] * magic) >> 24);
                    rk[i] = atomicAdd(&hist[bn[i]], 1);
                }
            }
            __syncthreads();
            {
                int h = hist[tid];
                if (tid < nbins && h > 0) gbase[tid] = atomicAdd(&g_bin_cnt[tid], h);
                if (warp == 0) {
                    int v[8]; int sum = 0;
                    #pragma unroll
                    for (int i = 0; i < 8; i++) { v[i] = hist[lane * 8 + i]; sum += v[i]; }
                    int inc = sum;
                    #pragma unroll
                    for (int o = 1; o < 32; o <<= 1) { int t = __shfl_up_sync(0xffffffffu, inc, o); if (lane >= o) inc += t; }
                    int run = inc - sum;
                    #pragma unroll
                    for (int i = 0; i < 8; i++) { loff[lane * 8 + i] = run; run += v[i]; }
                }
            }
            __syncthreads();
            #pragma unroll
            for (int i = 0; i < P1_EPT; i++) {
                if (d[i] >= 0) sorted[loff[bn[i]] + rk[i]] = make_uint2(rec[i], (uint32_t)d[i]);
            }
            __syncthreads();
            const int cnt = end - beg;
            for (int i = tid; i < cnt; i += 256) {
                uint2 r = sorted[i];
                int b = (int)(((uint64_t)r.y * magic) >> 24);
                int pos = gbase[b] + (i - loff[b]);
                if (pos < BINCAP) {
                    g_bins[b * BINCAP + pos] = make_uint2(r.x, r.y - (uint32_t)(b * NB));
                } else {
                    int p = atomicAdd(&g_ovf_cnt, 2);
                    g_ovf[p] = (int)r.y; g_ovf[p + 1] = (int)r.x;
                }
            }
            __syncthreads();
        }
        return;
    }

    const int gb = blockIdx.x - P;
    const int type = gb >= n_row_tiles ? 1 : 0;
    const int tile = type ? gb - n_row_tiles : gb;

    uint4 X0[4], X1[4];
    const int q = lane & 3;
    const int r0 = tile * K1_ROWS + warp * 16 + (lane >> 2);
    {
        const uint4* xr0 = reinterpret_cast<const uint4*>(x) + (size_t)r0 * 16 + q;
        const uint4* xr1 = xr0 + 8 * 16;
        #pragma unroll
        for (int c = 0; c < 4; c++) {
            X0[c] = (r0 < N) ? __ldg(xr0 + c * 4) : make_uint4(0, 0, 0, 0);
            X1[c] = (r0 + 8 < N) ? __ldg(xr1 + c * 4) : make_uint4(0, 0, 0, 0);
        }
    }
    {
        const uint4* W0 = reinterpret_cast<const uint4*>(type ? w_a : w_b);
        const uint4* W1 = reinterpret_cast<const uint4*>(type ? w_u : w_v);
        #pragma unroll
        for (int it = 0; it < 8; it++) {
            int u = it * 256 + tid;
            int mtx = u >> 10, k = (u >> 3) & 127, m = u & 7;
            const uint4* p = (mtx ? W1 : W0) + k * 16 + m * 2;
            uint4 lo = __ldg(p), hi = __ldg(p + 1);
            uint4 c0 = make_uint4(lo.x, lo.z, hi.x, hi.z);
            uint4 c1 = make_uint4(lo.y, lo.w, hi.y, hi.w);
            int f = (((k >> 3) & 3) << 1) | (k & 1);
            uint8_t* row = smem + mtx * 32768 + k * 256;
            *reinterpret_cast<uint4*>(row + (((2 * m) ^ f) << 4)) = c0;
            *reinterpret_cast<uint4*>(row + (((2 * m + 1) ^ f) << 4)) = c1;
        }
    }
    __syncthreads();
    {
        const uint32_t sbase = (uint32_t)__cvta_generic_to_shared(smem);
        const int mi = lane >> 3, ii = lane & 7;
        const int hh = mi & 1, tj = mi >> 1;
        uint4* outp = (type ? g_AU : g_T);
        #pragma unroll 1
        for (int m = 0; m < 8; m++) {
            float acc[4][4];
            #pragma unroll
            for (int t = 0; t < 4; t++) { acc[t][0] = acc[t][1] = acc[t][2] = acc[t][3] = 0.f; }
            #pragma unroll
            for (int c = 0; c < 4; c++) {
                #pragma unroll
                for (int s = 0; s < 2; s++) {
                    int k = 32 * c + 8 * (ii >> 1) + 4 * s + 2 * hh + (ii & 1);
                    int f = (((k >> 3) & 3) << 1) | (k & 1);
                    uint32_t addr = sbase + k * 256 + (((2 * m + tj) ^ f) << 4);
                    uint32_t b0, b1, b2, b3, h0, h1, h2, h3;
                    ldmatrix_x4_trans(b0, b1, b2, b3, addr);
                    ldmatrix_x4_trans(h0, h1, h2, h3, addr + 32768);
                    uint32_t a0 = s ? X0[c].z : X0[c].x, a1 = s ? X1[c].z : X1[c].x;
                    uint32_t a2 = s ? X0[c].w : X0[c].y, a3 = s ? X1[c].w : X1[c].y;
                    mma_bf16(acc[0], a0, a1, a2, a3, b0, b1);
                    mma_bf16(acc[1], a0, a1, a2, a3, b2, b3);
                    mma_bf16(acc[2], a0, a1, a2, a3, h0, h1);
                    mma_bf16(acc[3], a0, a1, a2, a3, h2, h3);
                }
            }
            uint4 o0 = make_uint4(pack_bf16(acc[0][0], acc[0][1]), pack_bf16(acc[1][0], acc[1][1]),
                                  pack_bf16(acc[2][0], acc[2][1]), pack_bf16(acc[3][0], acc[3][1]));
            uint4 o1 = make_uint4(pack_bf16(acc[0][2], acc[0][3]), pack_bf16(acc[1][2], acc[1][3]),
                                  pack_bf16(acc[2][2], acc[2][3]), pack_bf16(acc[3][2], acc[3][3]));
            if (r0 < N) outp[(size_t)r0 * 32 + 4 * m + q] = o0;
            if (r0 + 8 < N) outp[(size_t)(r0 + 8) * 32 + 4 * m + q] = o1;
        }
    }
}

__device__ __forceinline__ void edge_accum(const uint4 v, const float e, const float a[4], const float cc[4],
                                           float num[4], float den[4]) {
    float y0 = fmaf(bf_lo(v.x), -LOG2E, fmaf(e, cc[0], a[0]));
    float y1 = fmaf(bf_hi(v.x), -LOG2E, fmaf(e, cc[1], a[1]));
    float y2 = fmaf(bf_lo(v.y), -LOG2E, fmaf(e, cc[2], a[2]));
    float y3 = fmaf(bf_hi(v.y), -LOG2E, fmaf(e, cc[3], a[3]));
    float s0 = rcp_approx(1.f + ex2_approx(y0));
    float s1 = rcp_approx(1.f + ex2_approx(y1));
    float s2 = rcp_approx(1.f + ex2_approx(y2));
    float s3 = rcp_approx(1.f + ex2_approx(y3));
    den[0] += s0; den[1] += s1; den[2] += s2; den[3] += s3;
    num[0] = fmaf(s0, bf_lo(v.z), num[0]);
    num[1] = fmaf(s1, bf_hi(v.z), num[1]);
    num[2] = fmaf(s2, bf_lo(v.w), num[2]);
    num[3] = fmaf(s3, bf_hi(v.w), num[3]);
}

#define K2_THREADS 1024
#define K2_STAGES 3
#define K2_RPT (BINCAP / K2_THREADS)
#define K2_NW (K2_THREADS / 32)
#define SORT_WORDS (BINCAP + 4 * MAXNB)
#define K2_DYN_SMEM (K2_NW * K2_STAGES * 2048)

__device__ __forceinline__ void cp_async16(uint32_t saddr, const void* g) {
    asm volatile("cp.async.cg.shared.global [%0], [%1], 16;" :: "r"(saddr), "l"(g) : "memory");
}
__device__ __forceinline__ void cp_async_commit() { asm volatile("cp.async.commit_group;" ::: "memory"); }
template<int NPEND> __device__ __forceinline__ void cp_async_wait() { asm volatile("cp.async.wait_group %0;" :: "n"(NPEND) : "memory"); }

__global__ void __launch_bounds__(K2_THREADS, 1) k2_kernel(
    const __nv_bfloat16* __restrict__ x, const __nv_bfloat16* __restrict__ w_c,
    __nv_bfloat16* __restrict__ out, int N, int NB)
{
    extern __shared__ __align__(128) uint8_t dsm[];
    __shared__ __align__(16) uint32_t s_sorted[SORT_WORDS];
    __shared__ int s_hist[MAXNB];
    __shared__ int s_off[MAXNB + 1];

    const int tid = threadIdx.x;
    const int lane = tid & 31, warp = tid >> 5;
    const int bin = blockIdx.x;
    const int node0 = bin * NB;
    const int nn = min(NB, N - node0);

    const uint2 wc = __ldg(reinterpret_cast<const uint2*>(w_c) + lane);
    const float cc[4] = { -LOG2E * bf_lo(wc.x), -LOG2E * bf_hi(wc.x), -LOG2E * bf_lo(wc.y), -LOG2E * bf_hi(wc.y) };
    if (tid < MAXNB) s_hist[tid] = 0;
    for (int i = tid; i < SORT_WORDS; i += K2_THREADS) s_sorted[i] = (uint32_t)N;
    __syncthreads();

    asm volatile("griddepcontrol.wait;" ::: "memory");

    const int cnt = min(g_bin_cnt[bin], BINCAP);
    const int ovf_n = g_ovf_cnt;
    {
        uint2 r[K2_RPT]; int rk[K2_RPT];
        #pragma unroll
        for (int i = 0; i < K2_RPT; i++) {
            int idx = i * K2_THREADS + tid;
            if (idx < cnt) r[i] = g_bins[bin * BINCAP + idx];
        }
        #pragma unroll
        for (int i = 0; i < K2_RPT; i++) {
            int idx = i * K2_THREADS + tid;
            if (idx < cnt) rk[i] = atomicAdd(&s_hist[r[i].y], 1);
        }
        __syncthreads();
        if (warp == 0) {
            int v[4]; int sum = 0;
            #pragma unroll
            for (int i = 0; i < 4; i++) { v[i] = (s_hist[lane * 4 + i] + 3) & ~3; sum += v[i]; }
            int inc = sum;
            #pragma unroll
            for (int o = 1; o < 32; o <<= 1) { int t = __shfl_up_sync(0xffffffffu, inc, o); if (lane >= o) inc += t; }
            int run = inc - sum;
            #pragma unroll
            for (int i = 0; i < 4; i++) { s_off[lane * 4 + i] = run; run += v[i]; }
            if (lane == 31) s_off[MAXNB] = run;
        }
        if (tid == 32) g_bin_cnt[bin] = 0;
        __syncthreads();
        #pragma unroll
        for (int i = 0; i < K2_RPT; i++) {
            int idx = i * K2_THREADS + tid;
            if (idx < cnt) s_sorted[s_off[r[i].y] + rk[i]] = r[i].x;
        }
        __syncthreads();
    }

    const char* Tl = reinterpret_cast<const char*>(g_T) + lane * 16;
    int ln, ln_end;
    {
        const int total = s_off[MAXNB];
        const int lo = (int)(((long long)total * warp) / K2_NW);
        const int hi = (int)(((long long)total * (warp + 1)) / K2_NW);
        int c_lo = 0, c_hi = 0;
        #pragma unroll
        for (int i = 0; i < 4; i++) {
            int node = i * 32 + lane;
            int o = (node < nn) ? s_off[node] : 0x7fffffff;
            c_lo += __popc(__ballot_sync(0xffffffffu, o < lo));
            c_hi += __popc(__ballot_sync(0xffffffffu, o < hi));
        }
        ln = c_lo; ln_end = (warp == K2_NW - 1) ? nn : c_hi;
        if (warp == 0) ln = 0;
    }
    if (ln < ln_end) {
        int g = s_off[ln] >> 2;
        const int g_end = s_off[ln_end] >> 2;
        const uint32_t ring = (uint32_t)__cvta_generic_to_shared(dsm) + warp * (K2_STAGES * 2048) + lane * 16;
        const uint8_t* ring_p = dsm + warp * (K2_STAGES * 2048) + lane * 16;

        #define ISSUE(GI, ST) { \
            if ((GI) < g_end) { \
                const uint4 t_ = *reinterpret_cast<const uint4*>(s_sorted + 4 * (GI)); \
                cp_async16(ring + (ST) * 2048,        Tl + (size_t)(t_.x & 0xffffu) * 512); \
                cp_async16(ring + (ST) * 2048 + 512,  Tl + (size_t)(t_.y & 0xffffu) * 512); \
                cp_async16(ring + (ST) * 2048 + 1024, Tl + (size_t)(t_.z & 0xffffu) * 512); \
                cp_async16(ring + (ST) * 2048 + 1536, Tl + (size_t)(t_.w & 0xffffu) * 512); \
            } \
            cp_async_commit(); }
        #pragma unroll
        for (int st = 0; st < K2_STAGES - 1; st++) ISSUE(g + st, st);

        uint4 au = g_AU[(size_t)(node0 + ln) * 32 + lane];
        uint2 xv = __ldg(reinterpret_cast<const uint2*>(x) + (size_t)(node0 + ln) * 32 + lane);
        float a[4] = { -LOG2E * bf_lo(au.x), -LOG2E * bf_hi(au.x), -LOG2E * bf_lo(au.y), -LOG2E * bf_hi(au.y) };
        float num[4] = {0.f, 0.f, 0.f, 0.f}, den[4] = {0.f, 0.f, 0.f, 0.f};
        int node_end = s_off[ln + 1] >> 2;
        int st_c = 0;
        int st_p = K2_STAGES - 1;

        while (true) {
            while (g == node_end) {
                const int n = node0 + ln;
                if (ovf_n != 0) {
                    for (int base = 0; base < ovf_n; base += 64) {
                        int i2 = base + 2 * lane;
                        int od = (i2 < ovf_n) ? g_ovf[i2] : -1;
                        uint32_t orec = (i2 < ovf_n) ? (uint32_t)g_ovf[i2 + 1] : 0u;
                        unsigned msk = __ballot_sync(0xffffffffu, od == n);
                        while (msk) {
                            int l = __ffs(msk) - 1; msk &= msk - 1;
                            uint32_t r = __shfl_sync(0xffffffffu, orec, l);
                            uint4 v = __ldg(reinterpret_cast<const uint4*>(Tl + (size_t)(r & 0xffffu) * 512));
                            edge_accum(v, bf_hi(r), a, cc, num, den);
                        }
                    }
                }
                {
                    const float u4[4] = { bf_lo(au.z), bf_hi(au.z), bf_lo(au.w), bf_hi(au.w) };
                    const float x4[4] = { bf_lo(xv.x), bf_hi(xv.x), bf_lo(xv.y), bf_hi(xv.y) };
                    float o[4];
                    #pragma unroll
                    for (int i = 0; i < 4; i++) {
                        float agg = round_bf16(__fdividef(num[i], den[i] + 1e-6f));
                        float z = round_bf16(u4[i] + agg);
                        float rz = (z > 0.f) ? z : 0.f * z;
                        o[i] = x4[i] + rz;
                        num[i] = 0.f; den[i] = 0.f;
                    }
                    reinterpret_cast<uint2*>(out)[(size_t)n * 32 + lane] = make_uint2(pack_bf16(o[0], o[1]), pack_bf16(o[2], o[3]));
                }
                ln++;
                if (ln >= ln_end) goto done;
                au = g_AU[(size_t)(node0 + ln) * 32 + lane];
                xv = __ldg(reinterpret_cast<const uint2*>(x) + (size_t)(node0 + ln) * 32 + lane);
                a[0] = -LOG2E * bf_lo(au.x); a[1] = -LOG2E * bf_hi(au.x); a[2] = -LOG2E * bf_lo(au.y); a[3] = -LOG2E * bf_hi(au.y);
                node_end = s_off[ln + 1] >> 2;
            }
            ISSUE(g + K2_STAGES - 1, st_p);
            cp_async_wait<K2_STAGES - 1>();
            {
                const uint4 t = *reinterpret_cast<const uint4*>(s_sorted + 4 * g);
                const uint8_t* sp = ring_p + st_c * 2048;
                const uint4 v0 = *reinterpret_cast<const uint4*>(sp);
                const uint4 v1 = *reinterpret_cast<const uint4*>(sp + 512);
                const uint4 v2 = *reinterpret_cast<const uint4*>(sp + 1024);
                const uint4 v3 = *reinterpret_cast<const uint4*>(sp + 1536);
                edge_accum(v0, bf_hi(t.x), a, cc, num, den);
                edge_accum(v1, bf_hi(t.y), a, cc, num, den);
                edge_accum(v2, bf_hi(t.z), a, cc, num, den);
                edge_accum(v3, bf_hi(t.w), a, cc, num, den);
            }
            st_p = st_c;
            st_c = (st_c + 1 == K2_STAGES) ? 0 : st_c + 1;
            g++;
        }
        done:;
    }
    if (ovf_n != 0) {
        __syncthreads();
        if (tid == 0) {
            __threadfence();
            int t = atomicAdd(&g_done, 1);
            if (t == (int)gridDim.x - 1) { g_done = 0; __threadfence(); g_ovf_cnt = 0; }
        }
    }
}

extern "C" void kernel_launch(void* const* d_in, const int* in_sizes, int n_in,
                              void* d_out, int out_size) {
    const __nv_bfloat16* x      = (const __nv_bfloat16*)d_in[0];
    const __nv_bfloat16* e_attr = (const __nv_bfloat16*)d_in[1];
    const int* src = (const int*)d_in[2];
    const int* dst = (const int*)d_in[3];
    const __nv_bfloat16* w_a = (const __nv_bfloat16*)d_in[4];
    const __nv_bfloat16* w_b = (const __nv_bfloat16*)d_in[5];
    const __nv_bfloat16* w_c = (const __nv_bfloat16*)d_in[6];
    const __nv_bfloat16* w_u = (const __nv_bfloat16*)d_in[7];
    const __nv_bfloat16* w_v = (const __nv_bfloat16*)d_in[8];
    __nv_bfloat16* out = (__nv_bfloat16*)d_out;
    const int N = in_sizes[0] / D_FEAT;
    const int E = in_sizes[2];
    if (N > MAX_N || 2 * E > MAX_E || N <= 0) return;

    static int num_sms = 0;
    if (num_sms == 0) {
        int dev = 0;
        cudaGetDevice(&dev);
        cudaDeviceGetAttribute(&num_sms, cudaDevAttrMultiProcessorCount, dev);
        if (num_sms <= 0 || num_sms > MAXBINS) num_sms = 132;
        cudaFuncSetAttribute(k1_kernel, cudaFuncAttributeMaxDynamicSharedMemorySize, 65536);
        cudaFuncSetAttribute(k2_kernel, cudaFuncAttributeMaxDynamicSharedMemorySize, K2_DYN_SMEM);
    }
    cudaStream_t st = cudaStreamPerThread;
    int NB = (N + num_sms - 1) / num_sms;
    if (NB > MAXNB) NB = MAXNB;
    const int nbins = (N + NB - 1) / NB;
    const uint32_t magic = (uint32_t)(((1u << 24) + NB - 1) / NB);
    const int P = num_sms;
    int chunk = (E + P - 1) / P;
    if (chunk > P1_CHUNK) chunk = P1_CHUNK;
    if (chunk < 1) chunk = 1;
    const int n_row_tiles = (N + K1_ROWS - 1) / K1_ROWS;
    k1_kernel<<<P + 2 * n_row_tiles, 256, 65536, st>>>(x, e_attr, src, dst, w_a, w_b, w_u, w_v,
                                                        N, E, n_row_tiles, P, chunk, NB, nbins, magic);

    cudaLaunchConfig_t cfg = {};
    cfg.gridDim = dim3(nbins);
    cfg.blockDim = dim3(K2_THREADS);
    cfg.dynamicSmemBytes = K2_DYN_SMEM;
    cfg.stream = st;
    cudaLaunchAttribute at[1];
    at[0].id = cudaLaunchAttributeProgrammaticStreamSerialization;
    at[0].val.programmaticStreamSerializationAllowed = 1;
    cfg.attrs = at; cfg.numAttrs = 1;
    cudaLaunchKernelEx(&cfg, k2_kernel, x, w_c, out, N, NB);
}
```

```cpp
#include <cuda_runtime.h>
#include <cuda_bf16.h>
#include <stdint.h>

#define D_FEAT 128
#define MAX_N 16384
#define MAX_E (1 << 20)
#define LOG2E 1.4426950408889634f

#define MAXBINS 256
#define MAXNB 128
#define BINCAP 3072
__device__ uint4 g_T[(MAX_N + 1) * 32];
__device__ int g_bin_cnt[MAXBINS];
__device__ uint2 g_bins[MAXBINS * BINCAP];
__device__ int g_ovf[MAX_E];
__device__ int g_ovf_cnt;
__device__ int g_done;

__device__ __forceinline__ float ex2_approx(float x) {
    float y; asm("ex2.approx.ftz.f32 %0, %1;" : "=f"(y) : "f"(x)); return y;
}
__device__ __forceinline__ float rcp_approx(float x) {
    float y; asm("rcp.approx.ftz.f32 %0, %1;" : "=f"(y) : "f"(x)); return y;
}
__device__ __forceinline__ uint32_t pack_bf16(float lo, float hi) {
    __nv_bfloat162 t = __floats2bfloat162_rn(lo, hi);
    return *reinterpret_cast<uint32_t*>(&t);
}
__device__ __forceinline__ float bf_lo(uint32_t v) { return __uint_as_float(v << 16); }
__device__ __forceinline__ float bf_hi(uint32_t v) { return __uint_as_float(v & 0xffff0000u); }
__device__ __forceinline__ float round_bf16(float x) { return __bfloat162float(__float2bfloat16_rn(x)); }

__device__ __forceinline__ void mma_bf16(float c[4], uint32_t a0, uint32_t a1, uint32_t a2, uint32_t a3,
                                         uint32_t b0, uint32_t b1) {
    asm volatile("mma.sync.aligned.m16n8k16.row.col.f32.bf16.bf16.f32 "
                 "{%0,%1,%2,%3}, {%4,%5,%6,%7}, {%8,%9}, {%0,%1,%2,%3};"
                 : "+f"(c[0]), "+f"(c[1]), "+f"(c[2]), "+f"(c[3])
                 : "r"(a0), "r"(a1), "r"(a2), "r"(a3), "r"(b0), "r"(b1));
}
__device__ __forceinline__ void ldmatrix_x4_trans(uint32_t& r0, uint32_t& r1, uint32_t& r2, uint32_t& r3, uint32_t addr) {
    asm volatile("ldmatrix.sync.aligned.m8n8.x4.trans.shared.b16 {%0,%1,%2,%3}, [%4];"
                 : "=r"(r0), "=r"(r1), "=r"(r2), "=r"(r3) : "r"(addr));
}

__device__ __forceinline__ void stage_weights(uint8_t* smem, const __nv_bfloat16* w0, const __nv_bfloat16* w1,
                                              int tid, int nthreads) {
    const uint4* W0 = reinterpret_cast<const uint4*>(w0);
    const uint4* W1 = reinterpret_cast<const uint4*>(w1);
    for (int u = tid; u < 2048; u += nthreads) {
        int mtx = u >> 10, k = (u >> 3) & 127, m = u & 7;
        const uint4* p = (mtx ? W1 : W0) + k * 16 + m * 2;
        uint4 lo = __ldg(p), hi = __ldg(p + 1);
        uint4 c0 = make_uint4(lo.x, lo.z, hi.x, hi.z);
        uint4 c1 = make_uint4(lo.y, lo.w, hi.y, hi.w);
        int f = (((k >> 3) & 3) << 1) | (k & 1);
        uint8_t* row = smem + mtx * 32768 + k * 256;
        *reinterpret_cast<uint4*>(row + (((2 * m) ^ f) << 4)) = c0;
        *reinterpret_cast<uint4*>(row + (((2 * m + 1) ^ f) << 4)) = c1;
    }
}

__device__ __forceinline__ void load_x_frags(uint4 X0[4], uint4 X1[4], const __nv_bfloat16* x, int r0, int N, int q) {
    const uint4* xr0 = reinterpret_cast<const uint4*>(x) + (size_t)r0 * 16 + q;
    const uint4* xr1 = xr0 + 8 * 16;
    #pragma unroll
    for (int c = 0; c < 4; c++) {
        X0[c] = (r0 < N) ? __ldg(xr0 + c * 4) : make_uint4(0, 0, 0, 0);
        X1[c] = (r0 + 8 < N) ? __ldg(xr1 + c * 4) : make_uint4(0, 0, 0, 0);
    }
}

__device__ __forceinline__ void gemm_group(const uint4 X0[4], const uint4 X1[4], uint32_t sbase, int m, int lane,
                                           uint4& o0, uint4& o1) {
    const int mi = lane >> 3, ii = lane & 7;
    const int hh = mi & 1, tj = mi >> 1;
    float acc[4][4];
    #pragma unroll
    for (int t = 0; t < 4; t++) { acc[t][0] = acc[t][1] = acc[t][2] = acc[t][3] = 0.f; }
    #pragma unroll
    for (int c = 0; c < 4; c++) {
        #pragma unroll
        for (int s = 0; s < 2; s++) {
            int k = 32 * c + 8 * (ii >> 1) + 4 * s + 2 * hh + (ii & 1);
            int f = (((k >> 3) & 3) << 1) | (k & 1);
            uint32_t addr = sbase + k * 256 + (((2 * m + tj) ^ f) << 4);
            uint32_t b0, b1, b2, b3, h0, h1, h2, h3;
            ldmatrix_x4_trans(b0, b1, b2, b3, addr);
            ldmatrix_x4_trans(h0, h1, h2, h3, addr + 32768);
            uint32_t a0 = s ? X0[c].z : X0[c].x, a1 = s ? X1[c].z : X1[c].x;
            uint32_t a2 = s ? X0[c].w : X0[c].y, a3 = s ? X1[c].w : X1[c].y;
            mma_bf16(acc[0], a0, a1, a2, a3, b0, b1);
            mma_bf16(acc[1], a0, a1, a2, a3, b2, b3);
            mma_bf16(acc[2], a0, a1, a2, a3, h0, h1);
            mma_bf16(acc[3], a0, a1, a2, a3, h2, h3);
        }
    }
    o0 = make_uint4(pack_bf16(acc[0][0], acc[0][1]), pack_bf16(acc[1][0], acc[1][1]),
                    pack_bf16(acc[2][0], acc[2][1]), pack_bf16(acc[3][0], acc[3][1]));
    o1 = make_uint4(pack_bf16(acc[0][2], acc[0][3]), pack_bf16(acc[1][2], acc[1][3]),
                    pack_bf16(acc[2][2], acc[2][3]), pack_bf16(acc[3][2], acc[3][3]));
}

#define K1_GW 10
#define K1_THREADS ((K1_GW + 8) * 32)
#define P1_EPT 10
#define P1_CHUNK (256 * P1_EPT)
#define K1_SMEM (65536 + 3 * MAXBINS * 4 + P1_CHUNK * 8)

__device__ __forceinline__ void p1_bar() { asm volatile("bar.sync 1, 256;" ::: "memory"); }

__global__ void __launch_bounds__(K1_THREADS, 1) k1_kernel(
    const __nv_bfloat16* __restrict__ x, const __nv_bfloat16* __restrict__ e_attr,
    const int* __restrict__ src, const int* __restrict__ dst,
    const __nv_bfloat16* __restrict__ w_b, const __nv_bfloat16* __restrict__ w_v,
    int N, int E, int chunk, int NB, int nbins, uint32_t magic)
{
    extern __shared__ __align__(128) uint8_t smem[];
    asm volatile("griddepcontrol.launch_dependents;");

    const int warp = threadIdx.x >> 5, lane = threadIdx.x & 31;

    if (warp >= K1_GW) {
        const int tid = threadIdx.x - K1_GW * 32;
        if (blockIdx.x == 0 && tid < 32)
            g_T[(size_t)N * 32 + tid] = make_uint4(0xff80ff80u, 0xff80ff80u, 0u, 0u);
        int* hist = reinterpret_cast<int*>(smem + 65536);
        int* loff = hist + MAXBINS;
        int* gbase = loff + MAXBINS;
        uint2* sorted = reinterpret_cast<uint2*>(smem + 65536 + 3 * MAXBINS * 4);
        for (int beg = blockIdx.x * chunk; beg < E; beg += gridDim.x * chunk) {
            const int end = min(E, beg + chunk);
            int d[P1_EPT]; uint32_t rec[P1_EPT]; int rk[P1_EPT]; int bn[P1_EPT];
            #pragma unroll
            for (int i = 0; i < P1_EPT; i++) {
                int e = beg + i * 256 + tid;
                d[i] = -1;
                if (e < end) {
                    d[i] = __ldg(dst + e);
                    uint32_t s = (uint32_t)__ldg(src + e);
                    uint32_t ev = (uint32_t)__ldg(reinterpret_cast<const unsigned short*>(e_attr) + e);
                    rec[i] = (ev << 16) | s;
                }
            }
            hist[tid] = 0;
            p1_bar();
            #pragma unroll
            for (int i = 0; i < P1_EPT; i++) {
                if (d[i] >= 0) {
                    bn[i] = (int)(((uint64_t)(uint32_t)d[i] * magic) >> 24);
                    rk[i] = atomicAdd(&hist[bn[i]], 1);
                }
            }
            p1_bar();
            {
                int h = hist[tid];
                if (tid < nbins && h > 0) gbase[tid] = atomicAdd(&g_bin_cnt[tid], h);
                if (tid < 32) {
                    int v[8]; int sum = 0;
                    #pragma unroll
                    for (int i = 0; i < 8; i++) { v[i] = hist[lane * 8 + i]; sum += v[i]; }
                    int inc = sum;
                    #pragma unroll
                    for (int o = 1; o < 32; o <<= 1) { int t = __shfl_up_sync(0xffffffffu, inc, o); if (lane >= o) inc += t; }
                    int run = inc - sum;
                    #pragma unroll
                    for (int i = 0; i < 8; i++) { loff[lane * 8 + i] = run; run += v[i]; }
                }
            }
            p1_bar();
            #pragma unroll
            for (int i = 0; i < P1_EPT; i++) {
                if (d[i] >= 0) sorted[loff[bn[i]] + rk[i]] = make_uint2(rec[i], (uint32_t)d[i]);
            }
            p1_bar();
            const int cnt = end - beg;
            for (int i = tid; i < cnt; i += 256) {
                uint2 r = sorted[i];
                int b = (int)(((uint64_t)r.y * magic) >> 24);
                int pos = gbase[b] + (i - loff[b]);
                if (pos < BINCAP) {
                    g_bins[b * BINCAP + pos] = make_uint2(r.x, r.y - (uint32_t)(b * NB));
                } else {
                    int p = atomicAdd(&g_ovf_cnt, 2);
                    g_ovf[p] = (int)r.y; g_ovf[p + 1] = (int)r.x;
                }
            }
            p1_bar();
        }
        return;
    }

    const int q = lane & 3;
    const int n_tasks = ((N + 15) >> 4) * 2;
    int task = blockIdx.x * K1_GW + warp;
    uint4 X0[4], X1[4];
    int r0 = (task >> 1) * 16 + (lane >> 2);
    if (task < n_tasks) load_x_frags(X0, X1, x, r0, N, q);
    stage_weights(smem, w_b, w_v, threadIdx.x, K1_GW * 32);
    asm volatile("bar.sync 2, %0;" :: "n"(K1_GW * 32) : "memory");
    const uint32_t sbase = (uint32_t)__cvta_generic_to_shared(smem);
    while (task < n_tasks) {
        const int m0 = (task & 1) * 4;
        #pragma unroll 2
        for (int m = m0; m < m0 + 4; m++) {
            uint4 o0, o1;
            gemm_group(X0, X1, sbase, m, lane, o0, o1);
            if (r0 < N) g_T[(size_t)r0 * 32 + 4 * m + q] = o0;
            if (r0 + 8 < N) g_T[(size_t)(r0 + 8) * 32 + 4 * m + q] = o1;
        }
        task += gridDim.x * K1_GW;
        if (task < n_tasks) {
            r0 = (task >> 1) * 16 + (lane >> 2);
            load_x_frags(X0, X1, x, r0, N, q);
        }
    }
}

__device__ __forceinline__ void edge_accum(const uint4 v, const float e, const float a[4], const float cc[4],
                                           float num[4], float den[4]) {
    float y0 = fmaf(bf_lo(v.x), -LOG2E, fmaf(e, cc[0], a[0]));
    float y1 = fmaf(bf_hi(v.x), -LOG2E, fmaf(e, cc[1], a[1]));
    float y2 = fmaf(bf_lo(v.y), -LOG2E, fmaf(e, cc[2], a[2]));
    float y3 = fmaf(bf_hi(v.y), -LOG2E, fmaf(e, cc[3], a[3]));
    float s0 = rcp_approx(1.f + ex2_approx(y0));
    float s1 = rcp_approx(1.f + ex2_approx(y1));
    float s2 = rcp_approx(1.f + ex2_approx(y2));
    float s3 = rcp_approx(1.f + ex2_approx(y3));
    den[0] += s0; den[1] += s1; den[2] += s2; den[3] += s3;
    num[0] = fmaf(s0, bf_lo(v.z), num[0]);
    num[1] = fmaf(s1, bf_hi(v.z), num[1]);
    num[2] = fmaf(s2, bf_lo(v.w), num[2]);
    num[3] = fmaf(s3, bf_hi(v.w), num[3]);
}

#define K2_THREADS 512
#define K2_RPT (BINCAP / K2_THREADS)
#define K2_NW (K2_THREADS / 32)
#define SORT_WORDS (BINCAP + 4 * MAXNB)

struct Grp { uint4 v[4]; };

__device__ __forceinline__ const uint4* row_ptr(const char* Tl, uint32_t rec) {
    return reinterpret_cast<const uint4*>(Tl + (size_t)((rec & 0xffffu) * 512u));
}
__device__ __forceinline__ void grp_load(Grp& g, const uint32_t* sp, const char* Tl) {
    const uint4 t = *reinterpret_cast<const uint4*>(sp);
    g.v[0] = __ldg(row_ptr(Tl, t.x));
    g.v[1] = __ldg(row_ptr(Tl, t.y));
    g.v[2] = __ldg(row_ptr(Tl, t.z));
    g.v[3] = __ldg(row_ptr(Tl, t.w));
}
__device__ __forceinline__ void grp_consume(const Grp& g, const uint32_t* sp, const float a[4], const float cc[4],
                                            float num[4], float den[4]) {
    const uint4 t = *reinterpret_cast<const uint4*>(sp);
    edge_accum(g.v[0], bf_hi(t.x), a, cc, num, den);
    edge_accum(g.v[1], bf_hi(t.y), a, cc, num, den);
    edge_accum(g.v[2], bf_hi(t.z), a, cc, num, den);
    edge_accum(g.v[3], bf_hi(t.w), a, cc, num, den);
}

__global__ void __launch_bounds__(K2_THREADS, 1) k2_kernel(
    const __nv_bfloat16* __restrict__ x, const __nv_bfloat16* __restrict__ w_a, const __nv_bfloat16* __restrict__ w_u,
    const __nv_bfloat16* __restrict__ w_c, __nv_bfloat16* __restrict__ out, int N, int NB)
{
    extern __shared__ __align__(128) uint8_t dsm[];
    __shared__ __align__(16) uint32_t s_sorted[SORT_WORDS];
    __shared__ int s_hist[MAXNB];
    __shared__ int s_off[MAXNB + 1];
    uint4* s_AU = reinterpret_cast<uint4*>(dsm + 65536);

    const int tid = threadIdx.x;
    const int lane = tid & 31, warp = tid >> 5;
    const int bin = blockIdx.x;
    const int node0 = bin * NB;
    const int nn = min(NB, N - node0);

    {
        const int q = lane & 3;
        const int n_tasks = ((nn + 15) >> 4) * 2;
        uint4 X0[4], X1[4];
        int task = warp;
        int lr = (task >> 1) * 16 + (lane >> 2);
        const int lim = node0 + nn;
        if (task < n_tasks) load_x_frags(X0, X1, x, node0 + lr, lim, q);
        stage_weights(dsm, w_a, w_u, tid, K2_THREADS);
        if (tid < MAXNB) s_hist[tid] = 0;
        for (int i = tid; i < SORT_WORDS; i += K2_THREADS) s_sorted[i] = (uint32_t)N;
        __syncthreads();
        const uint32_t sbase = (uint32_t)__cvta_generic_to_shared(dsm);
        while (task < n_tasks) {
            const int m0 = (task & 1) * 4;
            #pragma unroll 1
            for (int m = m0; m < m0 + 4; m++) {
                uint4 o0, o1;
                gemm_group(X0, X1, sbase, m, lane, o0, o1);
                s_AU[lr * 32 + 4 * m + q] = o0;
                s_AU[(lr + 8) * 32 + 4 * m + q] = o1;
            }
            task += K2_NW;
            if (task < n_tasks) {
                lr = (task >> 1) * 16 + (lane >> 2);
                load_x_frags(X0, X1, x, node0 + lr, lim, q);
            }
        }
    }
    const uint2 wc = __ldg(reinterpret_cast<const uint2*>(w_c) + lane);
    const float cc[4] = { -LOG2E * bf_lo(wc.x), -LOG2E * bf_hi(wc.x), -LOG2E * bf_lo(wc.y), -LOG2E * bf_hi(wc.y) };

    asm volatile("griddepcontrol.wait;" ::: "memory");

    const int cnt = min(g_bin_cnt[bin], BINCAP);
    const int ovf_n = g_ovf_cnt;
    {
        uint2 r[K2_RPT]; int rk[K2_RPT];
        #pragma unroll
        for (int i = 0; i < K2_RPT; i++) {
            int idx = i * K2_THREADS + tid;
            if (idx < cnt) r[i] = g_bins[bin * BINCAP + idx];
        }
        #pragma unroll
        for (int i = 0; i < K2_RPT; i++) {
            int idx = i * K2_THREADS + tid;
            if (idx < cnt) rk[i] = atomicAdd(&s_hist[r[i].y], 1);
        }
        __syncthreads();
        if (warp == 0) {
            int v[4]; int sum = 0;
            #pragma unroll
            for (int i = 0; i < 4; i++) { v[i] = (s_hist[lane * 4 + i] + 3) & ~3; sum += v[i]; }
            int inc = sum;
            #pragma unroll
            for (int o = 1; o < 32; o <<= 1) { int t = __shfl_up_sync(0xffffffffu, inc, o); if (lane >= o) inc += t; }
            int run = inc - sum;
            #pragma unroll
            for (int i = 0; i < 4; i++) { s_off[lane * 4 + i] = run; run += v[i]; }
            if (lane == 31) s_off[MAXNB] = run;
        }
        if (tid == 32) g_bin_cnt[bin] = 0;
        __syncthreads();
        #pragma unroll
        for (int i = 0; i < K2_RPT; i++) {
            int idx = i * K2_THREADS + tid;
            if (idx < cnt) s_sorted[s_off[r[i].y] + rk[i]] = r[i].x;
        }
        __syncthreads();
    }

    const char* Tl = reinterpret_cast<const char*>(g_T) + lane * 16;
    int ln, ln_end;
    {
        const int total = s_off[MAXNB];
        const int lo = (int)(((long long)total * warp) / K2_NW);
        const int hi = (int)(((long long)total * (warp + 1)) / K2_NW);
        int c_lo = 0, c_hi = 0;
        #pragma unroll
        for (int i = 0; i < 4; i++) {
            int node = i * 32 + lane;
            int o = (node < nn) ? s_off[node] : 0x7fffffff;
            c_lo += __popc(__ballot_sync(0xffffffffu, o < lo));
            c_hi += __popc(__ballot_sync(0xffffffffu, o < hi));
        }
        ln = c_lo; ln_end = (warp == K2_NW - 1) ? nn : c_hi;
        if (warp == 0) ln = 0;
    }
    if (ln < ln_end) {
        int g = s_off[ln] >> 2;
        const int g_end = s_off[ln_end] >> 2;
        Grp b0, b1, b2;
        if (g < g_end) grp_load(b0, s_sorted + 4 * g, Tl);
        if (g + 1 < g_end) grp_load(b1, s_sorted + 4 * (g + 1), Tl);
        if (g + 2 < g_end) grp_load(b2, s_sorted + 4 * (g + 2), Tl);
        uint2 xv = __ldg(reinterpret_cast<const uint2*>(x) + (size_t)(node0 + ln) * 32 + lane);
        uint4 au = s_AU[ln * 32 + lane];
        float a[4] = { -LOG2E * bf_lo(au.x), -LOG2E * bf_hi(au.x), -LOG2E * bf_lo(au.y), -LOG2E * bf_hi(au.y) };
        float num[4] = {0.f, 0.f, 0.f, 0.f}, den[4] = {0.f, 0.f, 0.f, 0.f};
        int node_end = s_off[ln + 1] >> 2;

        #define FINISH_NODES() \
        while (g == node_end) { \
            const int n = node0 + ln; \
            if (ovf_n != 0) { \
                for (int base = 0; base < ovf_n; base += 64) { \
                    int i2 = base + 2 * lane; \
                    int od = (i2 < ovf_n) ? g_ovf[i2] : -1; \
                    uint32_t orec = (i2 < ovf_n) ? (uint32_t)g_ovf[i2 + 1] : 0u; \
                    unsigned msk = __ballot_sync(0xffffffffu, od == n); \
                    while (msk) { \
                        int l = __ffs(msk) - 1; msk &= msk - 1; \
                        uint32_t r = __shfl_sync(0xffffffffu, orec, l); \
                        uint4 v = __ldg(row_ptr(Tl, r)); \
                        edge_accum(v, bf_hi(r), a, cc, num, den); \
                    } \
                } \
            } \
            { \
                const float u4[4] = { bf_lo(au.z), bf_hi(au.z), bf_lo(au.w), bf_hi(au.w) }; \
                const float x4[4] = { bf_lo(xv.x), bf_hi(xv.x), bf_lo(xv.y), bf_hi(xv.y) }; \
                float o[4]; \
                _Pragma("unroll") for (int i = 0; i < 4; i++) { \
                    float agg = round_bf16(__fdividef(num[i], den[i] + 1e-6f)); \
                    float z = round_bf16(u4[i] + agg); \
                    float rz = (z > 0.f) ? z : 0.f * z; \
                    o[i] = x4[i] + rz; \
                    num[i] = 0.f; den[i] = 0.f; \
                } \
                reinterpret_cast<uint2*>(out)[(size_t)n * 32 + lane] = make_uint2(pack_bf16(o[0], o[1]), pack_bf16(o[2], o[3])); \
            } \
            ln++; \
            if (ln >= ln_end) goto done; \
            au = s_AU[ln * 32 + lane]; \
            xv = __ldg(reinterpret_cast<const uint2*>(x) + (size_t)(node0 + ln) * 32 + lane); \
            a[0] = -LOG2E * bf_lo(au.x); a[1] = -LOG2E * bf_hi(au.x); a[2] = -LOG2E * bf_lo(au.y); a[3] = -LOG2E * bf_hi(au.y); \
            node_end = s_off[ln + 1] >> 2; \
        }
        #define STEP(B) \
            FINISH_NODES(); \
            grp_consume(B, s_sorted + 4 * g, a, cc, num, den); \
            if (g + 3 < g_end) grp_load(B, s_sorted + 4 * (g + 3), Tl); \
            g++;
        while (true) {
            STEP(b0);
            STEP(b1);
            STEP(b2);
        }
        done:;
    }
    if (ovf_n != 0) {
        __syncthreads();
        if (tid == 0) {
            __threadfence();
            int t = atomicAdd(&g_done, 1);
            if (t == (int)gridDim.x - 1) { g_done = 0; __threadfence(); g_ovf_cnt = 0; }
        }
    }
}

extern "C" void kernel_launch(void* const* d_in, const int* in_sizes, int n_in,
                              void* d_out, int out_size) {
    const __nv_bfloat16* x      = (const __nv_bfloat16*)d_in[0];
    const __nv_bfloat16* e_attr = (const __nv_bfloat16*)d_in[1];
    const int* src = (const int*)d_in[2];
    const int* dst = (const int*)d_in[3];
    const __nv_bfloat16* w_a = (const __nv_bfloat16*)d_in[4];
    const __nv_bfloat16* w_b = (const __nv_bfloat16*)d_in[5];
    const __nv_bfloat16* w_c = (const __nv_bfloat16*)d_in[6];
    const __nv_bfloat16* w_u = (const __nv_bfloat16*)d_in[7];
    const __nv_bfloat16* w_v = (const __nv_bfloat16*)d_in[8];
    __nv_bfloat16* out = (__nv_bfloat16*)d_out;
    const int N = in_sizes[0] / D_FEAT;
    const int E = in_sizes[2];
    if (N > MAX_N || 2 * E > MAX_E || N <= 0) return;

    static int num_sms = 0;
    if (num_sms == 0) {
        int dev = 0;
        cudaGetDevice(&dev);
        cudaDeviceGetAttribute(&num_sms, cudaDevAttrMultiProcessorCount, dev);
        if (num_sms <= 0 || num_sms > MAXBINS) num_sms = 132;
        cudaFuncSetAttribute(k1_kernel, cudaFuncAttributeMaxDynamicSharedMemorySize, K1_SMEM);
        cudaFuncSetAttribute(k2_kernel, cudaFuncAttributeMaxDynamicSharedMemorySize, 65536 + MAXNB * 512);
    }
    cudaStream_t st = cudaStreamPerThread;
    int NB = (N + num_sms - 1) / num_sms;
    if (NB > MAXNB) NB = MAXNB;
    const int nbins = (N + NB - 1) / NB;
    const uint32_t magic = (uint32_t)(((1u << 24) + NB - 1) / NB);
    const int P = num_sms;
    int chunk = (E + P - 1) / P;
    if (chunk > P1_CHUNK) chunk = P1_CHUNK;
    if (chunk < 1) chunk = 1;
    k1_kernel<<<P, K1_THREADS, K1_SMEM, st>>>(x, e_attr, src, dst, w_b, w_v, N, E, chunk, NB, nbins, magic);

    cudaLaunchConfig_t cfg = {};
    cfg.gridDim = dim3(nbins);
    cfg.blockDim = dim3(K2_THREADS);
    cfg.dynamicSmemBytes = 65536 + ((NB + 15) / 16) * 16 * 512;
    cfg.stream = st;
    cudaLaunchAttribute at[1];
    at[0].id = cudaLaunchAttributeProgrammaticStreamSerialization;
    at[0].val.programmaticStreamSerializationAllowed = 1;
    cfg.attrs = at; cfg.numAttrs = 1;
    cudaLaunchKernelEx(&cfg, k2_kernel, x, w_a, w_u, w_c, out, N, NB);
}
```

```cpp
#include <cuda_runtime.h>
#include <cuda_bf16.h>
#include <stdint.h>

#define D_FEAT 128
#define MAX_N 16384
#define MAX_E (1 << 20)
#define LOG2E 1.4426950408889634f

#define MAXBINS 256
#define MAXNB 128
#define BINCAP 3072
__device__ uint4 g_T[(MAX_N + 1) * 32];
__device__ uint4 g_AU[MAX_N * 32];
__device__ int g_bin_cnt[MAXBINS];
__device__ uint2 g_bins[MAXBINS * BINCAP];
__device__ int g_ovf[MAX_E];
__device__ int g_ovf_cnt;
__device__ int g_done;

__device__ __forceinline__ float ex2_approx(float x) {
    float y; asm("ex2.approx.ftz.f32 %0, %1;" : "=f"(y) : "f"(x)); return y;
}
__device__ __forceinline__ float rcp_approx(float x) {
    float y; asm("rcp.approx.ftz.f32 %0, %1;" : "=f"(y) : "f"(x)); return y;
}
__device__ __forceinline__ uint32_t pack_bf16(float lo, float hi) {
    __nv_bfloat162 t = __floats2bfloat162_rn(lo, hi);
    return *reinterpret_cast<uint32_t*>(&t);
}
__device__ __forceinline__ float bf_lo(uint32_t v) { return __uint_as_float(v << 16); }
__device__ __forceinline__ float bf_hi(uint32_t v) { return __uint_as_float(v & 0xffff0000u); }
__device__ __forceinline__ float round_bf16(float x) { return __bfloat162float(__float2bfloat16_rn(x)); }

__device__ __forceinline__ void mma_bf16(float c[4], uint32_t a0, uint32_t a1, uint32_t a2, uint32_t a3,
                                         uint32_t b0, uint32_t b1) {
    asm volatile("mma.sync.aligned.m16n8k16.row.col.f32.bf16.bf16.f32 "
                 "{%0,%1,%2,%3}, {%4,%5,%6,%7}, {%8,%9}, {%0,%1,%2,%3};"
                 : "+f"(c[0]), "+f"(c[1]), "+f"(c[2]), "+f"(c[3])
                 : "r"(a0), "r"(a1), "r"(a2), "r"(a3), "r"(b0), "r"(b1));
}
__device__ __forceinline__ void ldmatrix_x4_trans(uint32_t& r0, uint32_t& r1, uint32_t& r2, uint32_t& r3, uint32_t addr) {
    asm volatile("ldmatrix.sync.aligned.m8n8.x4.trans.shared.b16 {%0,%1,%2,%3}, [%4];"
                 : "=r"(r0), "=r"(r1), "=r"(r2), "=r"(r3) : "r"(addr));
}

__device__ __forceinline__ void stage_weights(uint8_t* smem, const __nv_bfloat16* w0, const __nv_bfloat16* w1,
                                              int tid, int nthreads) {
    const uint4* W0 = reinterpret_cast<const uint4*>(w0);
    const uint4* W1 = reinterpret_cast<const uint4*>(w1);
    for (int u = tid; u < 2048; u += nthreads) {
        int mtx = u >> 10, k = (u >> 3) & 127, m = u & 7;
        const uint4* p = (mtx ? W1 : W0) + k * 16 + m * 2;
        uint4 lo = __ldg(p), hi = __ldg(p + 1);
        uint4 c0 = make_uint4(lo.x, lo.z, hi.x, hi.z);
        uint4 c1 = make_uint4(lo.y, lo.w, hi.y, hi.w);
        int f = (((k >> 3) & 3) << 1) | (k & 1);
        uint8_t* row = smem + mtx * 32768 + k * 256;
        *reinterpret_cast<uint4*>(row + (((2 * m) ^ f) << 4)) = c0;
        *reinterpret_cast<uint4*>(row + (((2 * m + 1) ^ f) << 4)) = c1;
    }
}

__device__ __forceinline__ void load_x_frags(uint4 X0[4], uint4 X1[4], const __nv_bfloat16* x, int r0, int N, int q) {
    const uint4* xr0 = reinterpret_cast<const uint4*>(x) + (size_t)r0 * 16 + q;
    const uint4* xr1 = xr0 + 8 * 16;
    #pragma unroll
    for (int c = 0; c < 4; c++) {
        X0[c] = (r0 < N) ? __ldg(xr0 + c * 4) : make_uint4(0, 0, 0, 0);
        X1[c] = (r0 + 8 < N) ? __ldg(xr1 + c * 4) : make_uint4(0, 0, 0, 0);
    }
}

__device__ __forceinline__ void gemm_group(const uint4 X0[4], const uint4 X1[4], uint32_t sbase, int m, int lane,
                                           uint4& o0, uint4& o1) {
    const int mi = lane >> 3, ii = lane & 7;
    const int hh = mi & 1, tj = mi >> 1;
    float acc[4][4];
    #pragma unroll
    for (int t = 0; t < 4; t++) { acc[t][0] = acc[t][1] = acc[t][2] = acc[t][3] = 0.f; }
    #pragma unroll
    for (int c = 0; c < 4; c++) {
        #pragma unroll
        for (int s = 0; s < 2; s++) {
            int k = 32 * c + 8 * (ii >> 1) + 4 * s + 2 * hh + (ii & 1);
            int f = (((k >> 3) & 3) << 1) | (k & 1);
            uint32_t addr = sbase + k * 256 + (((2 * m + tj) ^ f) << 4);
            uint32_t b0, b1, b2, b3, h0, h1, h2, h3;
            ldmatrix_x4_trans(b0, b1, b2, b3, addr);
            ldmatrix_x4_trans(h0, h1, h2, h3, addr + 32768);
            uint32_t a0 = s ? X0[c].z : X0[c].x, a1 = s ? X1[c].z : X1[c].x;
            uint32_t a2 = s ? X0[c].w : X0[c].y, a3 = s ? X1[c].w : X1[c].y;
            mma_bf16(acc[0], a0, a1, a2, a3, b0, b1);
            mma_bf16(acc[1], a0, a1, a2, a3, b2, b3);
            mma_bf16(acc[2], a0, a1, a2, a3, h0, h1);
            mma_bf16(acc[3], a0, a1, a2, a3, h2, h3);
        }
    }
    o0 = make_uint4(pack_bf16(acc[0][0], acc[0][1]), pack_bf16(acc[1][0], acc[1][1]),
                    pack_bf16(acc[2][0], acc[2][1]), pack_bf16(acc[3][0], acc[3][1]));
    o1 = make_uint4(pack_bf16(acc[0][2], acc[0][3]), pack_bf16(acc[1][2], acc[1][3]),
                    pack_bf16(acc[2][2], acc[2][3]), pack_bf16(acc[3][2], acc[3][3]));
}

#define K1_GW 10
#define K1_THREADS ((K1_GW + 8) * 32)
#define P1_EPT 10
#define P1_CHUNK (256 * P1_EPT)
#define K1_WBYTES 131072
#define K1_SMEM (K1_WBYTES + 3 * MAXBINS * 4 + P1_CHUNK * 8)

__device__ __forceinline__ void p1_bar() { asm volatile("bar.sync 1, 256;" ::: "memory"); }

__global__ void __launch_bounds__(K1_THREADS, 1) k1_kernel(
    const __nv_bfloat16* __restrict__ x, const __nv_bfloat16* __restrict__ e_attr,
    const int* __restrict__ src, const int* __restrict__ dst,
    const __nv_bfloat16* __restrict__ w_b, const __nv_bfloat16* __restrict__ w_v,
    const __nv_bfloat16* __restrict__ w_a, const __nv_bfloat16* __restrict__ w_u,
    int N, int E, int chunk, int NB, int nbins, uint32_t magic)
{
    extern __shared__ __align__(128) uint8_t smem[];
    asm volatile("griddepcontrol.launch_dependents;");

    const int warp = threadIdx.x >> 5, lane = threadIdx.x & 31;

    if (warp >= K1_GW) {
        const int tid = threadIdx.x - K1_GW * 32;
        if (blockIdx.x == 0 && tid < 32)
            g_T[(size_t)N * 32 + tid] = make_uint4(0xff80ff80u, 0xff80ff80u, 0u, 0u);
        int* hist = reinterpret_cast<int*>(smem + K1_WBYTES);
        int* loff = hist + MAXBINS;
        int* gbase = loff + MAXBINS;
        uint2* sorted = reinterpret_cast<uint2*>(smem + K1_WBYTES + 3 * MAXBINS * 4);
        for (int beg = blockIdx.x * chunk; beg < E; beg += gridDim.x * chunk) {
            const int end = min(E, beg + chunk);
            int d[P1_EPT]; uint32_t rec[P1_EPT]; int rk[P1_EPT]; int bn[P1_EPT];
            #pragma unroll
            for (int i = 0; i < P1_EPT; i++) {
                int e = beg + i * 256 + tid;
                d[i] = -1;
                if (e < end) {
                    d[i] = __ldg(dst + e);
                    uint32_t s = (uint32_t)__ldg(src + e);
                    uint32_t ev = (uint32_t)__ldg(reinterpret_cast<const unsigned short*>(e_attr) + e);
                    rec[i] = (ev << 16) | s;
                }
            }
            hist[tid] = 0;
            p1_bar();
            #pragma unroll
            for (int i = 0; i < P1_EPT; i++) {
                if (d[i] >= 0) {
                    bn[i] = (int)(((uint64_t)(uint32_t)d[i] * magic) >> 24);
                    rk[i] = atomicAdd(&hist[bn[i]], 1);
                }
            }
            p1_bar();
            {
                int h = hist[tid];
                if (tid < nbins && h > 0) gbase[tid] = atomicAdd(&g_bin_cnt[tid], h);
                if (tid < 32) {
                    int v[8]; int sum = 0;
                    #pragma unroll
                    for (int i = 0; i < 8; i++) { v[i] = hist[lane * 8 + i]; sum += v[i]; }
                    int inc = sum;
                    #pragma unroll
                    for (int o = 1; o < 32; o <<= 1) { int t = __shfl_up_sync(0xffffffffu, inc, o); if (lane >= o) inc += t; }
                    int run = inc - sum;
                    #pragma unroll
                    for (int i = 0; i < 8; i++) { loff[lane * 8 + i] = run; run += v[i]; }
                }
            }
            p1_bar();
            #pragma unroll
            for (int i = 0; i < P1_EPT; i++) {
                if (d[i] >= 0) sorted[loff[bn[i]] + rk[i]] = make_uint2(rec[i], (uint32_t)d[i]);
            }
            p1_bar();
            const int cnt = end - beg;
            for (int i = tid; i < cnt; i += 256) {
                uint2 r = sorted[i];
                int b = (int)(((uint64_t)r.y * magic) >> 24);
                int pos = gbase[b] + (i - loff[b]);
                if (pos < BINCAP) {
                    g_bins[b * BINCAP + pos] = make_uint2(r.x, r.y - (uint32_t)(b * NB));
                } else {
                    int p = atomicAdd(&g_ovf_cnt, 2);
                    g_ovf[p] = (int)r.y; g_ovf[p + 1] = (int)r.x;
                }
            }
            p1_bar();
        }
        return;
    }

    const int q = lane & 3;
    const int n_tasks = ((N + 15) >> 4) * 2;
    int task = blockIdx.x * K1_GW + warp;
    uint4 X0[4], X1[4];
    int r0 = (task >> 1) * 16 + (lane >> 2);
    if (task < n_tasks) load_x_frags(X0, X1, x, r0, N, q);
    stage_weights(smem, w_b, w_v, threadIdx.x, K1_GW * 32);
    stage_weights(smem + 65536, w_a, w_u, threadIdx.x, K1_GW * 32);
    asm volatile("bar.sync 2, %0;" :: "n"(K1_GW * 32) : "memory");
    const uint32_t sbase = (uint32_t)__cvta_generic_to_shared(smem);
    while (task < n_tasks) {
        const int m0 = (task & 1) * 4;
        #pragma unroll 2
        for (int m = m0; m < m0 + 4; m++) {
            uint4 o0, o1;
            gemm_group(X0, X1, sbase, m, lane, o0, o1);
            if (r0 < N) g_T[(size_t)r0 * 32 + 4 * m + q] = o0;
            if (r0 + 8 < N) g_T[(size_t)(r0 + 8) * 32 + 4 * m + q] = o1;
        }
        #pragma unroll 2
        for (int m = m0; m < m0 + 4; m++) {
            uint4 o0, o1;
            gemm_group(X0, X1, sbase + 65536, m, lane, o0, o1);
            if (r0 < N) g_AU[(size_t)r0 * 32 + 4 * m + q] = o0;
            if (r0 + 8 < N) g_AU[(size_t)(r0 + 8) * 32 + 4 * m + q] = o1;
        }
        task += gridDim.x * K1_GW;
        if (task < n_tasks) {
            r0 = (task >> 1) * 16 + (lane >> 2);
            load_x_frags(X0, X1, x, r0, N, q);
        }
    }
}

__device__ __forceinline__ void edge_accum(const uint4 v, const float e, const float a[4], const float cc[4],
                                           float num[4], float den[4]) {
    float y0 = fmaf(bf_lo(v.x), -LOG2E, fmaf(e, cc[0], a[0]));
    float y1 = fmaf(bf_hi(v.x), -LOG2E, fmaf(e, cc[1], a[1]));
    float y2 = fmaf(bf_lo(v.y), -LOG2E, fmaf(e, cc[2], a[2]));
    float y3 = fmaf(bf_hi(v.y), -LOG2E, fmaf(e, cc[3], a[3]));
    float s0 = rcp_approx(1.f + ex2_approx(y0));
    float s1 = rcp_approx(1.f + ex2_approx(y1));
    float s2 = rcp_approx(1.f + ex2_approx(y2));
    float s3 = rcp_approx(1.f + ex2_approx(y3));
    den[0] += s0; den[1] += s1; den[2] += s2; den[3] += s3;
    num[0] = fmaf(s0, bf_lo(v.z), num[0]);
    num[1] = fmaf(s1, bf_hi(v.z), num[1]);
    num[2] = fmaf(s2, bf_lo(v.w), num[2]);
    num[3] = fmaf(s3, bf_hi(v.w), num[3]);
}

#define K2_THREADS 512
#define K2_D 3
#define K2_DYN_SMEM (100 * 1024)
#define K2_RPT ((BINCAP + K2_THREADS - 1) / K2_THREADS)
#define K2_NW (K2_THREADS / 32)
#define SORT_WORDS (BINCAP + 4 * MAXNB)

struct Grp { uint4 v[4]; };

__device__ __forceinline__ const uint4* row_ptr(const char* Tl, uint32_t rec) {
    return reinterpret_cast<const uint4*>(Tl + (size_t)((rec & 0xffffu) * 512u));
}
__device__ __forceinline__ void grp_load(Grp& g, const uint32_t* sp, const char* Tl) {
    const uint4 t = *reinterpret_cast<const uint4*>(sp);
    g.v[0] = __ldg(row_ptr(Tl, t.x));
    g.v[1] = __ldg(row_ptr(Tl, t.y));
    g.v[2] = __ldg(row_ptr(Tl, t.z));
    g.v[3] = __ldg(row_ptr(Tl, t.w));
}
__device__ __forceinline__ void grp_consume(const Grp& g, const uint32_t* sp, const float a[4], const float cc[4],
                                            float num[4], float den[4]) {
    const uint4 t = *reinterpret_cast<const uint4*>(sp);
    edge_accum(g.v[0], bf_hi(t.x), a, cc, num, den);
    edge_accum(g.v[1], bf_hi(t.y), a, cc, num, den);
    edge_accum(g.v[2], bf_hi(t.z), a, cc, num, den);
    edge_accum(g.v[3], bf_hi(t.w), a, cc, num, den);
}

__global__ void __launch_bounds__(K2_THREADS, 1) k2_kernel(
    const __nv_bfloat16* __restrict__ x,
    const __nv_bfloat16* __restrict__ w_c, __nv_bfloat16* __restrict__ out, int N, int NB)
{
    __shared__ __align__(16) uint32_t s_sorted[SORT_WORDS];
    __shared__ int s_hist[MAXNB];
    __shared__ int s_off[MAXNB + 1];

    const int tid = threadIdx.x;
    const int lane = tid & 31, warp = tid >> 5;
    const int bin = blockIdx.x;
    const int node0 = bin * NB;
    const int nn = min(NB, N - node0);

    if (tid < MAXNB) s_hist[tid] = 0;
    for (int i = tid; i < SORT_WORDS; i += K2_THREADS) s_sorted[i] = (uint32_t)N;
    __syncthreads();
    const uint2 wc = __ldg(reinterpret_cast<const uint2*>(w_c) + lane);
    const float cc[4] = { -LOG2E * bf_lo(wc.x), -LOG2E * bf_hi(wc.x), -LOG2E * bf_lo(wc.y), -LOG2E * bf_hi(wc.y) };

    asm volatile("griddepcontrol.wait;" ::: "memory");

    const int cnt = min(g_bin_cnt[bin], BINCAP);
    const int ovf_n = g_ovf_cnt;
    {
        uint2 r[K2_RPT]; int rk[K2_RPT];
        #pragma unroll
        for (int i = 0; i < K2_RPT; i++) {
            int idx = i * K2_THREADS + tid;
            if (idx < cnt) r[i] = g_bins[bin * BINCAP + idx];
        }
        #pragma unroll
        for (int i = 0; i < K2_RPT; i++) {
            int idx = i * K2_THREADS + tid;
            if (idx < cnt) rk[i] = atomicAdd(&s_hist[r[i].y], 1);
        }
        __syncthreads();
        if (warp == 0) {
            int v[4]; int sum = 0;
            #pragma unroll
            for (int i = 0; i < 4; i++) { v[i] = (s_hist[lane * 4 + i] + 3) & ~3; sum += v[i]; }
            int inc = sum;
            #pragma unroll
            for (int o = 1; o < 32; o <<= 1) { int t = __shfl_up_sync(0xffffffffu, inc, o); if (lane >= o) inc += t; }
            int run = inc - sum;
            #pragma unroll
            for (int i = 0; i < 4; i++) { s_off[lane * 4 + i] = run; run += v[i]; }
            if (lane == 31) s_off[MAXNB] = run;
        }
        if (tid == 32) g_bin_cnt[bin] = 0;
        __syncthreads();
        #pragma unroll
        for (int i = 0; i < K2_RPT; i++) {
            int idx = i * K2_THREADS + tid;
            if (idx < cnt) s_sorted[s_off[r[i].y] + rk[i]] = r[i].x;
        }
        __syncthreads();
    }

    const char* Tl = reinterpret_cast<const char*>(g_T) + lane * 16;
    int ln, ln_end;
    {
        const int total = s_off[MAXNB];
        const int lo = (int)(((long long)total * warp) / K2_NW);
        const int hi = (int)(((long long)total * (warp + 1)) / K2_NW);
        int c_lo = 0, c_hi = 0;
        #pragma unroll
        for (int i = 0; i < 4; i++) {
            int node = i * 32 + lane;
            int o = (node < nn) ? s_off[node] : 0x7fffffff;
            c_lo += __popc(__ballot_sync(0xffffffffu, o < lo));
            c_hi += __popc(__ballot_sync(0xffffffffu, o < hi));
        }
        ln = c_lo; ln_end = (warp == K2_NW - 1) ? nn : c_hi;
        if (warp == 0) ln = 0;
    }
    if (ln < ln_end) {
        int g = s_off[ln] >> 2;
        const int g_end = s_off[ln_end] >> 2;
        Grp b0, b1, b2;
        if (g < g_end) grp_load(b0, s_sorted + 4 * g, Tl);
        if (g + 1 < g_end) grp_load(b1, s_sorted + 4 * (g + 1), Tl);
        if (g + 2 < g_end) grp_load(b2, s_sorted + 4 * (g + 2), Tl);
        uint2 xv = __ldg(reinterpret_cast<const uint2*>(x) + (size_t)(node0 + ln) * 32 + lane);
        uint4 au = g_AU[(size_t)(node0 + ln) * 32 + lane];
        uint4 au_n; uint2 xv_n;
        if (ln + 1 < ln_end) {
            au_n = g_AU[(size_t)(node0 + ln + 1) * 32 + lane];
            xv_n = __ldg(reinterpret_cast<const uint2*>(x) + (size_t)(node0 + ln + 1) * 32 + lane);
        }
        float a[4] = { -LOG2E * bf_lo(au.x), -LOG2E * bf_hi(au.x), -LOG2E * bf_lo(au.y), -LOG2E * bf_hi(au.y) };
        float num[4] = {0.f, 0.f, 0.f, 0.f}, den[4] = {0.f, 0.f, 0.f, 0.f};
        int node_end = s_off[ln + 1] >> 2;

        #define FINISH_NODES() \
        while (g == node_end) { \
            const int n = node0 + ln; \
            if (ovf_n != 0) { \
                for (int base = 0; base < ovf_n; base += 64) { \
                    int i2 = base + 2 * lane; \
                    int od = (i2 < ovf_n) ? g_ovf[i2] : -1; \
                    uint32_t orec = (i2 < ovf_n) ? (uint32_t)g_ovf[i2 + 1] : 0u; \
                    unsigned msk = __ballot_sync(0xffffffffu, od == n); \
                    while (msk) { \
                        int l = __ffs(msk) - 1; msk &= msk - 1; \
                        uint32_t r = __shfl_sync(0xffffffffu, orec, l); \
                        uint4 v = __ldg(row_ptr(Tl, r)); \
                        edge_accum(v, bf_hi(r), a, cc, num, den); \
                    } \
                } \
            } \
            { \
                const float u4[4] = { bf_lo(au.z), bf_hi(au.z), bf_lo(au.w), bf_hi(au.w) }; \
                const float x4[4] = { bf_lo(xv.x), bf_hi(xv.x), bf_lo(xv.y), bf_hi(xv.y) }; \
                float o[4]; \
                _Pragma("unroll") for (int i = 0; i < 4; i++) { \
                    float agg = round_bf16(__fdividef(num[i], den[i] + 1e-6f)); \
                    float z = round_bf16(u4[i] + agg); \
                    float rz = (z > 0.f) ? z : 0.f * z; \
                    o[i] = x4[i] + rz; \
                    num[i] = 0.f; den[i] = 0.f; \
                } \
                reinterpret_cast<uint2*>(out)[(size_t)n * 32 + lane] = make_uint2(pack_bf16(o[0], o[1]), pack_bf16(o[2], o[3])); \
            } \
            ln++; \
            if (ln >= ln_end) goto done; \
            au = au_n; xv = xv_n; \
            if (ln + 1 < ln_end) { \
                au_n = g_AU[(size_t)(node0 + ln + 1) * 32 + lane]; \
                xv_n = __ldg(reinterpret_cast<const uint2*>(x) + (size_t)(node0 + ln + 1) * 32 + lane); \
            } \
            a[0] = -LOG2E * bf_lo(au.x); a[1] = -LOG2E * bf_hi(au.x); a[2] = -LOG2E * bf_lo(au.y); a[3] = -LOG2E * bf_hi(au.y); \
            node_end = s_off[ln + 1] >> 2; \
        }
        #define STEP(B) \
            FINISH_NODES(); \
            grp_consume(B, s_sorted + 4 * g, a, cc, num, den); \
            if (g + K2_D < g_end) grp_load(B, s_sorted + 4 * (g + K2_D), Tl); \
            g++;
        while (true) {
            STEP(b0);
            STEP(b1);
            STEP(b2);
        }
        done:;
    }
    if (ovf_n != 0) {
        __syncthreads();
        if (tid == 0) {
            __threadfence();
            int t = atomicAdd(&g_done, 1);
            if (t == (int)gridDim.x - 1) { g_done = 0; __threadfence(); g_ovf_cnt = 0; }
        }
    }
}

extern "C" void kernel_launch(void* const* d_in, const int* in_sizes, int n_in,
                              void* d_out, int out_size) {
    const __nv_bfloat16* x      = (const __nv_bfloat16*)d_in[0];
    const __nv_bfloat16* e_attr = (const __nv_bfloat16*)d_in[1];
    const int* src = (const int*)d_in[2];
    const int* dst = (const int*)d_in[3];
    const __nv_bfloat16* w_a = (const __nv_bfloat16*)d_in[4];
    const __nv_bfloat16* w_b = (const __nv_bfloat16*)d_in[5];
    const __nv_bfloat16* w_c = (const __nv_bfloat16*)d_in[6];
    const __nv_bfloat16* w_u = (const __nv_bfloat16*)d_in[7];
    const __nv_bfloat16* w_v = (const __nv_bfloat16*)d_in[8];
    __nv_bfloat16* out = (__nv_bfloat16*)d_out;
    const int N = in_sizes[0] / D_FEAT;
    const int E = in_sizes[2];
    if (N > MAX_N || 2 * E > MAX_E || N <= 0) return;

    static int num_sms = 0;
    if (num_sms == 0) {
        int dev = 0;
        cudaGetDevice(&dev);
        cudaDeviceGetAttribute(&num_sms, cudaDevAttrMultiProcessorCount, dev);
        if (num_sms <= 0 || num_sms > MAXBINS) num_sms = 132;
        cudaFuncSetAttribute(k1_kernel, cudaFuncAttributeMaxDynamicSharedMemorySize, K1_SMEM);
        cudaFuncSetAttribute(k2_kernel, cudaFuncAttributeMaxDynamicSharedMemorySize, K2_DYN_SMEM);
    }
    cudaStream_t st = cudaStreamPerThread;
    int NB = (N + num_sms - 1) / num_sms;
    if (NB > MAXNB) NB = MAXNB;
    const int nbins = (N + NB - 1) / NB;
    const uint32_t magic = (uint32_t)(((1u << 24) + NB - 1) / NB);
    const int P = num_sms;
    int chunk = (E + P - 1) / P;
    if (chunk > P1_CHUNK) chunk = P1_CHUNK;
    if (chunk < 1) chunk = 1;
    k1_kernel<<<P, K1_THREADS, K1_SMEM, st>>>(x, e_attr, src, dst, w_b, w_v, w_a, w_u, N, E, chunk, NB, nbins, magic);

    cudaLaunchConfig_t cfg = {};
    cfg.gridDim = dim3(nbins);
    cfg.blockDim = dim3(K2_THREADS);
    cfg.dynamicSmemBytes = K2_DYN_SMEM;
    cfg.stream = st;
    cudaLaunchAttribute at[1];
    at[0].id = cudaLaunchAttributeProgrammaticStreamSerialization;
    at[0].val.programmaticStreamSerializationAllowed = 1;
    cfg.attrs = at; cfg.numAttrs = 1;
    cudaLaunchKernelEx(&cfg, k2_kernel, x, w_c, out, N, NB);
}
```

```cpp
#include <cuda_runtime.h>
#include <cuda_bf16.h>
#include <stdint.h>

#define D_FEAT 128
#define MAX_N 16384
#define MAX_E (1 << 20)
#define LOG2E 1.4426950408889634f

#define MAXBINS 256
#define MAXNB 128
#define BINCAP 3072
__device__ uint4 g_T[(MAX_N + 1) * 32];
__device__ uint4 g_AU[MAX_N * 32];
__device__ int g_bin_cnt[MAXBINS];
__device__ uint2 g_bins[MAXBINS * BINCAP];
__device__ int g_ovf[MAX_E];
__device__ int g_ovf_cnt;
__device__ int g_done;

__device__ __forceinline__ float ex2_approx(float x) {
    float y; asm("ex2.approx.ftz.f32 %0, %1;" : "=f"(y) : "f"(x)); return y;
}
__device__ __forceinline__ float rcp_approx(float x) {
    float y; asm("rcp.approx.ftz.f32 %0, %1;" : "=f"(y) : "f"(x)); return y;
}
__device__ __forceinline__ uint32_t pack_bf16(float lo, float hi) {
    __nv_bfloat162 t = __floats2bfloat162_rn(lo, hi);
    return *reinterpret_cast<uint32_t*>(&t);
}
__device__ __forceinline__ float bf_lo(uint32_t v) { return __uint_as_float(v << 16); }
__device__ __forceinline__ float bf_hi(uint32_t v) { return __uint_as_float(v & 0xffff0000u); }
__device__ __forceinline__ float round_bf16(float x) { return __bfloat162float(__float2bfloat16_rn(x)); }

__device__ __forceinline__ void mma_bf16(float c[4], uint32_t a0, uint32_t a1, uint32_t a2, uint32_t a3,
                                         uint32_t b0, uint32_t b1) {
    asm volatile("mma.sync.aligned.m16n8k16.row.col.f32.bf16.bf16.f32 "
                 "{%0,%1,%2,%3}, {%4,%5,%6,%7}, {%8,%9}, {%0,%1,%2,%3};"
                 : "+f"(c[0]), "+f"(c[1]), "+f"(c[2]), "+f"(c[3])
                 : "r"(a0), "r"(a1), "r"(a2), "r"(a3), "r"(b0), "r"(b1));
}
__device__ __forceinline__ void ldmatrix_x4_trans(uint32_t& r0, uint32_t& r1, uint32_t& r2, uint32_t& r3, uint32_t addr) {
    asm volatile("ldmatrix.sync.aligned.m8n8.x4.trans.shared.b16 {%0,%1,%2,%3}, [%4];"
                 : "=r"(r0), "=r"(r1), "=r"(r2), "=r"(r3) : "r"(addr));
}

__device__ __forceinline__ void cp_async16(uint32_t saddr, const void* g) {
    asm volatile("cp.async.cg.shared.global [%0], [%1], 16;" :: "r"(saddr), "l"(g) : "memory");
}
__device__ __forceinline__ void stage_weight(uint32_t sdst, const __nv_bfloat16* w, int tid, int nthreads) {
    const uint4* W = reinterpret_cast<const uint4*>(w);
    for (int u = tid; u < 2048; u += nthreads) {
        int k = u >> 4, c = u & 15;
        int f = (((k >> 3) & 3) << 1) | (k & 1);
        cp_async16(sdst + k * 256 + ((c ^ f) << 4), W + u);
    }
}

__device__ __forceinline__ void load_x_frags(uint4 X0[4], uint4 X1[4], const __nv_bfloat16* x, int r0, int N, int q) {
    const uint4* xr0 = reinterpret_cast<const uint4*>(x) + (size_t)r0 * 16 + q;
    const uint4* xr1 = xr0 + 8 * 16;
    #pragma unroll
    for (int c = 0; c < 4; c++) {
        X0[c] = (r0 < N) ? __ldg(xr0 + c * 4) : make_uint4(0, 0, 0, 0);
        X1[c] = (r0 + 8 < N) ? __ldg(xr1 + c * 4) : make_uint4(0, 0, 0, 0);
    }
}

__device__ __forceinline__ void gemm_group(const uint4 X0[4], const uint4 X1[4], uint32_t sbase, int m, int lane,
                                           uint4& o0, uint4& o1) {
    const int mi = lane >> 3, ii = lane & 7;
    const int hh = mi & 1, tj = mi >> 1;
    float acc[4][4];
    #pragma unroll
    for (int t = 0; t < 4; t++) { acc[t][0] = acc[t][1] = acc[t][2] = acc[t][3] = 0.f; }
    #pragma unroll
    for (int c = 0; c < 4; c++) {
        #pragma unroll
        for (int s = 0; s < 2; s++) {
            int k = 32 * c + 8 * (ii >> 1) + 4 * s + 2 * hh + (ii & 1);
            int f = (((k >> 3) & 3) << 1) | (k & 1);
            uint32_t addr = sbase + k * 256 + (((2 * m + tj) ^ f) << 4);
            uint32_t b0, b1, b2, b3, h0, h1, h2, h3;
            ldmatrix_x4_trans(b0, b1, b2, b3, addr);
            ldmatrix_x4_trans(h0, h1, h2, h3, addr + 32768);
            uint32_t a0 = s ? X0[c].z : X0[c].x, a1 = s ? X1[c].z : X1[c].x;
            uint32_t a2 = s ? X0[c].w : X0[c].y, a3 = s ? X1[c].w : X1[c].y;
            mma_bf16(acc[0], a0, a1, a2, a3, b0, b1);
            mma_bf16(acc[1], a0, a1, a2, a3, b2, b3);
            mma_bf16(acc[2], a0, a1, a2, a3, h0, h1);
            mma_bf16(acc[3], a0, a1, a2, a3, h2, h3);
        }
    }
    o0 = make_uint4(pack_bf16(acc[0][0], acc[0][1]), pack_bf16(acc[1][0], acc[1][1]),
                    pack_bf16(acc[2][0], acc[2][1]), pack_bf16(acc[3][0], acc[3][1]));
    o1 = make_uint4(pack_bf16(acc[0][2], acc[0][3]), pack_bf16(acc[1][2], acc[1][3]),
                    pack_bf16(acc[2][2], acc[2][3]), pack_bf16(acc[3][2], acc[3][3]));
}

#define K1_GW 10
#define K1_THREADS ((K1_GW + 8) * 32)
#define P1_EPT 10
#define P1_CHUNK (256 * P1_EPT)
#define K1_WBYTES 131072
#define K1_SMEM (K1_WBYTES + 3 * MAXBINS * 4 + P1_CHUNK * 8)

__device__ __forceinline__ void p1_bar() { asm volatile("bar.sync 1, 256;" ::: "memory"); }

__global__ void __launch_bounds__(K1_THREADS, 1) k1_kernel(
    const __nv_bfloat16* __restrict__ x, const __nv_bfloat16* __restrict__ e_attr,
    const int* __restrict__ src, const int* __restrict__ dst,
    const __nv_bfloat16* __restrict__ w_b, const __nv_bfloat16* __restrict__ w_v,
    const __nv_bfloat16* __restrict__ w_a, const __nv_bfloat16* __restrict__ w_u,
    int N, int E, int chunk, int NB, int nbins, uint32_t magic)
{
    extern __shared__ __align__(128) uint8_t smem[];
    asm volatile("griddepcontrol.launch_dependents;");

    const int warp = threadIdx.x >> 5, lane = threadIdx.x & 31;

    if (warp >= K1_GW) {
        const int tid = threadIdx.x - K1_GW * 32;
        if (blockIdx.x == 0 && tid < 32)
            g_T[(size_t)N * 32 + tid] = make_uint4(0xff80ff80u, 0xff80ff80u, 0u, 0u);
        int* hist = reinterpret_cast<int*>(smem + K1_WBYTES);
        int* loff = hist + MAXBINS;
        int* gbase = loff + MAXBINS;
        uint2* sorted = reinterpret_cast<uint2*>(smem + K1_WBYTES + 3 * MAXBINS * 4);
        for (int beg = blockIdx.x * chunk; beg < E; beg += gridDim.x * chunk) {
            const int end = min(E, beg + chunk);
            int d[P1_EPT]; uint32_t rec[P1_EPT]; int rk[P1_EPT]; int bn[P1_EPT];
            #pragma unroll
            for (int i = 0; i < P1_EPT; i++) {
                int e = beg + i * 256 + tid;
                d[i] = -1;
                if (e < end) {
                    d[i] = __ldg(dst + e);
                    uint32_t s = (uint32_t)__ldg(src + e);
                    uint32_t ev = (uint32_t)__ldg(reinterpret_cast<const unsigned short*>(e_attr) + e);
                    rec[i] = (ev << 16) | s;
                }
            }
            hist[tid] = 0;
            p1_bar();
            #pragma unroll
            for (int i = 0; i < P1_EPT; i++) {
                if (d[i] >= 0) {
                    bn[i] = (int)(((uint64_t)(uint32_t)d[i] * magic) >> 24);
                    rk[i] = atomicAdd(&hist[bn[i]], 1);
                }
            }
            p1_bar();
            {
                int h = hist[tid];
                if (tid < nbins && h > 0) gbase[tid] = atomicAdd(&g_bin_cnt[tid], h);
                if (tid < 32) {
                    int v[8]; int sum = 0;
                    #pragma unroll
                    for (int i = 0; i < 8; i++) { v[i] = hist[lane * 8 + i]; sum += v[i]; }
                    int inc = sum;
                    #pragma unroll
                    for (int o = 1; o < 32; o <<= 1) { int t = __shfl_up_sync(0xffffffffu, inc, o); if (lane >= o) inc += t; }
                    int run = inc - sum;
                    #pragma unroll
                    for (int i = 0; i < 8; i++) { loff[lane * 8 + i] = run; run += v[i]; }
                }
            }
            p1_bar();
            #pragma unroll
            for (int i = 0; i < P1_EPT; i++) {
                if (d[i] >= 0) sorted[loff[bn[i]] + rk[i]] = make_uint2(rec[i], (uint32_t)d[i]);
            }
            p1_bar();
            const int cnt = end - beg;
            for (int i = tid; i < cnt; i += 256) {
                uint2 r = sorted[i];
                int b = (int)(((uint64_t)r.y * magic) >> 24);
                int pos = gbase[b] + (i - loff[b]);
                if (pos < BINCAP) {
                    g_bins[b * BINCAP + pos] = make_uint2(r.x, r.y - (uint32_t)(b * NB));
                } else {
                    int p = atomicAdd(&g_ovf_cnt, 2);
                    g_ovf[p] = (int)r.y; g_ovf[p + 1] = (int)r.x;
                }
            }
            p1_bar();
        }
        return;
    }

    const int q = lane & 3;
    const int n_tasks = ((N + 15) >> 4) * 2;
    int task = blockIdx.x * K1_GW + warp;
    uint4 X0[4], X1[4];
    int r0 = (task >> 1) * 16 + (lane >> 2);
    if (task < n_tasks) load_x_frags(X0, X1, x, r0, N, q);
    const uint32_t sbase = (uint32_t)__cvta_generic_to_shared(smem);
    stage_weight(sbase, w_b, threadIdx.x, K1_GW * 32);
    stage_weight(sbase + 32768, w_v, threadIdx.x, K1_GW * 32);
    stage_weight(sbase + 65536, w_a, threadIdx.x, K1_GW * 32);
    stage_weight(sbase + 98304, w_u, threadIdx.x, K1_GW * 32);
    asm volatile("cp.async.wait_all;" ::: "memory");
    asm volatile("bar.sync 2, %0;" :: "n"(K1_GW * 32) : "memory");
    while (task < n_tasks) {
        const int m0 = (task & 1) * 4;
        #pragma unroll 2
        for (int m = m0; m < m0 + 4; m++) {
            uint4 o0, o1;
            gemm_group(X0, X1, sbase, m, lane, o0, o1);
            if (r0 < N) g_T[(size_t)r0 * 32 + 4 * m + q] = o0;
            if (r0 + 8 < N) g_T[(size_t)(r0 + 8) * 32 + 4 * m + q] = o1;
        }
        #pragma unroll 2
        for (int m = m0; m < m0 + 4; m++) {
            uint4 o0, o1;
            gemm_group(X0, X1, sbase + 65536, m, lane, o0, o1);
            if (r0 < N) g_AU[(size_t)r0 * 32 + 4 * m + q] = o0;
            if (r0 + 8 < N) g_AU[(size_t)(r0 + 8) * 32 + 4 * m + q] = o1;
        }
        task += gridDim.x * K1_GW;
        if (task < n_tasks) {
            r0 = (task >> 1) * 16 + (lane >> 2);
            load_x_frags(X0, X1, x, r0, N, q);
        }
    }
}

__device__ __forceinline__ void edge_accum(const uint4 v, const float e, const float a[4], const float cc[4],
                                           float num[4], float den[4]) {
    float y0 = fmaf(bf_lo(v.x), -LOG2E, fmaf(e, cc[0], a[0]));
    float y1 = fmaf(bf_hi(v.x), -LOG2E, fmaf(e, cc[1], a[1]));
    float y2 = fmaf(bf_lo(v.y), -LOG2E, fmaf(e, cc[2], a[2]));
    float y3 = fmaf(bf_hi(v.y), -LOG2E, fmaf(e, cc[3], a[3]));
    float s0 = rcp_approx(1.f + ex2_approx(y0));
    float s1 = rcp_approx(1.f + ex2_approx(y1));
    float s2 = rcp_approx(1.f + ex2_approx(y2));
    float s3 = rcp_approx(1.f + ex2_approx(y3));
    den[0] += s0; den[1] += s1; den[2] += s2; den[3] += s3;
    num[0] = fmaf(s0, bf_lo(v.z), num[0]);
    num[1] = fmaf(s1, bf_hi(v.z), num[1]);
    num[2] = fmaf(s2, bf_lo(v.w), num[2]);
    num[3] = fmaf(s3, bf_hi(v.w), num[3]);
}

#define K2_THREADS 512
#define K2_D 3
#define K2_DYN_SMEM (100 * 1024)
#define K2_RPT ((BINCAP + K2_THREADS - 1) / K2_THREADS)
#define K2_NW (K2_THREADS / 32)
#define SORT_WORDS (BINCAP + 4 * MAXNB)

struct Grp { uint4 v[4]; };

__device__ __forceinline__ const uint4* row_ptr(const char* Tl, uint32_t rec) {
    return reinterpret_cast<const uint4*>(Tl + (size_t)((rec & 0xffffu) * 512u));
}
__device__ __forceinline__ void grp_load(Grp& g, const uint32_t* sp, const char* Tl) {
    const uint4 t = *reinterpret_cast<const uint4*>(sp);
    g.v[0] = __ldg(row_ptr(Tl, t.x));
    g.v[1] = __ldg(row_ptr(Tl, t.y));
    g.v[2] = __ldg(row_ptr(Tl, t.z));
    g.v[3] = __ldg(row_ptr(Tl, t.w));
}
__device__ __forceinline__ void grp_consume(const Grp& g, const uint32_t* sp, const float a[4], const float cc[4],
                                            float num[4], float den[4]) {
    const uint4 t = *reinterpret_cast<const uint4*>(sp);
    edge_accum(g.v[0], bf_hi(t.x), a, cc, num, den);
    edge_accum(g.v[1], bf_hi(t.y), a, cc, num, den);
    edge_accum(g.v[2], bf_hi(t.z), a, cc, num, den);
    edge_accum(g.v[3], bf_hi(t.w), a, cc, num, den);
}

__global__ void __launch_bounds__(K2_THREADS, 1) k2_kernel(
    const __nv_bfloat16* __restrict__ x,
    const __nv_bfloat16* __restrict__ w_c, __nv_bfloat16* __restrict__ out, int N, int NB)
{
    __shared__ __align__(16) uint32_t s_sorted[SORT_WORDS];
    __shared__ int s_hist[MAXNB];
    __shared__ int s_off[MAXNB + 1];

    const int tid = threadIdx.x;
    const int lane = tid & 31, warp = tid >> 5;
    const int bin = blockIdx.x;
    const int node0 = bin * NB;
    const int nn = min(NB, N - node0);

    if (tid < MAXNB) s_hist[tid] = 0;
    for (int i = tid; i < SORT_WORDS; i += K2_THREADS) s_sorted[i] = (uint32_t)N;
    __syncthreads();
    const int fw = (lane >> 2) * 8 + (lane & 3);
    const uint2 wc = make_uint2(__ldg(reinterpret_cast<const uint32_t*>(w_c) + fw), __ldg(reinterpret_cast<const uint32_t*>(w_c) + fw + 4));
    const uint32_t* x32 = reinterpret_cast<const uint32_t*>(x) + fw;
    uint32_t* out32 = reinterpret_cast<uint32_t*>(out) + fw;
    const float cc[4] = { -LOG2E * bf_lo(wc.x), -LOG2E * bf_hi(wc.x), -LOG2E * bf_lo(wc.y), -LOG2E * bf_hi(wc.y) };

    asm volatile("griddepcontrol.wait;" ::: "memory");

    const int cnt = min(g_bin_cnt[bin], BINCAP);
    const int ovf_n = g_ovf_cnt;
    {
        uint2 r[K2_RPT]; int rk[K2_RPT];
        #pragma unroll
        for (int i = 0; i < K2_RPT; i++) {
            int idx = i * K2_THREADS + tid;
            if (idx < cnt) r[i] = g_bins[bin * BINCAP + idx];
        }
        #pragma unroll
        for (int i = 0; i < K2_RPT; i++) {
            int idx = i * K2_THREADS + tid;
            if (idx < cnt) rk[i] = atomicAdd(&s_hist[r[i].y], 1);
        }
        __syncthreads();
        if (warp == 0) {
            int v[4]; int sum = 0;
            #pragma unroll
            for (int i = 0; i < 4; i++) { v[i] = (s_hist[lane * 4 + i] + 3) & ~3; sum += v[i]; }
            int inc = sum;
            #pragma unroll
            for (int o = 1; o < 32; o <<= 1) { int t = __shfl_up_sync(0xffffffffu, inc, o); if (lane >= o) inc += t; }
            int run = inc - sum;
            #pragma unroll
            for (int i = 0; i < 4; i++) { s_off[lane * 4 + i] = run; run += v[i]; }
            if (lane == 31) s_off[MAXNB] = run;
        }
        if (tid == 32) g_bin_cnt[bin] = 0;
        __syncthreads();
        #pragma unroll
        for (int i = 0; i < K2_RPT; i++) {
            int idx = i * K2_THREADS + tid;
            if (idx < cnt) s_sorted[s_off[r[i].y] + rk[i]] = r[i].x;
        }
        __syncthreads();
    }

    const char* Tl = reinterpret_cast<const char*>(g_T) + lane * 16;
    int ln, ln_end;
    {
        const int total = s_off[MAXNB];
        const int lo = (int)(((long long)total * warp) / K2_NW);
        const int hi = (int)(((long long)total * (warp + 1)) / K2_NW);
        int c_lo = 0, c_hi = 0;
        #pragma unroll
        for (int i = 0; i < 4; i++) {
            int node = i * 32 + lane;
            int o = (node < nn) ? s_off[node] : 0x7fffffff;
            c_lo += __popc(__ballot_sync(0xffffffffu, o < lo));
            c_hi += __popc(__ballot_sync(0xffffffffu, o < hi));
        }
        ln = c_lo; ln_end = (warp == K2_NW - 1) ? nn : c_hi;
        if (warp == 0) ln = 0;
    }
    if (ln < ln_end) {
        int g = s_off[ln] >> 2;
        const int g_end = s_off[ln_end] >> 2;
        Grp b0, b1, b2;
        if (g < g_end) grp_load(b0, s_sorted + 4 * g, Tl);
        if (g + 1 < g_end) grp_load(b1, s_sorted + 4 * (g + 1), Tl);
        if (g + 2 < g_end) grp_load(b2, s_sorted + 4 * (g + 2), Tl);
        uint2 xv = make_uint2(__ldg(x32 + (size_t)(node0 + ln) * 64), __ldg(x32 + (size_t)(node0 + ln) * 64 + 4));
        uint4 au = g_AU[(size_t)(node0 + ln) * 32 + lane];
        uint4 au_n; uint2 xv_n;
        if (ln + 1 < ln_end) {
            au_n = g_AU[(size_t)(node0 + ln + 1) * 32 + lane];
            xv_n = make_uint2(__ldg(x32 + (size_t)(node0 + ln + 1) * 64), __ldg(x32 + (size_t)(node0 + ln + 1) * 64 + 4));
        }
        float a[4] = { -LOG2E * bf_lo(au.x), -LOG2E * bf_hi(au.x), -LOG2E * bf_lo(au.y), -LOG2E * bf_hi(au.y) };
        float num[4] = {0.f, 0.f, 0.f, 0.f}, den[4] = {0.f, 0.f, 0.f, 0.f};
        int node_end = s_off[ln + 1] >> 2;

        #define FINISH_NODES() \
        while (g == node_end) { \
            const int n = node0 + ln; \
            if (ovf_n != 0) { \
                for (int base = 0; base < ovf_n; base += 64) { \
                    int i2 = base + 2 * lane; \
                    int od = (i2 < ovf_n) ? g_ovf[i2] : -1; \
                    uint32_t orec = (i2 < ovf_n) ? (uint32_t)g_ovf[i2 + 1] : 0u; \
                    unsigned msk = __ballot_sync(0xffffffffu, od == n); \
                    while (msk) { \
                        int l = __ffs(msk) - 1; msk &= msk - 1; \
                        uint32_t r = __shfl_sync(0xffffffffu, orec, l); \
                        uint4 v = __ldg(row_ptr(Tl, r)); \
                        edge_accum(v, bf_hi(r), a, cc, num, den); \
                    } \
                } \
            } \
            { \
                const float u4[4] = { bf_lo(au.z), bf_hi(au.z), bf_lo(au.w), bf_hi(au.w) }; \
                const float x4[4] = { bf_lo(xv.x), bf_hi(xv.x), bf_lo(xv.y), bf_hi(xv.y) }; \
                float o[4]; \
                _Pragma("unroll") for (int i = 0; i < 4; i++) { \
                    float agg = round_bf16(__fdividef(num[i], den[i] + 1e-6f)); \
                    float z = round_bf16(u4[i] + agg); \
                    float rz = (z > 0.f) ? z : 0.f * z; \
                    o[i] = x4[i] + rz; \
                    num[i] = 0.f; den[i] = 0.f; \
                } \
                out32[(size_t)n * 64] = pack_bf16(o[0], o[1]); out32[(size_t)n * 64 + 4] = pack_bf16(o[2], o[3]); \
            } \
            ln++; \
            if (ln >= ln_end) goto done; \
            au = au_n; xv = xv_n; \
            if (ln + 1 < ln_end) { \
                au_n = g_AU[(size_t)(node0 + ln + 1) * 32 + lane]; \
                xv_n = make_uint2(__ldg(x32 + (size_t)(node0 + ln + 1) * 64), __ldg(x32 + (size_t)(node0 + ln + 1) * 64 + 4)); \
            } \
            a[0] = -LOG2E * bf_lo(au.x); a[1] = -LOG2E * bf_hi(au.x); a[2] = -LOG2E * bf_lo(au.y); a[3] = -LOG2E * bf_hi(au.y); \
            node_end = s_off[ln + 1] >> 2; \
        }
        #define STEP(B) \
            FINISH_NODES(); \
            grp_consume(B, s_sorted + 4 * g, a, cc, num, den); \
            if (g + K2_D < g_end) grp_load(B, s_sorted + 4 * (g + K2_D), Tl); \
            g++;
        while (true) {
            STEP(b0);
            STEP(b1);
            STEP(b2);
        }
        done:;
    }
    if (ovf_n != 0) {
        __syncthreads();
        if (tid == 0) {
            __threadfence();
            int t = atomicAdd(&g_done, 1);
            if (t == (int)gridDim.x - 1) { g_done = 0; __threadfence(); g_ovf_cnt = 0; }
        }
    }
}

extern "C" void kernel_launch(void* const* d_in, const int* in_sizes, int n_in,
                              void* d_out, int out_size) {
    const __nv_bfloat16* x      = (const __nv_bfloat16*)d_in[0];
    const __nv_bfloat16* e_attr = (const __nv_bfloat16*)d_in[1];
    const int* src = (const int*)d_in[2];
    const int* dst = (const int*)d_in[3];
    const __nv_bfloat16* w_a = (const __nv_bfloat16*)d_in[4];
    const __nv_bfloat16* w_b = (const __nv_bfloat16*)d_in[5];
    const __nv_bfloat16* w_c = (const __nv_bfloat16*)d_in[6];
    const __nv_bfloat16* w_u = (const __nv_bfloat16*)d_in[7];
    const __nv_bfloat16* w_v = (const __nv_bfloat16*)d_in[8];
    __nv_bfloat16* out = (__nv_bfloat16*)d_out;
    const int N = in_sizes[0] / D_FEAT;
    const int E = in_sizes[2];
    if (N > MAX_N || 2 * E > MAX_E || N <= 0) return;

    static int num_sms = 0;
    if (num_sms == 0) {
        int dev = 0;
        cudaGetDevice(&dev);
        cudaDeviceGetAttribute(&num_sms, cudaDevAttrMultiProcessorCount, dev);
        if (num_sms <= 0 || num_sms > MAXBINS) num_sms = 132;
        cudaFuncSetAttribute(k1_kernel, cudaFuncAttributeMaxDynamicSharedMemorySize, K1_SMEM);
        cudaFuncSetAttribute(k2_kernel, cudaFuncAttributeMaxDynamicSharedMemorySize, K2_DYN_SMEM);
    }
    cudaStream_t st = cudaStreamPerThread;
    int NB = (N + num_sms - 1) / num_sms;
    if (NB > MAXNB) NB = MAXNB;
    const int nbins = (N + NB - 1) / NB;
    const uint32_t magic = (uint32_t)(((1u << 24) + NB - 1) / NB);
    const int P = num_sms;
    int chunk = (E + P - 1) / P;
    if (chunk > P1_CHUNK) chunk = P1_CHUNK;
    if (chunk < 1) chunk = 1;
    k1_kernel<<<P, K1_THREADS, K1_SMEM, st>>>(x, e_attr, src, dst, w_b, w_v, w_a, w_u, N, E, chunk, NB, nbins, magic);

    cudaLaunchConfig_t cfg = {};
    cfg.gridDim = dim3(nbins);
    cfg.blockDim = dim3(K2_THREADS);
    cfg.dynamicSmemBytes = K2_DYN_SMEM;
    cfg.stream = st;
    cudaLaunchAttribute at[1];
    at[0].id = cudaLaunchAttributeProgrammaticStreamSerialization;
    at[0].val.programmaticStreamSerializationAllowed = 1;
    cfg.attrs = at; cfg.numAttrs = 1;
    cudaLaunchKernelEx(&cfg, k2_kernel, x, w_c, out, N, NB);
}
```

```cpp
#include <cuda_runtime.h>
#include <cuda_bf16.h>
#include <stdint.h>

#define D_FEAT 128
#define MAX_N 16384
#define MAX_E (1 << 20)
#define LOG2E 1.4426950408889634f

#define MAXBINS 256
#define MAXNB 128
#define BINCAP 3072
__device__ uint4 g_T[(MAX_N + 1) * 32];
__device__ uint4 g_AU[MAX_N * 32];
__device__ int g_bin_cnt[MAXBINS];
__device__ uint2 g_bins[MAXBINS * BINCAP];
__device__ int g_ovf[MAX_E];
__device__ int g_ovf_cnt;
__device__ int g_done;

__device__ __forceinline__ float ex2_approx(float x) {
    float y; asm("ex2.approx.ftz.f32 %0, %1;" : "=f"(y) : "f"(x)); return y;
}
__device__ __forceinline__ float rcp_approx(float x) {
    float y; asm("rcp.approx.ftz.f32 %0, %1;" : "=f"(y) : "f"(x)); return y;
}
__device__ __forceinline__ uint32_t pack_bf16(float lo, float hi) {
    __nv_bfloat162 t = __floats2bfloat162_rn(lo, hi);
    return *reinterpret_cast<uint32_t*>(&t);
}
__device__ __forceinline__ float bf_lo(uint32_t v) { return __uint_as_float(v << 16); }
__device__ __forceinline__ float bf_hi(uint32_t v) { return __uint_as_float(v & 0xffff0000u); }
__device__ __forceinline__ float round_bf16(float x) { return __bfloat162float(__float2bfloat16_rn(x)); }

__device__ __forceinline__ void mma_bf16(float c[4], uint32_t a0, uint32_t a1, uint32_t a2, uint32_t a3,
                                         uint32_t b0, uint32_t b1) {
    asm volatile("mma.sync.aligned.m16n8k16.row.col.f32.bf16.bf16.f32 "
                 "{%0,%1,%2,%3}, {%4,%5,%6,%7}, {%8,%9}, {%0,%1,%2,%3};"
                 : "+f"(c[0]), "+f"(c[1]), "+f"(c[2]), "+f"(c[3])
                 : "r"(a0), "r"(a1), "r"(a2), "r"(a3), "r"(b0), "r"(b1));
}
__device__ __forceinline__ void ldmatrix_x4_trans(uint32_t& r0, uint32_t& r1, uint32_t& r2, uint32_t& r3, uint32_t addr) {
    asm volatile("ldmatrix.sync.aligned.m8n8.x4.trans.shared.b16 {%0,%1,%2,%3}, [%4];"
                 : "=r"(r0), "=r"(r1), "=r"(r2), "=r"(r3) : "r"(addr));
}

__device__ __forceinline__ void cp_async16(uint32_t saddr, const void* g) {
    asm volatile("cp.async.cg.shared.global [%0], [%1], 16;" :: "r"(saddr), "l"(g) : "memory");
}
__device__ __forceinline__ void stage_weight(uint32_t sdst, const __nv_bfloat16* w, int mtx, int tid, int nthreads) {
    const uint4* W = reinterpret_cast<const uint4*>(w);
    for (int u = tid; u < 2048; u += nthreads) {
        int k = u >> 4, c16 = u & 15;
        int kg = ((k >> 5) << 2) | (((k >> 2) & 1) << 1) | ((k >> 1) & 1);
        int rr = (((k >> 3) & 3) << 1) | (k & 1);
        int h = mtx * 2 + (c16 >> 3);
        cp_async16(sdst + kg * 4096 + h * 1024 + rr * 128 + (((c16 & 7) ^ rr) << 4), W + u);
    }
}

__device__ __forceinline__ void load_x_frags(uint4 X0[4], uint4 X1[4], const __nv_bfloat16* x, int r0, int N, int q) {
    const uint4* xr0 = reinterpret_cast<const uint4*>(x) + (size_t)r0 * 16 + q;
    const uint4* xr1 = xr0 + 8 * 16;
    #pragma unroll
    for (int c = 0; c < 4; c++) {
        X0[c] = (r0 < N) ? __ldg(xr0 + c * 4) : make_uint4(0, 0, 0, 0);
        X1[c] = (r0 + 8 < N) ? __ldg(xr1 + c * 4) : make_uint4(0, 0, 0, 0);
    }
}

__device__ __forceinline__ void wgmma_m64n128k16(float d[64], uint32_t a0, uint32_t a1, uint32_t a2, uint32_t a3,
                                                 uint64_t desc, int scale_d) {
    asm volatile("{\n.reg .pred p;\nsetp.ne.b32 p, %69, 0;\n"
                 "wgmma.mma_async.sync.aligned.m64n128k16.f32.bf16.bf16 {%0,%1,%2,%3,%4,%5,%6,%7,%8,%9,%10,%11,%12,%13,%14,%15,%16,%17,%18,%19,%20,%21,%22,%23,%24,%25,%26,%27,%28,%29,%30,%31,%32,%33,%34,%35,%36,%37,%38,%39,%40,%41,%42,%43,%44,%45,%46,%47,%48,%49,%50,%51,%52,%53,%54,%55,%56,%57,%58,%59,%60,%61,%62,%63}, {%64,%65,%66,%67}, %68, p, 1, 1, 1;\n}"
                 : "+f"(d[0]),"+f"(d[1]),"+f"(d[2]),"+f"(d[3]),"+f"(d[4]),"+f"(d[5]),"+f"(d[6]),"+f"(d[7]),"+f"(d[8]),"+f"(d[9]),"+f"(d[10]),"+f"(d[11]),"+f"(d[12]),"+f"(d[13]),"+f"(d[14]),"+f"(d[15]),"+f"(d[16]),"+f"(d[17]),"+f"(d[18]),"+f"(d[19]),"+f"(d[20]),"+f"(d[21]),"+f"(d[22]),"+f"(d[23]),"+f"(d[24]),"+f"(d[25]),"+f"(d[26]),"+f"(d[27]),"+f"(d[28]),"+f"(d[29]),"+f"(d[30]),"+f"(d[31]),"+f"(d[32]),"+f"(d[33]),"+f"(d[34]),"+f"(d[35]),"+f"(d[36]),"+f"(d[37]),"+f"(d[38]),"+f"(d[39]),"+f"(d[40]),"+f"(d[41]),"+f"(d[42]),"+f"(d[43]),"+f"(d[44]),"+f"(d[45]),"+f"(d[46]),"+f"(d[47]),"+f"(d[48]),"+f"(d[49]),"+f"(d[50]),"+f"(d[51]),"+f"(d[52]),"+f"(d[53]),"+f"(d[54]),"+f"(d[55]),"+f"(d[56]),"+f"(d[57]),"+f"(d[58]),"+f"(d[59]),"+f"(d[60]),"+f"(d[61]),"+f"(d[62]),"+f"(d[63])
                 : "r"(a0), "r"(a1), "r"(a2), "r"(a3), "l"(desc), "r"(scale_d));
}

#define K1_GW 8
#define K1_THREADS ((K1_GW + 8) * 32)
#define P1_EPT 10
#define P1_CHUNK (256 * P1_EPT)
#define K1_WBYTES 131072
#define K1_SMEM (K1_WBYTES + 3 * MAXBINS * 4 + P1_CHUNK * 8)

__device__ __forceinline__ void p1_bar() { asm volatile("bar.sync 1, 256;" ::: "memory"); }

__global__ void __launch_bounds__(K1_THREADS, 1) k1_kernel(
    const __nv_bfloat16* __restrict__ x, const __nv_bfloat16* __restrict__ e_attr,
    const int* __restrict__ src, const int* __restrict__ dst,
    const __nv_bfloat16* __restrict__ w_b, const __nv_bfloat16* __restrict__ w_v,
    const __nv_bfloat16* __restrict__ w_a, const __nv_bfloat16* __restrict__ w_u,
    int N, int E, int chunk, int NB, int nbins, uint32_t magic)
{
    extern __shared__ __align__(1024) uint8_t smem[];
    asm volatile("griddepcontrol.launch_dependents;");

    const int warp = threadIdx.x >> 5, lane = threadIdx.x & 31;

    if (warp >= K1_GW) {
        const int tid = threadIdx.x - K1_GW * 32;
        if (blockIdx.x == 0 && tid < 32)
            g_T[(size_t)N * 32 + tid] = make_uint4(0xff80ff80u, 0xff80ff80u, 0u, 0u);
        int* hist = reinterpret_cast<int*>(smem + K1_WBYTES);
        int* loff = hist + MAXBINS;
        int* gbase = loff + MAXBINS;
        uint2* sorted = reinterpret_cast<uint2*>(smem + K1_WBYTES + 3 * MAXBINS * 4);
        for (int beg = blockIdx.x * chunk; beg < E; beg += gridDim.x * chunk) {
            const int end = min(E, beg + chunk);
            int d[P1_EPT]; uint32_t rec[P1_EPT]; int rk[P1_EPT]; int bn[P1_EPT];
            #pragma unroll
            for (int i = 0; i < P1_EPT; i++) {
                int e = beg + i * 256 + tid;
                d[i] = -1;
                if (e < end) {
                    d[i] = __ldg(dst + e);
                    uint32_t s = (uint32_t)__ldg(src + e);
                    uint32_t ev = (uint32_t)__ldg(reinterpret_cast<const unsigned short*>(e_attr) + e);
                    rec[i] = (ev << 16) | s;
                }
            }
            hist[tid] = 0;
            p1_bar();
            #pragma unroll
            for (int i = 0; i < P1_EPT; i++) {
                if (d[i] >= 0) {
                    bn[i] = (int)(((uint64_t)(uint32_t)d[i] * magic) >> 24);
                    rk[i] = atomicAdd(&hist[bn[i]], 1);
                }
            }
            p1_bar();
            {
                int h = hist[tid];
                if (tid < nbins && h > 0) gbase[tid] = atomicAdd(&g_bin_cnt[tid], h);
                if (tid < 32) {
                    int v[8]; int sum = 0;
                    #pragma unroll
                    for (int i = 0; i < 8; i++) { v[i] = hist[lane * 8 + i]; sum += v[i]; }
                    int inc = sum;
                    #pragma unroll
                    for (int o = 1; o < 32; o <<= 1) { int t = __shfl_up_sync(0xffffffffu, inc, o); if (lane >= o) inc += t; }
                    int run = inc - sum;
                    #pragma unroll
                    for (int i = 0; i < 8; i++) { loff[lane * 8 + i] = run; run += v[i]; }
                }
            }
            p1_bar();
            #pragma unroll
            for (int i = 0; i < P1_EPT; i++) {
                if (d[i] >= 0) sorted[loff[bn[i]] + rk[i]] = make_uint2(rec[i], (uint32_t)d[i]);
            }
            p1_bar();
            const int cnt = end - beg;
            for (int i = tid; i < cnt; i += 256) {
                uint2 r = sorted[i];
                int b = (int)(((uint64_t)r.y * magic) >> 24);
                int pos = gbase[b] + (i - loff[b]);
                if (pos < BINCAP) {
                    g_bins[b * BINCAP + pos] = make_uint2(r.x, r.y - (uint32_t)(b * NB));
                } else {
                    int p = atomicAdd(&g_ovf_cnt, 2);
                    g_ovf[p] = (int)r.y; g_ovf[p + 1] = (int)r.x;
                }
            }
            p1_bar();
        }
        return;
    }

    const int q = lane & 3;
    const int wg = warp >> 2;
    const int n_tasks = ((N + 63) >> 6) * 4;
    int task = blockIdx.x * 2 + wg;
    uint4 X0[4], X1[4];
    int r0 = (task >> 2) * 64 + (warp & 3) * 16 + (lane >> 2);
    if (task < n_tasks) load_x_frags(X0, X1, x, r0, N, q);
    const uint32_t sbase = (uint32_t)__cvta_generic_to_shared(smem);
    stage_weight(sbase, w_b, 0, threadIdx.x, K1_GW * 32);
    stage_weight(sbase, w_v, 1, threadIdx.x, K1_GW * 32);
    stage_weight(sbase + 65536, w_a, 0, threadIdx.x, K1_GW * 32);
    stage_weight(sbase + 65536, w_u, 1, threadIdx.x, K1_GW * 32);
    asm volatile("cp.async.wait_all;" ::: "memory");
    asm volatile("fence.proxy.async.shared::cta;" ::: "memory");
    asm volatile("bar.sync 2, %0;" :: "n"(K1_GW * 32) : "memory");
    while (task < n_tasks) {
        const int type = (task >> 1) & 1, hf = task & 1;
        const uint32_t saddr = sbase + type * 65536 + hf * 1024;
        const uint64_t desc0 = (uint64_t)((saddr & 0x3FFFF) >> 4) | ((uint64_t)(2048 >> 4) << 16) |
                               ((uint64_t)(4096 >> 4) << 32) | ((uint64_t)1 << 62);
        float d[64];
        #pragma unroll
        for (int i = 0; i < 64; i++) d[i] = 0.f;
        asm volatile("wgmma.fence.sync.aligned;" ::: "memory");
        #pragma unroll
        for (int c = 0; c < 4; c++) {
            wgmma_m64n128k16(d, X0[c].x, X1[c].x, X0[c].y, X1[c].y, desc0 + (uint64_t)((2 * c) * (8192 >> 4)), 1);
            wgmma_m64n128k16(d, X0[c].z, X1[c].z, X0[c].w, X1[c].w, desc0 + (uint64_t)((2 * c + 1) * (8192 >> 4)), 1);
        }
        asm volatile("wgmma.commit_group.sync.aligned;" ::: "memory");
        asm volatile("wgmma.wait_group.sync.aligned 0;" ::: "memory");
        uint4* outp = (type ? g_AU : g_T);
        #pragma unroll
        for (int mm = 0; mm < 4; mm++) {
            const int j0 = 2 * mm, j1 = 2 * mm + 1, j2 = 8 + 2 * mm, j3 = 9 + 2 * mm;
            uint4 o0 = make_uint4(pack_bf16(d[4 * j0], d[4 * j0 + 1]), pack_bf16(d[4 * j1], d[4 * j1 + 1]),
                                  pack_bf16(d[4 * j2], d[4 * j2 + 1]), pack_bf16(d[4 * j3], d[4 * j3 + 1]));
            uint4 o1 = make_uint4(pack_bf16(d[4 * j0 + 2], d[4 * j0 + 3]), pack_bf16(d[4 * j1 + 2], d[4 * j1 + 3]),
                                  pack_bf16(d[4 * j2 + 2], d[4 * j2 + 3]), pack_bf16(d[4 * j3 + 2], d[4 * j3 + 3]));
            const int m = 4 * hf + mm;
            if (r0 < N) outp[(size_t)r0 * 32 + 4 * m + q] = o0;
            if (r0 + 8 < N) outp[(size_t)(r0 + 8) * 32 + 4 * m + q] = o1;
        }
        task += gridDim.x * 2;
        if (task < n_tasks) {
            r0 = (task >> 2) * 64 + (warp & 3) * 16 + (lane >> 2);
            load_x_frags(X0, X1, x, r0, N, q);
        }
    }
}

__device__ __forceinline__ void edge_accum(const uint4 v, const float e, const float a[4], const float cc[4],
                                           float num[4], float den[4]) {
    float y0 = fmaf(bf_lo(v.x), -LOG2E, fmaf(e, cc[0], a[0]));
    float y1 = fmaf(bf_hi(v.x), -LOG2E, fmaf(e, cc[1], a[1]));
    float y2 = fmaf(bf_lo(v.y), -LOG2E, fmaf(e, cc[2], a[2]));
    float y3 = fmaf(bf_hi(v.y), -LOG2E, fmaf(e, cc[3], a[3]));
    float s0 = rcp_approx(1.f + ex2_approx(y0));
    float s1 = rcp_approx(1.f + ex2_approx(y1));
    float s2 = rcp_approx(1.f + ex2_approx(y2));
    float s3 = rcp_approx(1.f + ex2_approx(y3));
    den[0] += s0; den[1] += s1; den[2] += s2; den[3] += s3;
    num[0] = fmaf(s0, bf_lo(v.z), num[0]);
    num[1] = fmaf(s1, bf_hi(v.z), num[1]);
    num[2] = fmaf(s2, bf_lo(v.w), num[2]);
    num[3] = fmaf(s3, bf_hi(v.w), num[3]);
}

#define K2_THREADS 512
#define K2_D 3
#define K2_DYN_SMEM (100 * 1024)
#define K2_RPT ((BINCAP + K2_THREADS - 1) / K2_THREADS)
#define K2_NW (K2_THREADS / 32)
#define SORT_WORDS (BINCAP + 4 * MAXNB)

struct Grp { uint4 v[4]; };

__device__ __forceinline__ const uint4* row_ptr(const char* Tl, uint32_t rec) {
    return reinterpret_cast<const uint4*>(Tl + (size_t)((rec & 0xffffu) * 512u));
}
__device__ __forceinline__ void grp_load(Grp& g, const uint32_t* sp, const char* Tl) {
    const uint4 t = *reinterpret_cast<const uint4*>(sp);
    g.v[0] = __ldg(row_ptr(Tl, t.x));
    g.v[1] = __ldg(row_ptr(Tl, t.y));
    g.v[2] = __ldg(row_ptr(Tl, t.z));
    g.v[3] = __ldg(row_ptr(Tl, t.w));
}
__device__ __forceinline__ void grp_consume(const Grp& g, const uint32_t* sp, const float a[4], const float cc[4],
                                            float num[4], float den[4]) {
    const uint4 t = *reinterpret_cast<const uint4*>(sp);
    edge_accum(g.v[0], bf_hi(t.x), a, cc, num, den);
    edge_accum(g.v[1], bf_hi(t.y), a, cc, num, den);
    edge_accum(g.v[2], bf_hi(t.z), a, cc, num, den);
    edge_accum(g.v[3], bf_hi(t.w), a, cc, num, den);
}

__global__ void __launch_bounds__(K2_THREADS, 1) k2_kernel(
    const __nv_bfloat16* __restrict__ x,
    const __nv_bfloat16* __restrict__ w_c, __nv_bfloat16* __restrict__ out, int N, int NB)
{
    __shared__ __align__(16) uint32_t s_sorted[SORT_WORDS];
    __shared__ int s_hist[MAXNB];
    __shared__ int s_off[MAXNB + 1];

    const int tid = threadIdx.x;
    const int lane = tid & 31, warp = tid >> 5;
    const int bin = blockIdx.x;
    const int node0 = bin * NB;
    const int nn = min(NB, N - node0);

    if (tid < MAXNB) s_hist[tid] = 0;
    for (int i = tid; i < SORT_WORDS; i += K2_THREADS) s_sorted[i] = (uint32_t)N;
    __syncthreads();
    const int fw = (lane >> 2) * 8 + (lane & 3);
    const uint2 wc = make_uint2(__ldg(reinterpret_cast<const uint32_t*>(w_c) + fw), __ldg(reinterpret_cast<const uint32_t*>(w_c) + fw + 4));
    const uint32_t* x32 = reinterpret_cast<const uint32_t*>(x) + fw;
    uint32_t* out32 = reinterpret_cast<uint32_t*>(out) + fw;
    const float cc[4] = { -LOG2E * bf_lo(wc.x), -LOG2E * bf_hi(wc.x), -LOG2E * bf_lo(wc.y), -LOG2E * bf_hi(wc.y) };

    asm volatile("griddepcontrol.wait;" ::: "memory");

    const int cnt = min(g_bin_cnt[bin], BINCAP);
    const int ovf_n = g_ovf_cnt;
    {
        uint2 r[K2_RPT]; int rk[K2_RPT];
        #pragma unroll
        for (int i = 0; i < K2_RPT; i++) {
            int idx = i * K2_THREADS + tid;
            if (idx < cnt) r[i] = g_bins[bin * BINCAP + idx];
        }
        #pragma unroll
        for (int i = 0; i < K2_RPT; i++) {
            int idx = i * K2_THREADS + tid;
            if (idx < cnt) rk[i] = atomicAdd(&s_hist[r[i].y], 1);
        }
        __syncthreads();
        if (warp == 0) {
            int v[4]; int sum = 0;
            #pragma unroll
            for (int i = 0; i < 4; i++) { v[i] = (s_hist[lane * 4 + i] + 3) & ~3; sum += v[i]; }
            int inc = sum;
            #pragma unroll
            for (int o = 1; o < 32; o <<= 1) { int t = __shfl_up_sync(0xffffffffu, inc, o); if (lane >= o) inc += t; }
            int run = inc - sum;
            #pragma unroll
            for (int i = 0; i < 4; i++) { s_off[lane * 4 + i] = run; run += v[i]; }
            if (lane == 31) s_off[MAXNB] = run;
        }
        if (tid == 32) g_bin_cnt[bin] = 0;
        __syncthreads();
        #pragma unroll
        for (int i = 0; i < K2_RPT; i++) {
            int idx = i * K2_THREADS + tid;
            if (idx < cnt) s_sorted[s_off[r[i].y] + rk[i]] = r[i].x;
        }
        __syncthreads();
    }

    const char* Tl = reinterpret_cast<const char*>(g_T) + lane * 16;
    int ln, ln_end;
    {
        const int total = s_off[MAXNB];
        const int lo = (int)(((long long)total * warp) / K2_NW);
        const int hi = (int)(((long long)total * (warp + 1)) / K2_NW);
        int c_lo = 0, c_hi = 0;
        #pragma unroll
        for (int i = 0; i < 4; i++) {
            int node = i * 32 + lane;
            int o = (node < nn) ? s_off[node] : 0x7fffffff;
            c_lo += __popc(__ballot_sync(0xffffffffu, o < lo));
            c_hi += __popc(__ballot_sync(0xffffffffu, o < hi));
        }
        ln = c_lo; ln_end = (warp == K2_NW - 1) ? nn : c_hi;
        if (warp == 0) ln = 0;
    }
    if (ln < ln_end) {
        int g = s_off[ln] >> 2;
        const int g_end = s_off[ln_end] >> 2;
        Grp b0, b1, b2;
        if (g < g_end) grp_load(b0, s_sorted + 4 * g, Tl);
        if (g + 1 < g_end) grp_load(b1, s_sorted + 4 * (g + 1), Tl);
        if (g + 2 < g_end) grp_load(b2, s_sorted + 4 * (g + 2), Tl);
        uint2 xv = make_uint2(__ldg(x32 + (size_t)(node0 + ln) * 64), __ldg(x32 + (size_t)(node0 + ln) * 64 + 4));
        uint4 au = g_AU[(size_t)(node0 + ln) * 32 + lane];
        uint4 au_n; uint2 xv_n;
        if (ln + 1 < ln_end) {
            au_n = g_AU[(size_t)(node0 + ln + 1) * 32 + lane];
            xv_n = make_uint2(__ldg(x32 + (size_t)(node0 + ln + 1) * 64), __ldg(x32 + (size_t)(node0 + ln + 1) * 64 + 4));
        }
        float a[4] = { -LOG2E * bf_lo(au.x), -LOG2E * bf_hi(au.x), -LOG2E * bf_lo(au.y), -LOG2E * bf_hi(au.y) };
        float num[4] = {0.f, 0.f, 0.f, 0.f}, den[4] = {0.f, 0.f, 0.f, 0.f};
        int node_end = s_off[ln + 1] >> 2;

        #define FINISH_NODES() \
        while (g == node_end) { \
            const int n = node0 + ln; \
            if (ovf_n != 0) { \
                for (int base = 0; base < ovf_n; base += 64) { \
                    int i2 = base + 2 * lane; \
                    int od = (i2 < ovf_n) ? g_ovf[i2] : -1; \
                    uint32_t orec = (i2 < ovf_n) ? (uint32_t)g_ovf[i2 + 1] : 0u; \
                    unsigned msk = __ballot_sync(0xffffffffu, od == n); \
                    while (msk) { \
                        int l = __ffs(msk) - 1; msk &= msk - 1; \
                        uint32_t r = __shfl_sync(0xffffffffu, orec, l); \
                        uint4 v = __ldg(row_ptr(Tl, r)); \
                        edge_accum(v, bf_hi(r), a, cc, num, den); \
                    } \
                } \
            } \
            { \
                const float u4[4] = { bf_lo(au.z), bf_hi(au.z), bf_lo(au.w), bf_hi(au.w) }; \
                const float x4[4] = { bf_lo(xv.x), bf_hi(xv.x), bf_lo(xv.y), bf_hi(xv.y) }; \
                float o[4]; \
                _Pragma("unroll") for (int i = 0; i < 4; i++) { \
                    float agg = round_bf16(__fdividef(num[i], den[i] + 1e-6f)); \
                    float z = round_bf16(u4[i] + agg); \
                    float rz = (z > 0.f) ? z : 0.f * z; \
                    o[i] = x4[i] + rz; \
                    num[i] = 0.f; den[i] = 0.f; \
                } \
                out32[(size_t)n * 64] = pack_bf16(o[0], o[1]); out32[(size_t)n * 64 + 4] = pack_bf16(o[2], o[3]); \
            } \
            ln++; \
            if (ln >= ln_end) goto done; \
            au = au_n; xv = xv_n; \
            if (ln + 1 < ln_end) { \
                au_n = g_AU[(size_t)(node0 + ln + 1) * 32 + lane]; \
                xv_n = make_uint2(__ldg(x32 + (size_t)(node0 + ln + 1) * 64), __ldg(x32 + (size_t)(node0 + ln + 1) * 64 + 4)); \
            } \
            a[0] = -LOG2E * bf_lo(au.x); a[1] = -LOG2E * bf_hi(au.x); a[2] = -LOG2E * bf_lo(au.y); a[3] = -LOG2E * bf_hi(au.y); \
            node_end = s_off[ln + 1] >> 2; \
        }
        #define STEP(B) \
            FINISH_NODES(); \
            grp_consume(B, s_sorted + 4 * g, a, cc, num, den); \
            if (g + K2_D < g_end) grp_load(B, s_sorted + 4 * (g + K2_D), Tl); \
            g++;
        while (true) {
            STEP(b0);
            STEP(b1);
            STEP(b2);
        }
        done:;
    }
    if (ovf_n != 0) {
        __syncthreads();
        if (tid == 0) {
            __threadfence();
            int t = atomicAdd(&g_done, 1);
            if (t == (int)gridDim.x - 1) { g_done = 0; __threadfence(); g_ovf_cnt = 0; }
        }
    }
}

extern "C" void kernel_launch(void* const* d_in, const int* in_sizes, int n_in,
                              void* d_out, int out_size) {
    const __nv_bfloat16* x      = (const __nv_bfloat16*)d_in[0];
    const __nv_bfloat16* e_attr = (const __nv_bfloat16*)d_in[1];
    const int* src = (const int*)d_in[2];
    const int* dst = (const int*)d_in[3];
    const __nv_bfloat16* w_a = (const __nv_bfloat16*)d_in[4];
    const __nv_bfloat16* w_b = (const __nv_bfloat16*)d_in[5];
    const __nv_bfloat16* w_c = (const __nv_bfloat16*)d_in[6];
    const __nv_bfloat16* w_u = (const __nv_bfloat16*)d_in[7];
    const __nv_bfloat16* w_v = (const __nv_bfloat16*)d_in[8];
    __nv_bfloat16* out = (__nv_bfloat16*)d_out;
    const int N = in_sizes[0] / D_FEAT;
    const int E = in_sizes[2];
    if (N > MAX_N || 2 * E > MAX_E || N <= 0) return;

    static int num_sms = 0;
    if (num_sms == 0) {
        int dev = 0;
        cudaGetDevice(&dev);
        cudaDeviceGetAttribute(&num_sms, cudaDevAttrMultiProcessorCount, dev);
        if (num_sms <= 0 || num_sms > MAXBINS) num_sms = 132;
        cudaFuncSetAttribute(k1_kernel, cudaFuncAttributeMaxDynamicSharedMemorySize, K1_SMEM);
        cudaFuncSetAttribute(k2_kernel, cudaFuncAttributeMaxDynamicSharedMemorySize, K2_DYN_SMEM);
    }
    cudaStream_t st = cudaStreamPerThread;
    int NB = (N + num_sms - 1) / num_sms;
    if (NB > MAXNB) NB = MAXNB;
    const int nbins = (N + NB - 1) / NB;
    const uint32_t magic = (uint32_t)(((1u << 24) + NB - 1) / NB);
    const int P = num_sms;
    int chunk = (E + P - 1) / P;
    if (chunk > P1_CHUNK) chunk = P1_CHUNK;
    if (chunk < 1) chunk = 1;
    k1_kernel<<<P, K1_THREADS, K1_SMEM, st>>>(x, e_attr, src, dst, w_b, w_v, w_a, w_u, N, E, chunk, NB, nbins, magic);

    cudaLaunchConfig_t cfg = {};
    cfg.gridDim = dim3(nbins);
    cfg.blockDim = dim3(K2_THREADS);
    cfg.dynamicSmemBytes = K2_DYN_SMEM;
    cfg.stream = st;
    cudaLaunchAttribute at[1];
    at[0].id = cudaLaunchAttributeProgrammaticStreamSerialization;
    at[0].val.programmaticStreamSerializationAllowed = 1;
    cfg.attrs = at; cfg.numAttrs = 1;
    cudaLaunchKernelEx(&cfg, k2_kernel, x, w_c, out, N, NB);
}
```

```cpp
#include <cuda_runtime.h>
#include <cuda_bf16.h>
#include <stdint.h>

#define D_FEAT 128
#define MAX_N 16384
#define MAX_E (1 << 20)
#define LOG2E 1.4426950408889634f

#define MAXBINS 256
#define MAXNB 128
#define BINCAP 3072
__device__ uint4 g_T[(MAX_N + 1) * 32];
__device__ uint4 g_AU[MAX_N * 32];
__device__ int g_bin_cnt[MAXBINS];
__device__ uint2 g_bins[MAXBINS * BINCAP];
__device__ int g_ovf[MAX_E];
__device__ int g_ovf_cnt;
__device__ int g_done;

__device__ __forceinline__ float ex2_approx(float x) {
    float y; asm("ex2.approx.ftz.f32 %0, %1;" : "=f"(y) : "f"(x)); return y;
}
__device__ __forceinline__ float rcp_approx(float x) {
    float y; asm("rcp.approx.ftz.f32 %0, %1;" : "=f"(y) : "f"(x)); return y;
}
__device__ __forceinline__ uint32_t pack_bf16(float lo, float hi) {
    __nv_bfloat162 t = __floats2bfloat162_rn(lo, hi);
    return *reinterpret_cast<uint32_t*>(&t);
}
__device__ __forceinline__ float bf_lo(uint32_t v) { return __uint_as_float(v << 16); }
__device__ __forceinline__ float bf_hi(uint32_t v) { return __uint_as_float(v & 0xffff0000u); }
__device__ __forceinline__ float round_bf16(float x) { return __bfloat162float(__float2bfloat16_rn(x)); }

__device__ __forceinline__ void mma_bf16(float c[4], uint32_t a0, uint32_t a1, uint32_t a2, uint32_t a3,
                                         uint32_t b0, uint32_t b1) {
    asm volatile("mma.sync.aligned.m16n8k16.row.col.f32.bf16.bf16.f32 "
                 "{%0,%1,%2,%3}, {%4,%5,%6,%7}, {%8,%9}, {%0,%1,%2,%3};"
                 : "+f"(c[0]), "+f"(c[1]), "+f"(c[2]), "+f"(c[3])
                 : "r"(a0), "r"(a1), "r"(a2), "r"(a3), "r"(b0), "r"(b1));
}
__device__ __forceinline__ void ldmatrix_x4_trans(uint32_t& r0, uint32_t& r1, uint32_t& r2, uint32_t& r3, uint32_t addr) {
    asm volatile("ldmatrix.sync.aligned.m8n8.x4.trans.shared.b16 {%0,%1,%2,%3}, [%4];"
                 : "=r"(r0), "=r"(r1), "=r"(r2), "=r"(r3) : "r"(addr));
}

__device__ __forceinline__ void cp_async16(uint32_t saddr, const void* g) {
    asm volatile("cp.async.cg.shared.global [%0], [%1], 16;" :: "r"(saddr), "l"(g) : "memory");
}
__device__ __forceinline__ void cp_async16_zfill(uint32_t saddr, const void* g, int src_size) {
    asm volatile("cp.async.cg.shared.global [%0], [%1], 16, %2;" :: "r"(saddr), "l"(g), "r"(src_size) : "memory");
}
__device__ __forceinline__ void stage_weight(uint32_t sdst, const __nv_bfloat16* w, int mtx, int tid, int nthreads) {
    const uint4* W = reinterpret_cast<const uint4*>(w);
    for (int u = tid; u < 2048; u += nthreads) {
        int k = u >> 4, c16 = u & 15;
        int kg = k >> 3, rr = k & 7;
        int h = mtx * 2 + (c16 >> 3);
        cp_async16(sdst + kg * 4096 + h * 1024 + rr * 128 + (((c16 & 7) ^ rr) << 4), W + u);
    }
}
__device__ __forceinline__ void stage_x_tile(uint32_t sdst, const __nv_bfloat16* x, int row0, int N, int tid, int nthreads) {
    const uint4* X = reinterpret_cast<const uint4*>(x);
    for (int u = tid; u < 1024; u += nthreads) {
        int r = u >> 4, c16 = u & 15;
        int gr = row0 + r;
        bool ok = gr < N;
        cp_async16_zfill(sdst + (c16 >> 3) * 8192 + r * 128 + (((c16 & 7) ^ (r & 7)) << 4),
                         X + (size_t)(ok ? gr : 0) * 16 + c16, ok ? 16 : 0);
    }
}

__device__ __forceinline__ void wgmma_m64n128k16(float d[64], uint64_t desc_a, uint64_t desc_b, int scale_d) {
    asm volatile("{\n.reg .pred p;\nsetp.ne.b32 p, %66, 0;\n"
                 "wgmma.mma_async.sync.aligned.m64n128k16.f32.bf16.bf16 {%0,%1,%2,%3,%4,%5,%6,%7,%8,%9,%10,%11,%12,%13,%14,%15,%16,%17,%18,%19,%20,%21,%22,%23,%24,%25,%26,%27,%28,%29,%30,%31,%32,%33,%34,%35,%36,%37,%38,%39,%40,%41,%42,%43,%44,%45,%46,%47,%48,%49,%50,%51,%52,%53,%54,%55,%56,%57,%58,%59,%60,%61,%62,%63}, %64, %65, p, 1, 1, 0, 1;\n}"
                 : "+f"(d[0]),"+f"(d[1]),"+f"(d[2]),"+f"(d[3]),"+f"(d[4]),"+f"(d[5]),"+f"(d[6]),"+f"(d[7]),"+f"(d[8]),"+f"(d[9]),"+f"(d[10]),"+f"(d[11]),"+f"(d[12]),"+f"(d[13]),"+f"(d[14]),"+f"(d[15]),"+f"(d[16]),"+f"(d[17]),"+f"(d[18]),"+f"(d[19]),"+f"(d[20]),"+f"(d[21]),"+f"(d[22]),"+f"(d[23]),"+f"(d[24]),"+f"(d[25]),"+f"(d[26]),"+f"(d[27]),"+f"(d[28]),"+f"(d[29]),"+f"(d[30]),"+f"(d[31]),"+f"(d[32]),"+f"(d[33]),"+f"(d[34]),"+f"(d[35]),"+f"(d[36]),"+f"(d[37]),"+f"(d[38]),"+f"(d[39]),"+f"(d[40]),"+f"(d[41]),"+f"(d[42]),"+f"(d[43]),"+f"(d[44]),"+f"(d[45]),"+f"(d[46]),"+f"(d[47]),"+f"(d[48]),"+f"(d[49]),"+f"(d[50]),"+f"(d[51]),"+f"(d[52]),"+f"(d[53]),"+f"(d[54]),"+f"(d[55]),"+f"(d[56]),"+f"(d[57]),"+f"(d[58]),"+f"(d[59]),"+f"(d[60]),"+f"(d[61]),"+f"(d[62]),"+f"(d[63])
                 : "l"(desc_a), "l"(desc_b), "r"(scale_d));
}

#define K1_GW 8
#define K1_THREADS ((K1_GW + 8) * 32)
#define P1_EPT 10
#define P1_CHUNK (256 * P1_EPT)
#define K1_WBYTES (131072 + 2 * 16384)
#define K1_SMEM (K1_WBYTES + 3 * MAXBINS * 4 + P1_CHUNK * 8)

__device__ __forceinline__ void p1_bar() { asm volatile("bar.sync 1, 256;" ::: "memory"); }

__global__ void __launch_bounds__(K1_THREADS, 1) k1_kernel(
    const __nv_bfloat16* __restrict__ x, const __nv_bfloat16* __restrict__ e_attr,
    const int* __restrict__ src, const int* __restrict__ dst,
    const __nv_bfloat16* __restrict__ w_b, const __nv_bfloat16* __restrict__ w_v,
    const __nv_bfloat16* __restrict__ w_a, const __nv_bfloat16* __restrict__ w_u,
    int N, int E, int chunk, int NB, int nbins, uint32_t magic)
{
    extern __shared__ __align__(1024) uint8_t smem[];
    asm volatile("griddepcontrol.launch_dependents;");

    const int warp = threadIdx.x >> 5, lane = threadIdx.x & 31;

    if (warp >= K1_GW) {
        const int tid = threadIdx.x - K1_GW * 32;
        if (blockIdx.x == 0 && tid < 32)
            g_T[(size_t)N * 32 + tid] = make_uint4(0xff80ff80u, 0xff80ff80u, 0u, 0u);
        int* hist = reinterpret_cast<int*>(smem + K1_WBYTES);
        int* loff = hist + MAXBINS;
        int* gbase = loff + MAXBINS;
        uint2* sorted = reinterpret_cast<uint2*>(smem + K1_WBYTES + 3 * MAXBINS * 4);
        for (int beg = blockIdx.x * chunk; beg < E; beg += gridDim.x * chunk) {
            const int end = min(E, beg + chunk);
            int d[P1_EPT]; uint32_t rec[P1_EPT]; int rk[P1_EPT]; int bn[P1_EPT];
            #pragma unroll
            for (int i = 0; i < P1_EPT; i++) {
                int e = beg + i * 256 + tid;
                d[i] = -1;
                if (e < end) {
                    d[i] = __ldg(dst + e);
                    uint32_t s = (uint32_t)__ldg(src + e);
                    uint32_t ev = (uint32_t)__ldg(reinterpret_cast<const unsigned short*>(e_attr) + e);
                    rec[i] = (ev << 16) | s;
                }
            }
            hist[tid] = 0;
            p1_bar();
            #pragma unroll
            for (int i = 0; i < P1_EPT; i++) {
                if (d[i] >= 0) {
                    bn[i] = (int)(((uint64_t)(uint32_t)d[i] * magic) >> 24);
                    rk[i] = atomicAdd(&hist[bn[i]], 1);
                }
            }
            p1_bar();
            {
                int h = hist[tid];
                if (tid < nbins && h > 0) gbase[tid] = atomicAdd(&g_bin_cnt[tid], h);
                if (tid < 32) {
                    int v[8]; int sum = 0;
                    #pragma unroll
                    for (int i = 0; i < 8; i++) { v[i] = hist[lane * 8 + i]; sum += v[i]; }
                    int inc = sum;
                    #pragma unroll
                    for (int o = 1; o < 32; o <<= 1) { int t = __shfl_up_sync(0xffffffffu, inc, o); if (lane >= o) inc += t; }
                    int run = inc - sum;
                    #pragma unroll
                    for (int i = 0; i < 8; i++) { loff[lane * 8 + i] = run; run += v[i]; }
                }
            }
            p1_bar();
            #pragma unroll
            for (int i = 0; i < P1_EPT; i++) {
                if (d[i] >= 0) sorted[loff[bn[i]] + rk[i]] = make_uint2(rec[i], (uint32_t)d[i]);
            }
            p1_bar();
            const int cnt = end - beg;
            for (int i = tid; i < cnt; i += 256) {
                uint2 r = sorted[i];
                int b = (int)(((uint64_t)r.y * magic) >> 24);
                int pos = gbase[b] + (i - loff[b]);
                if (pos < BINCAP) {
                    g_bins[b * BINCAP + pos] = make_uint2(r.x, r.y - (uint32_t)(b * NB));
                } else {
                    int p = atomicAdd(&g_ovf_cnt, 2);
                    g_ovf[p] = (int)r.y; g_ovf[p + 1] = (int)r.x;
                }
            }
            p1_bar();
        }
        return;
    }

    const int q = lane & 3;
    const int wg = warp >> 2;
    const int n_tasks = ((N + 63) >> 6) * 4;
    const uint32_t sbase = (uint32_t)__cvta_generic_to_shared(smem);
    const uint32_t xbase = sbase + 131072;
    bool w_staged = false;
    int t_beg = (int)(((long long)n_tasks * blockIdx.x) / gridDim.x);
    const int t_end = (int)(((long long)n_tasks * (blockIdx.x + 1)) / gridDim.x);
    while (t_beg < t_end) {
        const int tile0 = t_beg >> 2;
        const int t_stop = min(t_end, (tile0 + 2) << 2);
        stage_x_tile(xbase, x, tile0 * 64, N, threadIdx.x, K1_GW * 32);
        if (((t_stop - 1) >> 2) > tile0) stage_x_tile(xbase + 16384, x, tile0 * 64 + 64, N, threadIdx.x, K1_GW * 32);
        if (!w_staged) {
            stage_weight(sbase, w_b, 0, threadIdx.x, K1_GW * 32);
            stage_weight(sbase, w_v, 1, threadIdx.x, K1_GW * 32);
            stage_weight(sbase + 65536, w_a, 0, threadIdx.x, K1_GW * 32);
            stage_weight(sbase + 65536, w_u, 1, threadIdx.x, K1_GW * 32);
            w_staged = true;
        }
        asm volatile("cp.async.wait_all;" ::: "memory");
        asm volatile("fence.proxy.async.shared::cta;" ::: "memory");
        asm volatile("bar.sync 2, %0;" :: "n"(K1_GW * 32) : "memory");
        for (int task = t_beg + wg; task < t_stop; task += 2) {
            const int tile = task >> 2, type = (task >> 1) & 1, hf = task & 1;
            const uint32_t baddr = sbase + type * 65536 + hf * 1024;
            const uint64_t descb = (uint64_t)((baddr & 0x3FFFF) >> 4) | ((uint64_t)(2048 >> 4) << 16) |
                                   ((uint64_t)(4096 >> 4) << 32) | ((uint64_t)1 << 62);
            const uint32_t aaddr = xbase + (tile - tile0) * 16384;
            const uint64_t desca = (uint64_t)((aaddr & 0x3FFFF) >> 4) | ((uint64_t)1 << 16) |
                                   ((uint64_t)(1024 >> 4) << 32) | ((uint64_t)1 << 62);
            float d[64];
            asm volatile("wgmma.fence.sync.aligned;" ::: "memory");
            #pragma unroll
            for (int ks = 0; ks < 8; ks++) {
                wgmma_m64n128k16(d, desca + (uint64_t)(((ks >> 2) * 8192 + (ks & 3) * 32) >> 4),
                                 descb + (uint64_t)(ks * (8192 >> 4)), ks > 0 ? 1 : 0);
            }
            asm volatile("wgmma.commit_group.sync.aligned;" ::: "memory");
            asm volatile("wgmma.wait_group.sync.aligned 0;" ::: "memory");
            uint4* outp = (type ? g_AU : g_T);
            const int r0 = tile * 64 + (warp & 3) * 16 + (lane >> 2);
            #pragma unroll
            for (int mm = 0; mm < 4; mm++) {
                const int j0 = 2 * mm, j1 = 2 * mm + 1, j2 = 8 + 2 * mm, j3 = 9 + 2 * mm;
                uint4 o0 = make_uint4(pack_bf16(d[4 * j0], d[4 * j0 + 1]), pack_bf16(d[4 * j1], d[4 * j1 + 1]),
                                      pack_bf16(d[4 * j2], d[4 * j2 + 1]), pack_bf16(d[4 * j3], d[4 * j3 + 1]));
                uint4 o1 = make_uint4(pack_bf16(d[4 * j0 + 2], d[4 * j0 + 3]), pack_bf16(d[4 * j1 + 2], d[4 * j1 + 3]),
                                      pack_bf16(d[4 * j2 + 2], d[4 * j2 + 3]), pack_bf16(d[4 * j3 + 2], d[4 * j3 + 3]));
                const int m = 4 * hf + mm;
                if (r0 < N) outp[(size_t)r0 * 32 + 4 * m + q] = o0;
                if (r0 + 8 < N) outp[(size_t)(r0 + 8) * 32 + 4 * m + q] = o1;
            }
        }
        t_beg = t_stop;
        if (t_beg < t_end) asm volatile("bar.sync 2, %0;" :: "n"(K1_GW * 32) : "memory");
    }
}

__device__ __forceinline__ void edge_accum(const uint4 v, const float e, const float a[4], const float cc[4],
                                           float num[4], float den[4]) {
    float y0 = fmaf(bf_lo(v.x), -LOG2E, fmaf(e, cc[0], a[0]));
    float y1 = fmaf(bf_hi(v.x), -LOG2E, fmaf(e, cc[1], a[1]));
    float y2 = fmaf(bf_lo(v.y), -LOG2E, fmaf(e, cc[2], a[2]));
    float y3 = fmaf(bf_hi(v.y), -LOG2E, fmaf(e, cc[3], a[3]));
    float s0 = rcp_approx(1.f + ex2_approx(y0));
    float s1 = rcp_approx(1.f + ex2_approx(y1));
    float s2 = rcp_approx(1.f + ex2_approx(y2));
    float s3 = rcp_approx(1.f + ex2_approx(y3));
    den[0] += s0; den[1] += s1; den[2] += s2; den[3] += s3;
    num[0] = fmaf(s0, bf_lo(v.z), num[0]);
    num[1] = fmaf(s1, bf_hi(v.z), num[1]);
    num[2] = fmaf(s2, bf_lo(v.w), num[2]);
    num[3] = fmaf(s3, bf_hi(v.w), num[3]);
}

#define K2_THREADS 512
#define K2_D 3
#define K2_DYN_SMEM (100 * 1024)
#define K2_RPT ((BINCAP + K2_THREADS - 1) / K2_THREADS)
#define K2_NW (K2_THREADS / 32)
#define SORT_WORDS (BINCAP + 4 * MAXNB)

struct Grp { uint4 v[4]; };

__device__ __forceinline__ const uint4* row_ptr(const char* Tl, uint32_t rec) {
    return reinterpret_cast<const uint4*>(Tl + (size_t)((rec & 0xffffu) * 512u));
}
__device__ __forceinline__ void grp_load(Grp& g, const uint32_t* sp, const char* Tl) {
    const uint4 t = *reinterpret_cast<const uint4*>(sp);
    g.v[0] = __ldg(row_ptr(Tl, t.x));
    g.v[1] = __ldg(row_ptr(Tl, t.y));
    g.v[2] = __ldg(row_ptr(Tl, t.z));
    g.v[3] = __ldg(row_ptr(Tl, t.w));
}
__device__ __forceinline__ void grp_consume(const Grp& g, const uint32_t* sp, const float a[4], const float cc[4],
                                            float num[4], float den[4]) {
    const uint4 t = *reinterpret_cast<const uint4*>(sp);
    edge_accum(g.v[0], bf_hi(t.x), a, cc, num, den);
    edge_accum(g.v[1], bf_hi(t.y), a, cc, num, den);
    edge_accum(g.v[2], bf_hi(t.z), a, cc, num, den);
    edge_accum(g.v[3], bf_hi(t.w), a, cc, num, den);
}

__global__ void __launch_bounds__(K2_THREADS, 1) k2_kernel(
    const __nv_bfloat16* __restrict__ x,
    const __nv_bfloat16* __restrict__ w_c, __nv_bfloat16* __restrict__ out, int N, int NB)
{
    __shared__ __align__(16) uint32_t s_sorted[SORT_WORDS];
    __shared__ int s_hist[MAXNB];
    __shared__ int s_off[MAXNB + 1];

    const int tid = threadIdx.x;
    const int lane = tid & 31, warp = tid >> 5;
    const int bin = blockIdx.x;
    const int node0 = bin * NB;
    const int nn = min(NB, N - node0);

    if (tid < MAXNB) s_hist[tid] = 0;
    for (int i = tid; i < SORT_WORDS; i += K2_THREADS) s_sorted[i] = (uint32_t)N;
    __syncthreads();
    const int fw = (lane >> 2) * 8 + (lane & 3);
    const uint2 wc = make_uint2(__ldg(reinterpret_cast<const uint32_t*>(w_c) + fw), __ldg(reinterpret_cast<const uint32_t*>(w_c) + fw + 4));
    const uint32_t* x32 = reinterpret_cast<const uint32_t*>(x) + fw;
    uint32_t* out32 = reinterpret_cast<uint32_t*>(out) + fw;
    const float cc[4] = { -LOG2E * bf_lo(wc.x), -LOG2E * bf_hi(wc.x), -LOG2E * bf_lo(wc.y), -LOG2E * bf_hi(wc.y) };

    asm volatile("griddepcontrol.wait;" ::: "memory");

    const int cnt = min(g_bin_cnt[bin], BINCAP);
    const int ovf_n = g_ovf_cnt;
    {
        uint2 r[K2_RPT]; int rk[K2_RPT];
        #pragma unroll
        for (int i = 0; i < K2_RPT; i++) {
            int idx = i * K2_THREADS + tid;
            if (idx < cnt) r[i] = g_bins[bin * BINCAP + idx];
        }
        #pragma unroll
        for (int i = 0; i < K2_RPT; i++) {
            int idx = i * K2_THREADS + tid;
            if (idx < cnt) rk[i] = atomicAdd(&s_hist[r[i].y], 1);
        }
        __syncthreads();
        if (warp == 0) {
            int v[4]; int sum = 0;
            #pragma unroll
            for (int i = 0; i < 4; i++) { v[i] = (s_hist[lane * 4 + i] + 3) & ~3; sum += v[i]; }
            int inc = sum;
            #pragma unroll
            for (int o = 1; o < 32; o <<= 1) { int t = __shfl_up_sync(0xffffffffu, inc, o); if (lane >= o) inc += t; }
            int run = inc - sum;
            #pragma unroll
            for (int i = 0; i < 4; i++) { s_off[lane * 4 + i] = run; run += v[i]; }
            if (lane == 31) s_off[MAXNB] = run;
        }
        if (tid == 32) g_bin_cnt[bin] = 0;
        __syncthreads();
        #pragma unroll
        for (int i = 0; i < K2_RPT; i++) {
            int idx = i * K2_THREADS + tid;
            if (idx < cnt) s_sorted[s_off[r[i].y] + rk[i]] = r[i].x;
        }
        __syncthreads();
    }

    const char* Tl = reinterpret_cast<const char*>(g_T) + lane * 16;
    int ln, ln_end;
    {
        const int total = s_off[MAXNB];
        const int lo = (int)(((long long)total * warp) / K2_NW);
        const int hi = (int)(((long long)total * (warp + 1)) / K2_NW);
        int c_lo = 0, c_hi = 0;
        #pragma unroll
        for (int i = 0; i < 4; i++) {
            int node = i * 32 + lane;
            int o = (node < nn) ? s_off[node] : 0x7fffffff;
            c_lo += __popc(__ballot_sync(0xffffffffu, o < lo));
            c_hi += __popc(__ballot_sync(0xffffffffu, o < hi));
        }
        ln = c_lo; ln_end = (warp == K2_NW - 1) ? nn : c_hi;
        if (warp == 0) ln = 0;
    }
    if (ln < ln_end) {
        int g = s_off[ln] >> 2;
        const int g_end = s_off[ln_end] >> 2;
        Grp b0, b1, b2;
        if (g < g_end) grp_load(b0, s_sorted + 4 * g, Tl);
        if (g + 1 < g_end) grp_load(b1, s_sorted + 4 * (g + 1), Tl);
        if (g + 2 < g_end) grp_load(b2, s_sorted + 4 * (g + 2), Tl);
        uint2 xv = make_uint2(__ldg(x32 + (size_t)(node0 + ln) * 64), __ldg(x32 + (size_t)(node0 + ln) * 64 + 4));
        uint4 au = g_AU[(size_t)(node0 + ln) * 32 + lane];
        uint4 au_n; uint2 xv_n;
        if (ln + 1 < ln_end) {
            au_n = g_AU[(size_t)(node0 + ln + 1) * 32 + lane];
            xv_n = make_uint2(__ldg(x32 + (size_t)(node0 + ln + 1) * 64), __ldg(x32 + (size_t)(node0 + ln + 1) * 64 + 4));
        }
        float a[4] = { -LOG2E * bf_lo(au.x), -LOG2E * bf_hi(au.x), -LOG2E * bf_lo(au.y), -LOG2E * bf_hi(au.y) };
        float num[4] = {0.f, 0.f, 0.f, 0.f}, den[4] = {0.f, 0.f, 0.f, 0.f};
        int node_end = s_off[ln + 1] >> 2;

        #define FINISH_NODES() \
        while (g == node_end) { \
            const int n = node0 + ln; \
            if (ovf_n != 0) { \
                for (int base = 0; base < ovf_n; base += 64) { \
                    int i2 = base + 2 * lane; \
                    int od = (i2 < ovf_n) ? g_ovf[i2] : -1; \
                    uint32_t orec = (i2 < ovf_n) ? (uint32_t)g_ovf[i2 + 1] : 0u; \
                    unsigned msk = __ballot_sync(0xffffffffu, od == n); \
                    while (msk) { \
                        int l = __ffs(msk) - 1; msk &= msk - 1; \
                        uint32_t r = __shfl_sync(0xffffffffu, orec, l); \
                        uint4 v = __ldg(row_ptr(Tl, r)); \
                        edge_accum(v, bf_hi(r), a, cc, num, den); \
                    } \
                } \
            } \
            { \
                const float u4[4] = { bf_lo(au.z), bf_hi(au.z), bf_lo(au.w), bf_hi(au.w) }; \
                const float x4[4] = { bf_lo(xv.x), bf_hi(xv.x), bf_lo(xv.y), bf_hi(xv.y) }; \
                float o[4]; \
                _Pragma("unroll") for (int i = 0; i < 4; i++) { \
                    float agg = round_bf16(__fdividef(num[i], den[i] + 1e-6f)); \
                    float z = round_bf16(u4[i] + agg); \
                    float rz = (z > 0.f) ? z : 0.f * z; \
                    o[i] = x4[i] + rz; \
                    num[i] = 0.f; den[i] = 0.f; \
                } \
                out32[(size_t)n * 64] = pack_bf16(o[0], o[1]); out32[(size_t)n * 64 + 4] = pack_bf16(o[2], o[3]); \
            } \
            ln++; \
            if (ln >= ln_end) goto done; \
            au = au_n; xv = xv_n; \
            if (ln + 1 < ln_end) { \
                au_n = g_AU[(size_t)(node0 + ln + 1) * 32 + lane]; \
                xv_n = make_uint2(__ldg(x32 + (size_t)(node0 + ln + 1) * 64), __ldg(x32 + (size_t)(node0 + ln + 1) * 64 + 4)); \
            } \
            a[0] = -LOG2E * bf_lo(au.x); a[1] = -LOG2E * bf_hi(au.x); a[2] = -LOG2E * bf_lo(au.y); a[3] = -LOG2E * bf_hi(au.y); \
            node_end = s_off[ln + 1] >> 2; \
        }
        #define STEP(B) \
            FINISH_NODES(); \
            grp_consume(B, s_sorted + 4 * g, a, cc, num, den); \
            if (g + K2_D < g_end) grp_load(B, s_sorted + 4 * (g + K2_D), Tl); \
            g++;
        while (true) {
            STEP(b0);
            STEP(b1);
            STEP(b2);
        }
        done:;
    }
    if (ovf_n != 0) {
        __syncthreads();
        if (tid == 0) {
            __threadfence();
            int t = atomicAdd(&g_done, 1);
            if (t == (int)gridDim.x - 1) { g_done = 0; __threadfence(); g_ovf_cnt = 0; }
        }
    }
}

extern "C" void kernel_launch(void* const* d_in, const int* in_sizes, int n_in,
                              void* d_out, int out_size) {
    const __nv_bfloat16* x      = (const __nv_bfloat16*)d_in[0];
    const __nv_bfloat16* e_attr = (const __nv_bfloat16*)d_in[1];
    const int* src = (const int*)d_in[2];
    const int* dst = (const int*)d_in[3];
    const __nv_bfloat16* w_a = (const __nv_bfloat16*)d_in[4];
    const __nv_bfloat16* w_b = (const __nv_bfloat16*)d_in[5];
    const __nv_bfloat16* w_c = (const __nv_bfloat16*)d_in[6];
    const __nv_bfloat16* w_u = (const __nv_bfloat16*)d_in[7];
    const __nv_bfloat16* w_v = (const __nv_bfloat16*)d_in[8];
    __nv_bfloat16* out = (__nv_bfloat16*)d_out;
    const int N = in_sizes[0] / D_FEAT;
    const int E = in_sizes[2];
    if (N > MAX_N || 2 * E > MAX_E || N <= 0) return;

    static int num_sms = 0;
    if (num_sms == 0) {
        int dev = 0;
        cudaGetDevice(&dev);
        cudaDeviceGetAttribute(&num_sms, cudaDevAttrMultiProcessorCount, dev);
        if (num_sms <= 0 || num_sms > MAXBINS) num_sms = 132;
        cudaFuncSetAttribute(k1_kernel, cudaFuncAttributeMaxDynamicSharedMemorySize, K1_SMEM);
        cudaFuncSetAttribute(k2_kernel, cudaFuncAttributeMaxDynamicSharedMemorySize, K2_DYN_SMEM);
    }
    cudaStream_t st = cudaStreamPerThread;
    int NB = (N + num_sms - 1) / num_sms;
    if (NB > MAXNB) NB = MAXNB;
    const int nbins = (N + NB - 1) / NB;
    const uint32_t magic = (uint32_t)(((1u << 24) + NB - 1) / NB);
    const int P = num_sms;
    int chunk = (E + P - 1) / P;
    if (chunk > P1_CHUNK) chunk = P1_CHUNK;
    if (chunk < 1) chunk = 1;
    k1_kernel<<<P, K1_THREADS, K1_SMEM, st>>>(x, e_attr, src, dst, w_b, w_v, w_a, w_u, N, E, chunk, NB, nbins, magic);

    cudaLaunchConfig_t cfg = {};
    cfg.gridDim = dim3(nbins);
    cfg.blockDim = dim3(K2_THREADS);
    cfg.dynamicSmemBytes = K2_DYN_SMEM;
    cfg.stream = st;
    cudaLaunchAttribute at[1];
    at[0].id = cudaLaunchAttributeProgrammaticStreamSerialization;
    at[0].val.programmaticStreamSerializationAllowed = 1;
    cfg.attrs = at; cfg.numAttrs = 1;
    cudaLaunchKernelEx(&cfg, k2_kernel, x, w_c, out, N, NB);
}
```

```cpp
#include <cuda_runtime.h>
#include <cuda_bf16.h>
#include <stdint.h>

#define D_FEAT 128
#define MAX_N 16384
#define MAX_E (1 << 20)
#define LOG2E 1.4426950408889634f

#define MAXBINS 256
#define MAXNB 128
#define BINCAP 3072
__device__ uint4 g_T[(MAX_N + 1) * 32];
__device__ uint4 g_AU[MAX_N * 32];
__device__ int g_bin_cnt[MAXBINS];
__device__ uint2 g_bins[MAXBINS * BINCAP];
__device__ int g_ovf[MAX_E];
__device__ int g_ovf_cnt;
__device__ int g_done;

__device__ __forceinline__ float ex2_approx(float x) {
    float y; asm("ex2.approx.ftz.f32 %0, %1;" : "=f"(y) : "f"(x)); return y;
}
__device__ __forceinline__ float rcp_approx(float x) {
    float y; asm("rcp.approx.ftz.f32 %0, %1;" : "=f"(y) : "f"(x)); return y;
}
__device__ __forceinline__ uint32_t pack_bf16(float lo, float hi) {
    __nv_bfloat162 t = __floats2bfloat162_rn(lo, hi);
    return *reinterpret_cast<uint32_t*>(&t);
}
__device__ __forceinline__ float bf_lo(uint32_t v) { return __uint_as_float(v << 16); }
__device__ __forceinline__ float bf_hi(uint32_t v) { return __uint_as_float(v & 0xffff0000u); }
__device__ __forceinline__ float round_bf16(float x) { return __bfloat162float(__float2bfloat16_rn(x)); }

__device__ __forceinline__ void mma_bf16(float c[4], uint32_t a0, uint32_t a1, uint32_t a2, uint32_t a3,
                                         uint32_t b0, uint32_t b1) {
    asm volatile("mma.sync.aligned.m16n8k16.row.col.f32.bf16.bf16.f32 "
                 "{%0,%1,%2,%3}, {%4,%5,%6,%7}, {%8,%9}, {%0,%1,%2,%3};"
                 : "+f"(c[0]), "+f"(c[1]), "+f"(c[2]), "+f"(c[3])
                 : "r"(a0), "r"(a1), "r"(a2), "r"(a3), "r"(b0), "r"(b1));
}
__device__ __forceinline__ void ldmatrix_x4_trans(uint32_t& r0, uint32_t& r1, uint32_t& r2, uint32_t& r3, uint32_t addr) {
    asm volatile("ldmatrix.sync.aligned.m8n8.x4.trans.shared.b16 {%0,%1,%2,%3}, [%4];"
                 : "=r"(r0), "=r"(r1), "=r"(r2), "=r"(r3) : "r"(addr));
}

__device__ __forceinline__ void cp_async16(uint32_t saddr, const void* g) {
    asm volatile("cp.async.cg.shared.global [%0], [%1], 16;" :: "r"(saddr), "l"(g) : "memory");
}
__device__ __forceinline__ void cp_async16_zfill(uint32_t saddr, const void* g, int src_size) {
    asm volatile("cp.async.cg.shared.global [%0], [%1], 16, %2;" :: "r"(saddr), "l"(g), "r"(src_size) : "memory");
}
__device__ __forceinline__ void stage_weight(uint32_t sdst, const __nv_bfloat16* w, int mtx, int tid, int nthreads) {
    const uint4* W = reinterpret_cast<const uint4*>(w);
    for (int u = tid; u < 2048; u += nthreads) {
        int k = u >> 4, c16 = u & 15;
        int kg = k >> 3, rr = k & 7;
        int h = mtx * 2 + (c16 >> 3);
        cp_async16(sdst + kg * 4096 + h * 1024 + rr * 128 + (((c16 & 7) ^ rr) << 4), W + u);
    }
}
__device__ __forceinline__ void stage_x_tile(uint32_t sdst, const __nv_bfloat16* x, int row0, int N, int tid, int nthreads) {
    const uint4* X = reinterpret_cast<const uint4*>(x);
    for (int u = tid; u < 1024; u += nthreads) {
        int r = u >> 4, c16 = u & 15;
        int gr = row0 + r;
        bool ok = gr < N;
        cp_async16_zfill(sdst + (c16 >> 3) * 8192 + r * 128 + (((c16 & 7) ^ (r & 7)) << 4),
                         X + (size_t)(ok ? gr : 0) * 16 + c16, ok ? 16 : 0);
    }
}

__device__ __forceinline__ void wgmma_m64n128k16(float d[64], uint64_t desc_a, uint64_t desc_b, int scale_d) {
    asm volatile("{\n.reg .pred p;\nsetp.ne.b32 p, %66, 0;\n"
                 "wgmma.mma_async.sync.aligned.m64n128k16.f32.bf16.bf16 {%0,%1,%2,%3,%4,%5,%6,%7,%8,%9,%10,%11,%12,%13,%14,%15,%16,%17,%18,%19,%20,%21,%22,%23,%24,%25,%26,%27,%28,%29,%30,%31,%32,%33,%34,%35,%36,%37,%38,%39,%40,%41,%42,%43,%44,%45,%46,%47,%48,%49,%50,%51,%52,%53,%54,%55,%56,%57,%58,%59,%60,%61,%62,%63}, %64, %65, p, 1, 1, 0, 1;\n}"
                 : "+f"(d[0]),"+f"(d[1]),"+f"(d[2]),"+f"(d[3]),"+f"(d[4]),"+f"(d[5]),"+f"(d[6]),"+f"(d[7]),"+f"(d[8]),"+f"(d[9]),"+f"(d[10]),"+f"(d[11]),"+f"(d[12]),"+f"(d[13]),"+f"(d[14]),"+f"(d[15]),"+f"(d[16]),"+f"(d[17]),"+f"(d[18]),"+f"(d[19]),"+f"(d[20]),"+f"(d[21]),"+f"(d[22]),"+f"(d[23]),"+f"(d[24]),"+f"(d[25]),"+f"(d[26]),"+f"(d[27]),"+f"(d[28]),"+f"(d[29]),"+f"(d[30]),"+f"(d[31]),"+f"(d[32]),"+f"(d[33]),"+f"(d[34]),"+f"(d[35]),"+f"(d[36]),"+f"(d[37]),"+f"(d[38]),"+f"(d[39]),"+f"(d[40]),"+f"(d[41]),"+f"(d[42]),"+f"(d[43]),"+f"(d[44]),"+f"(d[45]),"+f"(d[46]),"+f"(d[47]),"+f"(d[48]),"+f"(d[49]),"+f"(d[50]),"+f"(d[51]),"+f"(d[52]),"+f"(d[53]),"+f"(d[54]),"+f"(d[55]),"+f"(d[56]),"+f"(d[57]),"+f"(d[58]),"+f"(d[59]),"+f"(d[60]),"+f"(d[61]),"+f"(d[62]),"+f"(d[63])
                 : "l"(desc_a), "l"(desc_b), "r"(scale_d));
}

#define K1_GW 8
#define K1_THREADS ((K1_GW + 8) * 32)
#define P1_EPT 10
#define P1_CHUNK (256 * P1_EPT)
#define K1_WBYTES (131072 + 2 * 16384)
#define K1_SMEM (K1_WBYTES + 3 * MAXBINS * 4 + P1_CHUNK * 8)

__device__ __forceinline__ void p1_bar() { asm volatile("bar.sync 1, 256;" ::: "memory"); }

__global__ void __launch_bounds__(K1_THREADS, 1) k1_kernel(
    const __nv_bfloat16* __restrict__ x, const __nv_bfloat16* __restrict__ e_attr,
    const int* __restrict__ src, const int* __restrict__ dst,
    const __nv_bfloat16* __restrict__ w_b, const __nv_bfloat16* __restrict__ w_v,
    const __nv_bfloat16* __restrict__ w_a, const __nv_bfloat16* __restrict__ w_u,
    int N, int E, int chunk, int NB, int nbins, uint32_t magic)
{
    extern __shared__ __align__(1024) uint8_t smem[];
    asm volatile("griddepcontrol.launch_dependents;");

    const int warp = threadIdx.x >> 5, lane = threadIdx.x & 31;

    if (warp >= K1_GW) {
        const int tid = threadIdx.x - K1_GW * 32;
        if (blockIdx.x == 0 && tid < 32)
            g_T[(size_t)N * 32 + tid] = make_uint4(0xff80ff80u, 0xff80ff80u, 0u, 0u);
        int* hist = reinterpret_cast<int*>(smem + K1_WBYTES);
        int* loff = hist + MAXBINS;
        int* gbase = loff + MAXBINS;
        uint2* sorted = reinterpret_cast<uint2*>(smem + K1_WBYTES + 3 * MAXBINS * 4);
        for (int beg = blockIdx.x * chunk; beg < E; beg += gridDim.x * chunk) {
            const int end = min(E, beg + chunk);
            int d[P1_EPT]; uint32_t rec[P1_EPT]; int rk[P1_EPT]; int bn[P1_EPT];
            #pragma unroll
            for (int i = 0; i < P1_EPT; i++) {
                int e = beg + i * 256 + tid;
                d[i] = -1;
                if (e < end) {
                    d[i] = __ldg(dst + e);
                    uint32_t s = (uint32_t)__ldg(src + e);
                    uint32_t ev = (uint32_t)__ldg(reinterpret_cast<const unsigned short*>(e_attr) + e);
                    rec[i] = (ev << 16) | s;
                }
            }
            hist[tid] = 0;
            p1_bar();
            #pragma unroll
            for (int i = 0; i < P1_EPT; i++) {
                if (d[i] >= 0) {
                    bn[i] = (int)(((uint64_t)(uint32_t)d[i] * magic) >> 24);
                    rk[i] = atomicAdd(&hist[bn[i]], 1);
                }
            }
            p1_bar();
            {
                int h = hist[tid];
                if (tid < nbins && h > 0) gbase[tid] = atomicAdd(&g_bin_cnt[tid], h);
                if (tid < 32) {
                    int v[8]; int sum = 0;
                    #pragma unroll
                    for (int i = 0; i < 8; i++) { v[i] = hist[lane * 8 + i]; sum += v[i]; }
                    int inc = sum;
                    #pragma unroll
                    for (int o = 1; o < 32; o <<= 1) { int t = __shfl_up_sync(0xffffffffu, inc, o); if (lane >= o) inc += t; }
                    int run = inc - sum;
                    #pragma unroll
                    for (int i = 0; i < 8; i++) { loff[lane * 8 + i] = run; run += v[i]; }
                }
            }
            p1_bar();
            #pragma unroll
            for (int i = 0; i < P1_EPT; i++) {
                if (d[i] >= 0) sorted[loff[bn[i]] + rk[i]] = make_uint2(rec[i], (uint32_t)d[i]);
            }
            p1_bar();
            const int cnt = end - beg;
            for (int i = tid; i < cnt; i += 256) {
                uint2 r = sorted[i];
                int b = (int)(((uint64_t)r.y * magic) >> 24);
                int pos = gbase[b] + (i - loff[b]);
                if (pos < BINCAP) {
                    g_bins[b * BINCAP + pos] = make_uint2(r.x, r.y - (uint32_t)(b * NB));
                } else {
                    int p = atomicAdd(&g_ovf_cnt, 2);
                    g_ovf[p] = (int)r.y; g_ovf[p + 1] = (int)r.x;
                }
            }
            p1_bar();
        }
        return;
    }

    const int q = lane & 3;
    const int wg = warp >> 2;
    const int n_tasks = ((N + 63) >> 6) * 4;
    const uint32_t sbase = (uint32_t)__cvta_generic_to_shared(smem);
    const uint32_t xbase = sbase + 131072;
    bool w_staged = false;
    int t_beg = (int)(((long long)n_tasks * blockIdx.x) / gridDim.x);
    const int t_end = (int)(((long long)n_tasks * (blockIdx.x + 1)) / gridDim.x);
    while (t_beg < t_end) {
        const int tile0 = t_beg >> 2;
        const int t_stop = min(t_end, (tile0 + 2) << 2);
        stage_x_tile(xbase, x, tile0 * 64, N, threadIdx.x, K1_GW * 32);
        if (((t_stop - 1) >> 2) > tile0) stage_x_tile(xbase + 16384, x, tile0 * 64 + 64, N, threadIdx.x, K1_GW * 32);
        if (!w_staged) {
            stage_weight(sbase, w_b, 0, threadIdx.x, K1_GW * 32);
            stage_weight(sbase, w_v, 1, threadIdx.x, K1_GW * 32);
            stage_weight(sbase + 65536, w_a, 0, threadIdx.x, K1_GW * 32);
            stage_weight(sbase + 65536, w_u, 1, threadIdx.x, K1_GW * 32);
            w_staged = true;
        }
        asm volatile("cp.async.wait_all;" ::: "memory");
        asm volatile("fence.proxy.async.shared::cta;" ::: "memory");
        asm volatile("bar.sync 2, %0;" :: "n"(K1_GW * 32) : "memory");
        for (int task = t_beg + wg; task < t_stop; task += 2) {
            const int tile = task >> 2, type = (task >> 1) & 1, hf = task & 1;
            const uint32_t baddr = sbase + type * 65536 + hf * 1024;
            const uint64_t descb = (uint64_t)((baddr & 0x3FFFF) >> 4) | ((uint64_t)(2048 >> 4) << 16) |
                                   ((uint64_t)(4096 >> 4) << 32) | ((uint64_t)1 << 62);
            const uint32_t aaddr = xbase + (tile - tile0) * 16384;
            const uint64_t desca = (uint64_t)((aaddr & 0x3FFFF) >> 4) | ((uint64_t)1 << 16) |
                                   ((uint64_t)(1024 >> 4) << 32) | ((uint64_t)1 << 62);
            float d[64];
            asm volatile("wgmma.fence.sync.aligned;" ::: "memory");
            #pragma unroll
            for (int ks = 0; ks < 8; ks++) {
                wgmma_m64n128k16(d, desca + (uint64_t)(((ks >> 2) * 8192 + (ks & 3) * 32) >> 4),
                                 descb + (uint64_t)(ks * (8192 >> 4)), ks > 0 ? 1 : 0);
            }
            asm volatile("wgmma.commit_group.sync.aligned;" ::: "memory");
            asm volatile("wgmma.wait_group.sync.aligned 0;" ::: "memory");
            uint4* outp = (type ? g_AU : g_T);
            const int r0 = tile * 64 + (warp & 3) * 16 + (lane >> 2);
            #pragma unroll
            for (int mm = 0; mm < 4; mm++) {
                const int j0 = 2 * mm, j1 = 2 * mm + 1, j2 = 8 + 2 * mm, j3 = 9 + 2 * mm;
                uint4 o0 = make_uint4(pack_bf16(d[4 * j0], d[4 * j0 + 1]), pack_bf16(d[4 * j1], d[4 * j1 + 1]),
                                      pack_bf16(d[4 * j2], d[4 * j2 + 1]), pack_bf16(d[4 * j3], d[4 * j3 + 1]));
                uint4 o1 = make_uint4(pack_bf16(d[4 * j0 + 2], d[4 * j0 + 3]), pack_bf16(d[4 * j1 + 2], d[4 * j1 + 3]),
                                      pack_bf16(d[4 * j2 + 2], d[4 * j2 + 3]), pack_bf16(d[4 * j3 + 2], d[4 * j3 + 3]));
                const int m = 4 * hf + mm;
                if (r0 < N) outp[(size_t)r0 * 32 + 4 * m + q] = o0;
                if (r0 + 8 < N) outp[(size_t)(r0 + 8) * 32 + 4 * m + q] = o1;
            }
        }
        t_beg = t_stop;
        if (t_beg < t_end) asm volatile("bar.sync 2, %0;" :: "n"(K1_GW * 32) : "memory");
    }
}

__device__ __forceinline__ void edge_accum(const uint4 v, const float e, const float a[4], const float cc[4],
                                           float num[4], float den[4]) {
    float y0 = fmaf(bf_lo(v.x), -LOG2E, fmaf(e, cc[0], a[0]));
    float y1 = fmaf(bf_hi(v.x), -LOG2E, fmaf(e, cc[1], a[1]));
    float y2 = fmaf(bf_lo(v.y), -LOG2E, fmaf(e, cc[2], a[2]));
    float y3 = fmaf(bf_hi(v.y), -LOG2E, fmaf(e, cc[3], a[3]));
    float s0 = rcp_approx(1.f + ex2_approx(y0));
    float s1 = rcp_approx(1.f + ex2_approx(y1));
    float s2 = rcp_approx(1.f + ex2_approx(y2));
    float s3 = rcp_approx(1.f + ex2_approx(y3));
    den[0] += s0; den[1] += s1; den[2] += s2; den[3] += s3;
    num[0] = fmaf(s0, bf_lo(v.z), num[0]);
    num[1] = fmaf(s1, bf_hi(v.z), num[1]);
    num[2] = fmaf(s2, bf_lo(v.w), num[2]);
    num[3] = fmaf(s3, bf_hi(v.w), num[3]);
}

#define K2_THREADS 1024
#define K2_D 3
#define K2_GS 2
#define K2_RPT ((BINCAP + K2_THREADS - 1) / K2_THREADS)
#define K2_NW (K2_THREADS / 32)
#define SORT_WORDS (BINCAP + 4 * MAXNB)
#define K2_OFF_AU 0
#define K2_OFF_X (K2_OFF_AU + MAXNB * 512)
#define K2_OFF_PART (K2_OFF_X + MAXNB * 256)
#define K2_OFF_SORT (K2_OFF_PART + K2_NW * 1024)
#define K2_OFF_HIST (K2_OFF_SORT + SORT_WORDS * 4)
#define K2_OFF_OFF (K2_OFF_HIST + MAXNB * 4)
#define K2_DYN_SMEM (K2_OFF_OFF + (MAXNB + 4) * 4)

struct Grp { uint4 v[K2_GS]; };

__device__ __forceinline__ const uint4* row_ptr(const char* Tl, uint32_t rec) {
    return reinterpret_cast<const uint4*>(Tl + (size_t)((rec & 0xffffu) * 512u));
}
__device__ __forceinline__ void grp_load(Grp& g, const uint32_t* sp, const char* Tl) {
    const uint2 t = *reinterpret_cast<const uint2*>(sp);
    g.v[0] = __ldg(row_ptr(Tl, t.x));
    g.v[1] = __ldg(row_ptr(Tl, t.y));
}
__device__ __forceinline__ void grp_consume(const Grp& g, const uint32_t* sp, const float a[4], const float cc[4],
                                            float num[4], float den[4]) {
    const uint2 t = *reinterpret_cast<const uint2*>(sp);
    edge_accum(g.v[0], bf_hi(t.x), a, cc, num, den);
    edge_accum(g.v[1], bf_hi(t.y), a, cc, num, den);
}

__device__ __noinline__ void ovf_accum(int n, int ovf_n, const char* Tl, const float* a, const float* cc,
                                       float* num, float* den) {
    const int lane = threadIdx.x & 31;
    for (int base = 0; base < ovf_n; base += 64) {
        int i2 = base + 2 * lane;
        int od = (i2 < ovf_n) ? g_ovf[i2] : -1;
        uint32_t orec = (i2 < ovf_n) ? (uint32_t)g_ovf[i2 + 1] : 0u;
        unsigned msk = __ballot_sync(0xffffffffu, od == n);
        while (msk) {
            int l = __ffs(msk) - 1; msk &= msk - 1;
            uint32_t r = __shfl_sync(0xffffffffu, orec, l);
            uint4 v = __ldg(row_ptr(Tl, r));
            edge_accum(v, bf_hi(r), a, cc, num, den);
        }
    }
}

__global__ void __launch_bounds__(K2_THREADS, 1) k2_kernel(
    const __nv_bfloat16* __restrict__ x,
    const __nv_bfloat16* __restrict__ w_c, __nv_bfloat16* __restrict__ out, int N, int NB)
{
    extern __shared__ __align__(1024) uint8_t smem[];
    uint4* s_au = reinterpret_cast<uint4*>(smem + K2_OFF_AU);
    uint32_t* s_x = reinterpret_cast<uint32_t*>(smem + K2_OFF_X);
    float4* s_part = reinterpret_cast<float4*>(smem + K2_OFF_PART);
    uint32_t* s_sorted = reinterpret_cast<uint32_t*>(smem + K2_OFF_SORT);
    int* s_hist = reinterpret_cast<int*>(smem + K2_OFF_HIST);
    int* s_off = reinterpret_cast<int*>(smem + K2_OFF_OFF);

    const int tid = threadIdx.x;
    const int lane = tid & 31, warp = tid >> 5;
    const int bin = blockIdx.x;
    const int node0 = bin * NB;
    const int nn = min(NB, N - node0);
    const uint32_t sb = (uint32_t)__cvta_generic_to_shared(smem);

    for (int i = tid; i < nn * 16; i += K2_THREADS)
        cp_async16(sb + K2_OFF_X + i * 16, reinterpret_cast<const uint4*>(x) + (size_t)node0 * 16 + i);
    if (tid < MAXNB) s_hist[tid] = 0;
    for (int i = tid; i < SORT_WORDS; i += K2_THREADS) s_sorted[i] = (uint32_t)N;
    s_part[warp * 64 + lane] = make_float4(0.f, 0.f, 0.f, 0.f);
    s_part[warp * 64 + 32 + lane] = make_float4(0.f, 0.f, 0.f, 0.f);
    __syncthreads();
    const int fw = (lane >> 2) * 8 + (lane & 3);
    const uint2 wc = make_uint2(__ldg(reinterpret_cast<const uint32_t*>(w_c) + fw), __ldg(reinterpret_cast<const uint32_t*>(w_c) + fw + 4));
    float cc[4] = { -LOG2E * bf_lo(wc.x), -LOG2E * bf_hi(wc.x), -LOG2E * bf_lo(wc.y), -LOG2E * bf_hi(wc.y) };

    asm volatile("griddepcontrol.wait;" ::: "memory");

    for (int i = tid; i < nn * 32; i += K2_THREADS)
        cp_async16(sb + K2_OFF_AU + i * 16, g_AU + (size_t)node0 * 32 + i);

    const int cnt = min(g_bin_cnt[bin], BINCAP);
    const int ovf_n = g_ovf_cnt;
    {
        uint2 r[K2_RPT]; int rk[K2_RPT];
        #pragma unroll
        for (int i = 0; i < K2_RPT; i++) {
            int idx = i * K2_THREADS + tid;
            if (idx < cnt) r[i] = g_bins[bin * BINCAP + idx];
        }
        #pragma unroll
        for (int i = 0; i < K2_RPT; i++) {
            int idx = i * K2_THREADS + tid;
            if (idx < cnt) rk[i] = atomicAdd(&s_hist[r[i].y], 1);
        }
        __syncthreads();
        if (warp == 0) {
            int v[4]; int sum = 0;
            #pragma unroll
            for (int i = 0; i < 4; i++) { v[i] = (s_hist[lane * 4 + i] + K2_GS - 1) & ~(K2_GS - 1); sum += v[i]; }
            int inc = sum;
            #pragma unroll
            for (int o = 1; o < 32; o <<= 1) { int t = __shfl_up_sync(0xffffffffu, inc, o); if (lane >= o) inc += t; }
            int run = inc - sum;
            #pragma unroll
            for (int i = 0; i < 4; i++) { s_off[lane * 4 + i] = run; run += v[i]; }
            if (lane == 31) s_off[MAXNB] = run;
        }
        if (tid == 32) g_bin_cnt[bin] = 0;
        __syncthreads();
        #pragma unroll
        for (int i = 0; i < K2_RPT; i++) {
            int idx = i * K2_THREADS + tid;
            if (idx < cnt) s_sorted[s_off[r[i].y] + rk[i]] = r[i].x;
        }
        asm volatile("cp.async.wait_all;" ::: "memory");
        __syncthreads();
    }

    const char* Tl = reinterpret_cast<const char*>(g_T) + lane * 16;
    const int G = s_off[MAXNB] / K2_GS;
    int g = (G * warp) / K2_NW;
    const int g1 = (G * (warp + 1)) / K2_NW;
    int ln;
    {
        int c_lo = 0;
        #pragma unroll
        for (int i = 0; i < 4; i++) {
            int node = i * 32 + lane;
            int o = (node < nn) ? s_off[node] : 0x7fffffff;
            c_lo += __popc(__ballot_sync(0xffffffffu, o < g * K2_GS));
        }
        ln = c_lo;
    }
    bool head = ln > 0;
    if (head) ln--;
    float a[4], num[4] = {0.f, 0.f, 0.f, 0.f}, den[4] = {0.f, 0.f, 0.f, 0.f};
    int node_end;

    auto load_node = [&]() {
        const uint2 av = *reinterpret_cast<const uint2*>(s_au + ln * 32 + lane);
        a[0] = -LOG2E * bf_lo(av.x); a[1] = -LOG2E * bf_hi(av.x); a[2] = -LOG2E * bf_lo(av.y); a[3] = -LOG2E * bf_hi(av.y);
        node_end = s_off[ln + 1] / K2_GS;
    };
    auto finish_node = [&]() {
        const int n = node0 + ln;
        if (ovf_n != 0) {
            float t[16] = { a[0], a[1], a[2], a[3], cc[0], cc[1], cc[2], cc[3],
                            num[0], num[1], num[2], num[3], den[0], den[1], den[2], den[3] };
            ovf_accum(n, ovf_n, Tl, t, t + 4, t + 8, t + 12);
            #pragma unroll
            for (int i = 0; i < 4; i++) { num[i] = t[8 + i]; den[i] = t[12 + i]; }
        }
        const uint2 uv = *(reinterpret_cast<const uint2*>(s_au + ln * 32 + lane) + 1);
        const uint32_t x0 = s_x[ln * 64 + fw], x1 = s_x[ln * 64 + fw + 4];
        const float u4[4] = { bf_lo(uv.x), bf_hi(uv.x), bf_lo(uv.y), bf_hi(uv.y) };
        const float x4[4] = { bf_lo(x0), bf_hi(x0), bf_lo(x1), bf_hi(x1) };
        float o[4];
        #pragma unroll
        for (int i = 0; i < 4; i++) {
            float agg = round_bf16(__fdividef(num[i], den[i] + 1e-6f));
            float z = round_bf16(u4[i] + agg);
            float rz = (z > 0.f) ? z : 0.f * z;
            o[i] = x4[i] + rz;
        }
        uint32_t* o32 = reinterpret_cast<uint32_t*>(out) + (size_t)n * 64 + fw;
        o32[0] = pack_bf16(o[0], o[1]); o32[4] = pack_bf16(o[2], o[3]);
    };
    auto close_node = [&]() {
        if (head) {
            s_part[warp * 64 + lane] = make_float4(num[0], num[1], num[2], num[3]);
            s_part[warp * 64 + 32 + lane] = make_float4(den[0], den[1], den[2], den[3]);
            head = false;
        } else {
            finish_node();
        }
        #pragma unroll
        for (int i = 0; i < 4; i++) { num[i] = 0.f; den[i] = 0.f; }
    };

    bool tail = false;
    if (g < g1 || warp == K2_NW - 1) {
        load_node();
        Grp b[K2_D];
        #pragma unroll
        for (int d = 0; d < K2_D; d++)
            if (g + d < g1) grp_load(b[d], s_sorted + K2_GS * (g + d), Tl);
        while (g < g1) {
            #pragma unroll
            for (int d = 0; d < K2_D; d++) {
                if (g < g1) {
                    while (g == node_end) { close_node(); ln++; load_node(); }
                    grp_consume(b[d], s_sorted + K2_GS * g, a, cc, num, den);
                    if (g + K2_D < g1) grp_load(b[d], s_sorted + K2_GS * (g + K2_D), Tl);
                    g++;
                }
            }
        }
        if (warp == K2_NW - 1) {
            while (true) { close_node(); ln++; if (ln >= nn) break; load_node(); }
        } else if (node_end == g1 || head) {
            close_node();
        } else {
            tail = true;
        }
    }
    __syncthreads();
    if (tail) {
        for (int w2 = warp + 1; w2 < K2_NW && (G * w2) / K2_NW < node_end; w2++) {
            const float4 pn = s_part[w2 * 64 + lane], pd = s_part[w2 * 64 + 32 + lane];
            num[0] += pn.x; num[1] += pn.y; num[2] += pn.z; num[3] += pn.w;
            den[0] += pd.x; den[1] += pd.y; den[2] += pd.z; den[3] += pd.w;
        }
        finish_node();
    }
    if (ovf_n != 0) {
        __syncthreads();
        if (tid == 0) {
            __threadfence();
            int t = atomicAdd(&g_done, 1);
            if (t == (int)gridDim.x - 1) { g_done = 0; __threadfence(); g_ovf_cnt = 0; }
        }
    }
}

extern "C" void kernel_launch(void* const* d_in, const int* in_sizes, int n_in,
                              void* d_out, int out_size) {
    const __nv_bfloat16* x      = (const __nv_bfloat16*)d_in[0];
    const __nv_bfloat16* e_attr = (const __nv_bfloat16*)d_in[1];
    const int* src = (const int*)d_in[2];
    const int* dst = (const int*)d_in[3];
    const __nv_bfloat16* w_a = (const __nv_bfloat16*)d_in[4];
    const __nv_bfloat16* w_b = (const __nv_bfloat16*)d_in[5];
    const __nv_bfloat16* w_c = (const __nv_bfloat16*)d_in[6];
    const __nv_bfloat16* w_u = (const __nv_bfloat16*)d_in[7];
    const __nv_bfloat16* w_v = (const __nv_bfloat16*)d_in[8];
    __nv_bfloat16* out = (__nv_bfloat16*)d_out;
    const int N = in_sizes[0] / D_FEAT;
    const int E = in_sizes[2];
    if (N > MAX_N || 2 * E > MAX_E || N <= 0) return;

    static int num_sms = 0;
    if (num_sms == 0) {
        int dev = 0;
        cudaGetDevice(&dev);
        cudaDeviceGetAttribute(&num_sms, cudaDevAttrMultiProcessorCount, dev);
        if (num_sms <= 0 || num_sms > MAXBINS) num_sms = 132;
        cudaFuncSetAttribute(k1_kernel, cudaFuncAttributeMaxDynamicSharedMemorySize, K1_SMEM);
        cudaFuncSetAttribute(k2_kernel, cudaFuncAttributeMaxDynamicSharedMemorySize, K2_DYN_SMEM);
    }
    cudaStream_t st = cudaStreamPerThread;
    int NB = (N + num_sms - 1) / num_sms;
    if (NB > MAXNB) NB = MAXNB;
    const int nbins = (N + NB - 1) / NB;
    const uint32_t magic = (uint32_t)(((1u << 24) + NB - 1) / NB);
    const int P = num_sms;
    int chunk = (E + P - 1) / P;
    if (chunk > P1_CHUNK) chunk = P1_CHUNK;
    if (chunk < 1) chunk = 1;
    k1_kernel<<<P, K1_THREADS, K1_SMEM, st>>>(x, e_attr, src, dst, w_b, w_v, w_a, w_u, N, E, chunk, NB, nbins, magic);

    cudaLaunchConfig_t cfg = {};
    cfg.gridDim = dim3(nbins);
    cfg.blockDim = dim3(K2_THREADS);
    cfg.dynamicSmemBytes = K2_DYN_SMEM;
    cfg.stream = st;
    cudaLaunchAttribute at[1];
    at[0].id = cudaLaunchAttributeProgrammaticStreamSerialization;
    at[0].val.programmaticStreamSerializationAllowed = 1;
    cfg.attrs = at; cfg.numAttrs = 1;
    cudaLaunchKernelEx(&cfg, k2_kernel, x, w_c, out, N, NB);
}
```

```cpp
#include <cuda_runtime.h>
#include <cuda_bf16.h>
#include <stdint.h>

#define D_FEAT 128
#define MAX_N 16384
#define MAX_E (1 << 20)
#define LOG2E 1.4426950408889634f

#define MAXBINS 256
#define MAXNB 128
#define BINCAP 3072
__device__ uint4 g_T[(MAX_N + 1) * 32];
__device__ uint4 g_AU[MAX_N * 32];
__device__ int g_bin_cnt[MAXBINS];
__device__ uint2 g_bins[MAXBINS * BINCAP];
__device__ int g_ovf[MAX_E];
__device__ int g_ovf_cnt;
__device__ int g_done;

__device__ __forceinline__ float ex2_approx(float x) {
    float y; asm("ex2.approx.ftz.f32 %0, %1;" : "=f"(y) : "f"(x)); return y;
}
__device__ __forceinline__ float rcp_approx(float x) {
    float y; asm("rcp.approx.ftz.f32 %0, %1;" : "=f"(y) : "f"(x)); return y;
}
__device__ __forceinline__ uint32_t pack_bf16(float lo, float hi) {
    __nv_bfloat162 t = __floats2bfloat162_rn(lo, hi);
    return *reinterpret_cast<uint32_t*>(&t);
}
__device__ __forceinline__ float bf_lo(uint32_t v) { return __uint_as_float(v << 16); }
__device__ __forceinline__ float bf_hi(uint32_t v) { return __uint_as_float(v & 0xffff0000u); }
__device__ __forceinline__ float round_bf16(float x) { return __bfloat162float(__float2bfloat16_rn(x)); }

__device__ __forceinline__ void mma_bf16(float c[4], uint32_t a0, uint32_t a1, uint32_t a2, uint32_t a3,
                                         uint32_t b0, uint32_t b1) {
    asm volatile("mma.sync.aligned.m16n8k16.row.col.f32.bf16.bf16.f32 "
                 "{%0,%1,%2,%3}, {%4,%5,%6,%7}, {%8,%9}, {%0,%1,%2,%3};"
                 : "+f"(c[0]), "+f"(c[1]), "+f"(c[2]), "+f"(c[3])
                 : "r"(a0), "r"(a1), "r"(a2), "r"(a3), "r"(b0), "r"(b1));
}
__device__ __forceinline__ void ldmatrix_x4_trans(uint32_t& r0, uint32_t& r1, uint32_t& r2, uint32_t& r3, uint32_t addr) {
    asm volatile("ldmatrix.sync.aligned.m8n8.x4.trans.shared.b16 {%0,%1,%2,%3}, [%4];"
                 : "=r"(r0), "=r"(r1), "=r"(r2), "=r"(r3) : "r"(addr));
}

__device__ __forceinline__ void cp_async16(uint32_t saddr, const void* g) {
    asm volatile("cp.async.cg.shared.global [%0], [%1], 16;" :: "r"(saddr), "l"(g) : "memory");
}
__device__ __forceinline__ void cp_async16_zfill(uint32_t saddr, const void* g, int src_size) {
    asm volatile("cp.async.cg.shared.global [%0], [%1], 16, %2;" :: "r"(saddr), "l"(g), "r"(src_size) : "memory");
}
__device__ __forceinline__ void stage_weight(uint32_t sdst, const __nv_bfloat16* w, int mtx, int tid, int nthreads) {
    const uint4* W = reinterpret_cast<const uint4*>(w);
    for (int u = tid; u < 2048; u += nthreads) {
        int k = u >> 4, c16 = u & 15;
        int kg = k >> 3, rr = k & 7;
        int h = mtx * 2 + (c16 >> 3);
        cp_async16(sdst + kg * 4096 + h * 1024 + rr * 128 + (((c16 & 7) ^ rr) << 4), W + u);
    }
}
__device__ __forceinline__ void stage_x_tile(uint32_t sdst, const __nv_bfloat16* x, int row0, int N, int tid, int nthreads) {
    const uint4* X = reinterpret_cast<const uint4*>(x);
    for (int u = tid; u < 1024; u += nthreads) {
        int r = u >> 4, c16 = u & 15;
        int gr = row0 + r;
        bool ok = gr < N;
        cp_async16_zfill(sdst + (c16 >> 3) * 8192 + r * 128 + (((c16 & 7) ^ (r & 7)) << 4),
                         X + (size_t)(ok ? gr : 0) * 16 + c16, ok ? 16 : 0);
    }
}

__device__ __forceinline__ void wgmma_m64n128k16(float d[64], uint64_t desc_a, uint64_t desc_b, int scale_d) {
    asm volatile("{\n.reg .pred p;\nsetp.ne.b32 p, %66, 0;\n"
                 "wgmma.mma_async.sync.aligned.m64n128k16.f32.bf16.bf16 {%0,%1,%2,%3,%4,%5,%6,%7,%8,%9,%10,%11,%12,%13,%14,%15,%16,%17,%18,%19,%20,%21,%22,%23,%24,%25,%26,%27,%28,%29,%30,%31,%32,%33,%34,%35,%36,%37,%38,%39,%40,%41,%42,%43,%44,%45,%46,%47,%48,%49,%50,%51,%52,%53,%54,%55,%56,%57,%58,%59,%60,%61,%62,%63}, %64, %65, p, 1, 1, 0, 1;\n}"
                 : "+f"(d[0]),"+f"(d[1]),"+f"(d[2]),"+f"(d[3]),"+f"(d[4]),"+f"(d[5]),"+f"(d[6]),"+f"(d[7]),"+f"(d[8]),"+f"(d[9]),"+f"(d[10]),"+f"(d[11]),"+f"(d[12]),"+f"(d[13]),"+f"(d[14]),"+f"(d[15]),"+f"(d[16]),"+f"(d[17]),"+f"(d[18]),"+f"(d[19]),"+f"(d[20]),"+f"(d[21]),"+f"(d[22]),"+f"(d[23]),"+f"(d[24]),"+f"(d[25]),"+f"(d[26]),"+f"(d[27]),"+f"(d[28]),"+f"(d[29]),"+f"(d[30]),"+f"(d[31]),"+f"(d[32]),"+f"(d[33]),"+f"(d[34]),"+f"(d[35]),"+f"(d[36]),"+f"(d[37]),"+f"(d[38]),"+f"(d[39]),"+f"(d[40]),"+f"(d[41]),"+f"(d[42]),"+f"(d[43]),"+f"(d[44]),"+f"(d[45]),"+f"(d[46]),"+f"(d[47]),"+f"(d[48]),"+f"(d[49]),"+f"(d[50]),"+f"(d[51]),"+f"(d[52]),"+f"(d[53]),"+f"(d[54]),"+f"(d[55]),"+f"(d[56]),"+f"(d[57]),"+f"(d[58]),"+f"(d[59]),"+f"(d[60]),"+f"(d[61]),"+f"(d[62]),"+f"(d[63])
                 : "l"(desc_a), "l"(desc_b), "r"(scale_d));
}

#define K1_GW 8
#define K1_THREADS ((K1_GW + 8) * 32)
#define P1_EPT 10
#define P1_CHUNK (256 * P1_EPT)
#define K1_WBYTES (131072 + 2 * 16384)
#define K1_SMEM (K1_WBYTES + 3 * MAXBINS * 4 + P1_CHUNK * 8)

__device__ __forceinline__ void p1_bar() { asm volatile("bar.sync 1, 256;" ::: "memory"); }

__global__ void __launch_bounds__(K1_THREADS, 1) k1_kernel(
    const __nv_bfloat16* __restrict__ x, const __nv_bfloat16* __restrict__ e_attr,
    const int* __restrict__ src, const int* __restrict__ dst,
    const __nv_bfloat16* __restrict__ w_b, const __nv_bfloat16* __restrict__ w_v,
    const __nv_bfloat16* __restrict__ w_a, const __nv_bfloat16* __restrict__ w_u,
    int N, int E, int chunk, int NB, int nbins, uint32_t magic)
{
    extern __shared__ __align__(1024) uint8_t smem[];
    asm volatile("griddepcontrol.launch_dependents;");

    const int warp = threadIdx.x >> 5, lane = threadIdx.x & 31;

    if (warp >= K1_GW) {
        const int tid = threadIdx.x - K1_GW * 32;
        if (blockIdx.x == 0 && tid < 32)
            g_T[(size_t)N * 32 + tid] = make_uint4(0xff80ff80u, 0xff80ff80u, 0u, 0u);
        int* hist = reinterpret_cast<int*>(smem + K1_WBYTES);
        int* loff = hist + MAXBINS;
        int* gbase = loff + MAXBINS;
        uint2* sorted = reinterpret_cast<uint2*>(smem + K1_WBYTES + 3 * MAXBINS * 4);
        for (int beg = blockIdx.x * chunk; beg < E; beg += gridDim.x * chunk) {
            const int end = min(E, beg + chunk);
            int d[P1_EPT]; uint32_t rec[P1_EPT]; int rk[P1_EPT]; int bn[P1_EPT];
            #pragma unroll
            for (int i = 0; i < P1_EPT; i++) {
                int e = beg + i * 256 + tid;
                d[i] = -1;
                if (e < end) {
                    d[i] = __ldg(dst + e);
                    uint32_t s = (uint32_t)__ldg(src + e);
                    uint32_t ev = (uint32_t)__ldg(reinterpret_cast<const unsigned short*>(e_attr) + e);
                    rec[i] = (ev << 16) | s;
                }
            }
            hist[tid] = 0;
            p1_bar();
            #pragma unroll
            for (int i = 0; i < P1_EPT; i++) {
                if (d[i] >= 0) {
                    bn[i] = (int)(((uint64_t)(uint32_t)d[i] * magic) >> 24);
                    rk[i] = atomicAdd(&hist[bn[i]], 1);
                }
            }
            p1_bar();
            {
                int h = hist[tid];
                if (tid < nbins && h > 0) gbase[tid] = atomicAdd(&g_bin_cnt[tid], h);
                if (tid < 32) {
                    int v[8]; int sum = 0;
                    #pragma unroll
                    for (int i = 0; i < 8; i++) { v[i] = hist[lane * 8 + i]; sum += v[i]; }
                    int inc = sum;
                    #pragma unroll
                    for (int o = 1; o < 32; o <<= 1) { int t = __shfl_up_sync(0xffffffffu, inc, o); if (lane >= o) inc += t; }
                    int run = inc - sum;
                    #pragma unroll
                    for (int i = 0; i < 8; i++) { loff[lane * 8 + i] = run; run += v[i]; }
                }
            }
            p1_bar();
            #pragma unroll
            for (int i = 0; i < P1_EPT; i++) {
                if (d[i] >= 0) sorted[loff[bn[i]] + rk[i]] = make_uint2(rec[i], (uint32_t)d[i]);
            }
            p1_bar();
            const int cnt = end - beg;
            for (int i = tid; i < cnt; i += 256) {
                uint2 r = sorted[i];
                int b = (int)(((uint64_t)r.y * magic) >> 24);
                int pos = gbase[b] + (i - loff[b]);
                if (pos < BINCAP) {
                    g_bins[b * BINCAP + pos] = make_uint2(r.x, r.y - (uint32_t)(b * NB));
                } else {
                    int p = atomicAdd(&g_ovf_cnt, 2);
                    g_ovf[p] = (int)r.y; g_ovf[p + 1] = (int)r.x;
                }
            }
            p1_bar();
        }
        return;
    }

    const int q = lane & 3;
    const int wg = warp >> 2;
    const int n_tasks = ((N + 63) >> 6) * 4;
    const uint32_t sbase = (uint32_t)__cvta_generic_to_shared(smem);
    const uint32_t xbase = sbase + 131072;
    bool w_staged = false;
    int t_beg = (int)(((long long)n_tasks * blockIdx.x) / gridDim.x);
    const int t_end = (int)(((long long)n_tasks * (blockIdx.x + 1)) / gridDim.x);
    while (t_beg < t_end) {
        const int tile0 = t_beg >> 2;
        const int t_stop = min(t_end, (tile0 + 2) << 2);
        stage_x_tile(xbase, x, tile0 * 64, N, threadIdx.x, K1_GW * 32);
        if (((t_stop - 1) >> 2) > tile0) stage_x_tile(xbase + 16384, x, tile0 * 64 + 64, N, threadIdx.x, K1_GW * 32);
        if (!w_staged) {
            stage_weight(sbase, w_b, 0, threadIdx.x, K1_GW * 32);
            stage_weight(sbase, w_v, 1, threadIdx.x, K1_GW * 32);
            stage_weight(sbase + 65536, w_a, 0, threadIdx.x, K1_GW * 32);
            stage_weight(sbase + 65536, w_u, 1, threadIdx.x, K1_GW * 32);
            w_staged = true;
        }
        asm volatile("cp.async.wait_all;" ::: "memory");
        asm volatile("fence.proxy.async.shared::cta;" ::: "memory");
        asm volatile("bar.sync 2, %0;" :: "n"(K1_GW * 32) : "memory");
        for (int task = t_beg + wg; task < t_stop; task += 2) {
            const int tile = task >> 2, type = (task >> 1) & 1, hf = task & 1;
            const uint32_t baddr = sbase + type * 65536 + hf * 1024;
            const uint64_t descb = (uint64_t)((baddr & 0x3FFFF) >> 4) | ((uint64_t)(2048 >> 4) << 16) |
                                   ((uint64_t)(4096 >> 4) << 32) | ((uint64_t)1 << 62);
            const uint32_t aaddr = xbase + (tile - tile0) * 16384;
            const uint64_t desca = (uint64_t)((aaddr & 0x3FFFF) >> 4) | ((uint64_t)1 << 16) |
                                   ((uint64_t)(1024 >> 4) << 32) | ((uint64_t)1 << 62);
            float d[64];
            asm volatile("wgmma.fence.sync.aligned;" ::: "memory");
            #pragma unroll
            for (int ks = 0; ks < 8; ks++) {
                wgmma_m64n128k16(d, desca + (uint64_t)(((ks >> 2) * 8192 + (ks & 3) * 32) >> 4),
                                 descb + (uint64_t)(ks * (8192 >> 4)), ks > 0 ? 1 : 0);
            }
            asm volatile("wgmma.commit_group.sync.aligned;" ::: "memory");
            asm volatile("wgmma.wait_group.sync.aligned 0;" ::: "memory");
            uint4* outp = (type ? g_AU : g_T);
            const int r0 = tile * 64 + (warp & 3) * 16 + (lane >> 2);
            #pragma unroll
            for (int mm = 0; mm < 4; mm++) {
                const int j0 = 2 * mm, j1 = 2 * mm + 1, j2 = 8 + 2 * mm, j3 = 9 + 2 * mm;
                uint4 o0 = make_uint4(pack_bf16(d[4 * j0], d[4 * j0 + 1]), pack_bf16(d[4 * j1], d[4 * j1 + 1]),
                                      pack_bf16(d[4 * j2], d[4 * j2 + 1]), pack_bf16(d[4 * j3], d[4 * j3 + 1]));
                uint4 o1 = make_uint4(pack_bf16(d[4 * j0 + 2], d[4 * j0 + 3]), pack_bf16(d[4 * j1 + 2], d[4 * j1 + 3]),
                                      pack_bf16(d[4 * j2 + 2], d[4 * j2 + 3]), pack_bf16(d[4 * j3 + 2], d[4 * j3 + 3]));
                const int m = 4 * hf + mm;
                if (r0 < N) outp[(size_t)r0 * 32 + 4 * m + q] = o0;
                if (r0 + 8 < N) outp[(size_t)(r0 + 8) * 32 + 4 * m + q] = o1;
            }
        }
        t_beg = t_stop;
        if (t_beg < t_end) asm volatile("bar.sync 2, %0;" :: "n"(K1_GW * 32) : "memory");
    }
}

__device__ __forceinline__ void edge_accum(const uint4 v, const float e, const float a[4], const float cc[4],
                                           float num[4], float den[4]) {
    float y0 = fmaf(bf_lo(v.x), -LOG2E, fmaf(e, cc[0], a[0]));
    float y1 = fmaf(bf_hi(v.x), -LOG2E, fmaf(e, cc[1], a[1]));
    float y2 = fmaf(bf_lo(v.y), -LOG2E, fmaf(e, cc[2], a[2]));
    float y3 = fmaf(bf_hi(v.y), -LOG2E, fmaf(e, cc[3], a[3]));
    float s0 = rcp_approx(1.f + ex2_approx(y0));
    float s1 = rcp_approx(1.f + ex2_approx(y1));
    float s2 = rcp_approx(1.f + ex2_approx(y2));
    float s3 = rcp_approx(1.f + ex2_approx(y3));
    den[0] += s0; den[1] += s1; den[2] += s2; den[3] += s3;
    num[0] = fmaf(s0, bf_lo(v.z), num[0]);
    num[1] = fmaf(s1, bf_hi(v.z), num[1]);
    num[2] = fmaf(s2, bf_lo(v.w), num[2]);
    num[3] = fmaf(s3, bf_hi(v.w), num[3]);
}

#define K2_THREADS 1024
#define K2_D 3
#define K2_GS 2
#define K2_RPT ((BINCAP + K2_THREADS - 1) / K2_THREADS)
#define K2_NW (K2_THREADS / 32)
#define SORT_WORDS (BINCAP + 4 * MAXNB)
#define K2_OFF_AU 0
#define K2_OFF_X (K2_OFF_AU + MAXNB * 512)
#define K2_OFF_PART (K2_OFF_X + MAXNB * 256)
#define K2_OFF_SORT (K2_OFF_PART + K2_NW * 1024)
#define K2_OFF_HIST (K2_OFF_SORT + SORT_WORDS * 4)
#define K2_OFF_OFF (K2_OFF_HIST + MAXNB * 4)
#define K2_DYN_SMEM (K2_OFF_OFF + (MAXNB + 4) * 4)

struct Grp { uint4 v[K2_GS]; };

__device__ __forceinline__ const uint4* row_ptr(const char* Tl, uint32_t rec) {
    return reinterpret_cast<const uint4*>(Tl + (size_t)((rec & 0xffffu) * 512u));
}
__device__ __forceinline__ void grp_load(Grp& g, const uint32_t* sp, const char* Tl) {
    const uint2 t = *reinterpret_cast<const uint2*>(sp);
    g.v[0] = __ldg(row_ptr(Tl, t.x));
    g.v[1] = __ldg(row_ptr(Tl, t.y));
}
__device__ __forceinline__ void grp_consume(const Grp& g, const uint32_t* sp, const float a[4], const float cc[4],
                                            float num[4], float den[4]) {
    const uint2 t = *reinterpret_cast<const uint2*>(sp);
    edge_accum(g.v[0], bf_hi(t.x), a, cc, num, den);
    edge_accum(g.v[1], bf_hi(t.y), a, cc, num, den);
}

__device__ __forceinline__ void write_node(const uint4* s_au, const uint32_t* s_x, __nv_bfloat16* out, int ln, int n,
                                           int lane, int fw, const float num[4], const float den[4]) {
    const uint2 uv = *(reinterpret_cast<const uint2*>(s_au + ln * 32 + lane) + 1);
    const uint32_t x0 = s_x[ln * 64 + fw], x1 = s_x[ln * 64 + fw + 4];
    const float u4[4] = { bf_lo(uv.x), bf_hi(uv.x), bf_lo(uv.y), bf_hi(uv.y) };
    const float x4[4] = { bf_lo(x0), bf_hi(x0), bf_lo(x1), bf_hi(x1) };
    float o[4];
    #pragma unroll
    for (int i = 0; i < 4; i++) {
        float agg = round_bf16(__fdividef(num[i], den[i] + 1e-6f));
        float z = round_bf16(u4[i] + agg);
        float rz = (z > 0.f) ? z : 0.f * z;
        o[i] = x4[i] + rz;
    }
    uint32_t* o32 = reinterpret_cast<uint32_t*>(out) + (size_t)n * 64 + fw;
    o32[0] = pack_bf16(o[0], o[1]); o32[4] = pack_bf16(o[2], o[3]);
}

__device__ __noinline__ void slow_path(const uint4* s_au, const uint32_t* s_x, const uint32_t* s_sorted, const int* s_off,
                                       __nv_bfloat16* out, int node0, int nn, int ovf_n, float c0, float c1, float c2, float c3) {
    const int lane = threadIdx.x & 31, warp = threadIdx.x >> 5;
    const int fw = (lane >> 2) * 8 + (lane & 3);
    const float cc[4] = { c0, c1, c2, c3 };
    const char* Tl = reinterpret_cast<const char*>(g_T) + lane * 16;
    for (int ln = warp; ln < nn; ln += K2_NW) {
        const uint2 av = *reinterpret_cast<const uint2*>(s_au + ln * 32 + lane);
        const float a[4] = { -LOG2E * bf_lo(av.x), -LOG2E * bf_hi(av.x), -LOG2E * bf_lo(av.y), -LOG2E * bf_hi(av.y) };
        float num[4] = {0.f, 0.f, 0.f, 0.f}, den[4] = {0.f, 0.f, 0.f, 0.f};
        for (int i = s_off[ln]; i < s_off[ln + 1]; i++) {
            const uint32_t r = s_sorted[i];
            edge_accum(__ldg(row_ptr(Tl, r)), bf_hi(r), a, cc, num, den);
        }
        const int n = node0 + ln;
        for (int base = 0; base < ovf_n; base += 64) {
            int i2 = base + 2 * lane;
            int od = (i2 < ovf_n) ? g_ovf[i2] : -1;
            uint32_t orec = (i2 < ovf_n) ? (uint32_t)g_ovf[i2 + 1] : 0u;
            unsigned msk = __ballot_sync(0xffffffffu, od == n);
            while (msk) {
                int l = __ffs(msk) - 1; msk &= msk - 1;
                uint32_t r = __shfl_sync(0xffffffffu, orec, l);
                edge_accum(__ldg(row_ptr(Tl, r)), bf_hi(r), a, cc, num, den);
            }
        }
        write_node(s_au, s_x, out, ln, n, lane, fw, num, den);
    }
}

__global__ void __launch_bounds__(K2_THREADS, 1) k2_kernel(
    const __nv_bfloat16* __restrict__ x,
    const __nv_bfloat16* __restrict__ w_c, __nv_bfloat16* __restrict__ out, int N, int NB)
{
    extern __shared__ __align__(1024) uint8_t smem[];
    uint4* s_au = reinterpret_cast<uint4*>(smem + K2_OFF_AU);
    uint32_t* s_x = reinterpret_cast<uint32_t*>(smem + K2_OFF_X);
    float4* s_part = reinterpret_cast<float4*>(smem + K2_OFF_PART);
    uint32_t* s_sorted = reinterpret_cast<uint32_t*>(smem + K2_OFF_SORT);
    int* s_hist = reinterpret_cast<int*>(smem + K2_OFF_HIST);
    int* s_off = reinterpret_cast<int*>(smem + K2_OFF_OFF);

    const int tid = threadIdx.x;
    const int lane = tid & 31, warp = tid >> 5;
    const int bin = blockIdx.x;
    const int node0 = bin * NB;
    const int nn = min(NB, N - node0);
    const uint32_t sb = (uint32_t)__cvta_generic_to_shared(smem);

    for (int i = tid; i < nn * 16; i += K2_THREADS)
        cp_async16(sb + K2_OFF_X + i * 16, reinterpret_cast<const uint4*>(x) + (size_t)node0 * 16 + i);
    if (tid < MAXNB) s_hist[tid] = 0;
    for (int i = tid; i < SORT_WORDS; i += K2_THREADS) s_sorted[i] = (uint32_t)N;
    s_part[warp * 64 + lane] = make_float4(0.f, 0.f, 0.f, 0.f);
    s_part[warp * 64 + 32 + lane] = make_float4(0.f, 0.f, 0.f, 0.f);
    __syncthreads();
    const int fw = (lane >> 2) * 8 + (lane & 3);
    const uint2 wc = make_uint2(__ldg(reinterpret_cast<const uint32_t*>(w_c) + fw), __ldg(reinterpret_cast<const uint32_t*>(w_c) + fw + 4));
    float cc[4] = { -LOG2E * bf_lo(wc.x), -LOG2E * bf_hi(wc.x), -LOG2E * bf_lo(wc.y), -LOG2E * bf_hi(wc.y) };

    asm volatile("griddepcontrol.wait;" ::: "memory");

    for (int i = tid; i < nn * 32; i += K2_THREADS)
        cp_async16(sb + K2_OFF_AU + i * 16, g_AU + (size_t)node0 * 32 + i);

    const int cnt = min(g_bin_cnt[bin], BINCAP);
    const int ovf_n = g_ovf_cnt;
    {
        uint2 r[K2_RPT]; int rk[K2_RPT];
        #pragma unroll
        for (int i = 0; i < K2_RPT; i++) {
            int idx = i * K2_THREADS + tid;
            if (idx < cnt) r[i] = g_bins[bin * BINCAP + idx];
        }
        #pragma unroll
        for (int i = 0; i < K2_RPT; i++) {
            int idx = i * K2_THREADS + tid;
            if (idx < cnt) rk[i] = atomicAdd(&s_hist[r[i].y], 1);
        }
        __syncthreads();
        if (warp == 0) {
            int v[4]; int sum = 0;
            #pragma unroll
            for (int i = 0; i < 4; i++) { v[i] = (s_hist[lane * 4 + i] + K2_GS - 1) & ~(K2_GS - 1); sum += v[i]; }
            int inc = sum;
            #pragma unroll
            for (int o = 1; o < 32; o <<= 1) { int t = __shfl_up_sync(0xffffffffu, inc, o); if (lane >= o) inc += t; }
            int run = inc - sum;
            #pragma unroll
            for (int i = 0; i < 4; i++) { s_off[lane * 4 + i] = run; run += v[i]; }
            if (lane == 31) s_off[MAXNB] = run;
        }
        if (tid == 32) g_bin_cnt[bin] = 0;
        __syncthreads();
        #pragma unroll
        for (int i = 0; i < K2_RPT; i++) {
            int idx = i * K2_THREADS + tid;
            if (idx < cnt) s_sorted[s_off[r[i].y] + rk[i]] = r[i].x;
        }
        asm volatile("cp.async.wait_all;" ::: "memory");
        __syncthreads();
    }

    if (ovf_n != 0) {
        slow_path(s_au, s_x, s_sorted, s_off, out, node0, nn, ovf_n, cc[0], cc[1], cc[2], cc[3]);
        __syncthreads();
        if (tid == 0) {
            __threadfence();
            int t = atomicAdd(&g_done, 1);
            if (t == (int)gridDim.x - 1) { g_done = 0; __threadfence(); g_ovf_cnt = 0; }
        }
        return;
    }

    const char* Tl = reinterpret_cast<const char*>(g_T) + lane * 16;
    const int G = s_off[MAXNB] / K2_GS;
    int g = (G * warp) / K2_NW;
    const int g1 = (G * (warp + 1)) / K2_NW;
    int ln;
    {
        int c_lo = 0;
        #pragma unroll
        for (int i = 0; i < 4; i++) {
            int node = i * 32 + lane;
            int o = (node < nn) ? s_off[node] : 0x7fffffff;
            c_lo += __popc(__ballot_sync(0xffffffffu, o < g * K2_GS));
        }
        ln = c_lo;
    }
    bool head = ln > 0;
    if (head) ln--;
    float a[4], num[4] = {0.f, 0.f, 0.f, 0.f}, den[4] = {0.f, 0.f, 0.f, 0.f};
    int node_end;

    auto load_node = [&]() {
        const uint2 av = *reinterpret_cast<const uint2*>(s_au + ln * 32 + lane);
        a[0] = -LOG2E * bf_lo(av.x); a[1] = -LOG2E * bf_hi(av.x); a[2] = -LOG2E * bf_lo(av.y); a[3] = -LOG2E * bf_hi(av.y);
        node_end = s_off[ln + 1] / K2_GS;
    };
    auto finish_node = [&]() { write_node(s_au, s_x, out, ln, node0 + ln, lane, fw, num, den); };
    auto close_node = [&]() {
        if (head) {
            s_part[warp * 64 + lane] = make_float4(num[0], num[1], num[2], num[3]);
            s_part[warp * 64 + 32 + lane] = make_float4(den[0], den[1], den[2], den[3]);
            head = false;
        } else {
            finish_node();
        }
        #pragma unroll
        for (int i = 0; i < 4; i++) { num[i] = 0.f; den[i] = 0.f; }
    };

    bool tail = false;
    if (g < g1 || warp == K2_NW - 1) {
        load_node();
        Grp b[K2_D];
        #pragma unroll
        for (int d = 0; d < K2_D; d++)
            if (g + d < g1) grp_load(b[d], s_sorted + K2_GS * (g + d), Tl);
        while (g < g1) {
            #pragma unroll
            for (int d = 0; d < K2_D; d++) {
                if (g < g1) {
                    while (g == node_end) { close_node(); ln++; load_node(); }
                    grp_consume(b[d], s_sorted + K2_GS * g, a, cc, num, den);
                    if (g + K2_D < g1) grp_load(b[d], s_sorted + K2_GS * (g + K2_D), Tl);
                    g++;
                }
            }
        }
        if (warp == K2_NW - 1) {
            while (true) { close_node(); ln++; if (ln >= nn) break; load_node(); }
        } else if (node_end == g1 || head) {
            close_node();
        } else {
            tail = true;
        }
    }
    __syncthreads();
    if (tail) {
        for (int w2 = warp + 1; w2 < K2_NW && (G * w2) / K2_NW < node_end; w2++) {
            const float4 pn = s_part[w2 * 64 + lane], pd = s_part[w2 * 64 + 32 + lane];
            num[0] += pn.x; num[1] += pn.y; num[2] += pn.z; num[3] += pn.w;
            den[0] += pd.x; den[1] += pd.y; den[2] += pd.z; den[3] += pd.w;
        }
        finish_node();
    }
}

extern "C" void kernel_launch(void* const* d_in, const int* in_sizes, int n_in,
                              void* d_out, int out_size) {
    const __nv_bfloat16* x      = (const __nv_bfloat16*)d_in[0];
    const __nv_bfloat16* e_attr = (const __nv_bfloat16*)d_in[1];
    const int* src = (const int*)d_in[2];
    const int* dst = (const int*)d_in[3];
    const __nv_bfloat16* w_a = (const __nv_bfloat16*)d_in[4];
    const __nv_bfloat16* w_b = (const __nv_bfloat16*)d_in[5];
    const __nv_bfloat16* w_c = (const __nv_bfloat16*)d_in[6];
    const __nv_bfloat16* w_u = (const __nv_bfloat16*)d_in[7];
    const __nv_bfloat16* w_v = (const __nv_bfloat16*)d_in[8];
    __nv_bfloat16* out = (__nv_bfloat16*)d_out;
    const int N = in_sizes[0] / D_FEAT;
    const int E = in_sizes[2];
    if (N > MAX_N || 2 * E > MAX_E || N <= 0) return;

    static int num_sms = 0;
    if (num_sms == 0) {
        int dev = 0;
        cudaGetDevice(&dev);
        cudaDeviceGetAttribute(&num_sms, cudaDevAttrMultiProcessorCount, dev);
        if (num_sms <= 0 || num_sms > MAXBINS) num_sms = 132;
        cudaFuncSetAttribute(k1_kernel, cudaFuncAttributeMaxDynamicSharedMemorySize, K1_SMEM);
        cudaFuncSetAttribute(k2_kernel, cudaFuncAttributeMaxDynamicSharedMemorySize, K2_DYN_SMEM);
    }
    cudaStream_t st = cudaStreamPerThread;
    int NB = (N + num_sms - 1) / num_sms;
    if (NB > MAXNB) NB = MAXNB;
    const int nbins = (N + NB - 1) / NB;
    const uint32_t magic = (uint32_t)(((1u << 24) + NB - 1) / NB);
    const int P = num_sms;
    int chunk = (E + P - 1) / P;
    if (chunk > P1_CHUNK) chunk = P1_CHUNK;
    if (chunk < 1) chunk = 1;
    k1_kernel<<<P, K1_THREADS, K1_SMEM, st>>>(x, e_attr, src, dst, w_b, w_v, w_a, w_u, N, E, chunk, NB, nbins, magic);

    cudaLaunchConfig_t cfg = {};
    cfg.gridDim = dim3(nbins);
    cfg.blockDim = dim3(K2_THREADS);
    cfg.dynamicSmemBytes = K2_DYN_SMEM;
    cfg.stream = st;
    cudaLaunchAttribute at[1];
    at[0].id = cudaLaunchAttributeProgrammaticStreamSerialization;
    at[0].val.programmaticStreamSerializationAllowed = 1;
    cfg.attrs = at; cfg.numAttrs = 1;
    cudaLaunchKernelEx(&cfg, k2_kernel, x, w_c, out, N, NB);
}
```

```cpp
#include <cuda_runtime.h>
#include <cuda_bf16.h>
#include <stdint.h>

#define D_FEAT 128
#define MAX_N 16384
#define MAX_E (1 << 20)
#define LOG2E 1.4426950408889634f

#define MAXBINS 256
#define MAXNB 128
#define BINCAP 3072
__device__ uint4 g_T[(MAX_N + 1) * 32];
__device__ int g_bin_cnt[MAXBINS];
__device__ uint2 g_bins[MAXBINS * BINCAP];
__device__ int g_ovf[MAX_E];
__device__ int g_ovf_cnt;
__device__ int g_done;

__device__ __forceinline__ float ex2_approx(float x) {
    float y; asm("ex2.approx.ftz.f32 %0, %1;" : "=f"(y) : "f"(x)); return y;
}
__device__ __forceinline__ float rcp_approx(float x) {
    float y; asm("rcp.approx.ftz.f32 %0, %1;" : "=f"(y) : "f"(x)); return y;
}
__device__ __forceinline__ uint32_t pack_bf16(float lo, float hi) {
    __nv_bfloat162 t = __floats2bfloat162_rn(lo, hi);
    return *reinterpret_cast<uint32_t*>(&t);
}
__device__ __forceinline__ float bf_lo(uint32_t v) { return __uint_as_float(v << 16); }
__device__ __forceinline__ float bf_hi(uint32_t v) { return __uint_as_float(v & 0xffff0000u); }
__device__ __forceinline__ float round_bf16(float x) { return __bfloat162float(__float2bfloat16_rn(x)); }

__device__ __forceinline__ void mma_bf16(float c[4], uint32_t a0, uint32_t a1, uint32_t a2, uint32_t a3,
                                         uint32_t b0, uint32_t b1) {
    asm volatile("mma.sync.aligned.m16n8k16.row.col.f32.bf16.bf16.f32 "
                 "{%0,%1,%2,%3}, {%4,%5,%6,%7}, {%8,%9}, {%0,%1,%2,%3};"
                 : "+f"(c[0]), "+f"(c[1]), "+f"(c[2]), "+f"(c[3])
                 : "r"(a0), "r"(a1), "r"(a2), "r"(a3), "r"(b0), "r"(b1));
}
__device__ __forceinline__ void ldmatrix_x4_trans(uint32_t& r0, uint32_t& r1, uint32_t& r2, uint32_t& r3, uint32_t addr) {
    asm volatile("ldmatrix.sync.aligned.m8n8.x4.trans.shared.b16 {%0,%1,%2,%3}, [%4];"
                 : "=r"(r0), "=r"(r1), "=r"(r2), "=r"(r3) : "r"(addr));
}

__device__ __forceinline__ void cp_async16(uint32_t saddr, const void* g) {
    asm volatile("cp.async.cg.shared.global [%0], [%1], 16;" :: "r"(saddr), "l"(g) : "memory");
}
__device__ __forceinline__ void cp_async16_zfill(uint32_t saddr, const void* g, int src_size) {
    asm volatile("cp.async.cg.shared.global [%0], [%1], 16, %2;" :: "r"(saddr), "l"(g), "r"(src_size) : "memory");
}
__device__ __forceinline__ void stage_weight(uint32_t sdst, const __nv_bfloat16* w, int mtx, int tid, int nthreads) {
    const uint4* W = reinterpret_cast<const uint4*>(w);
    for (int u = tid; u < 2048; u += nthreads) {
        int k = u >> 4, c16 = u & 15;
        int kg = k >> 3, rr = k & 7;
        int h = mtx * 2 + (c16 >> 3);
        cp_async16(sdst + kg * 4096 + h * 1024 + rr * 128 + (((c16 & 7) ^ rr) << 4), W + u);
    }
}
__device__ __forceinline__ void stage_x_tile(uint32_t sdst, const __nv_bfloat16* x, int row0, int N, int tid, int nthreads) {
    const uint4* X = reinterpret_cast<const uint4*>(x);
    for (int u = tid; u < 1024; u += nthreads) {
        int r = u >> 4, c16 = u & 15;
        int gr = row0 + r;
        bool ok = gr < N;
        cp_async16_zfill(sdst + (c16 >> 3) * 8192 + r * 128 + (((c16 & 7) ^ (r & 7)) << 4),
                         X + (size_t)(ok ? gr : 0) * 16 + c16, ok ? 16 : 0);
    }
}

__device__ __forceinline__ void wgmma_m64n128k16(float d[64], uint64_t desc_a, uint64_t desc_b, int scale_d) {
    asm volatile("{\n.reg .pred p;\nsetp.ne.b32 p, %66, 0;\n"
                 "wgmma.mma_async.sync.aligned.m64n128k16.f32.bf16.bf16 {%0,%1,%2,%3,%4,%5,%6,%7,%8,%9,%10,%11,%12,%13,%14,%15,%16,%17,%18,%19,%20,%21,%22,%23,%24,%25,%26,%27,%28,%29,%30,%31,%32,%33,%34,%35,%36,%37,%38,%39,%40,%41,%42,%43,%44,%45,%46,%47,%48,%49,%50,%51,%52,%53,%54,%55,%56,%57,%58,%59,%60,%61,%62,%63}, %64, %65, p, 1, 1, 0, 1;\n}"
                 : "+f"(d[0]),"+f"(d[1]),"+f"(d[2]),"+f"(d[3]),"+f"(d[4]),"+f"(d[5]),"+f"(d[6]),"+f"(d[7]),"+f"(d[8]),"+f"(d[9]),"+f"(d[10]),"+f"(d[11]),"+f"(d[12]),"+f"(d[13]),"+f"(d[14]),"+f"(d[15]),"+f"(d[16]),"+f"(d[17]),"+f"(d[18]),"+f"(d[19]),"+f"(d[20]),"+f"(d[21]),"+f"(d[22]),"+f"(d[23]),"+f"(d[24]),"+f"(d[25]),"+f"(d[26]),"+f"(d[27]),"+f"(d[28]),"+f"(d[29]),"+f"(d[30]),"+f"(d[31]),"+f"(d[32]),"+f"(d[33]),"+f"(d[34]),"+f"(d[35]),"+f"(d[36]),"+f"(d[37]),"+f"(d[38]),"+f"(d[39]),"+f"(d[40]),"+f"(d[41]),"+f"(d[42]),"+f"(d[43]),"+f"(d[44]),"+f"(d[45]),"+f"(d[46]),"+f"(d[47]),"+f"(d[48]),"+f"(d[49]),"+f"(d[50]),"+f"(d[51]),"+f"(d[52]),"+f"(d[53]),"+f"(d[54]),"+f"(d[55]),"+f"(d[56]),"+f"(d[57]),"+f"(d[58]),"+f"(d[59]),"+f"(d[60]),"+f"(d[61]),"+f"(d[62]),"+f"(d[63])
                 : "l"(desc_a), "l"(desc_b), "r"(scale_d));
}

__device__ __forceinline__ void wgmma_m64n64k16(float d[32], uint64_t desc_a, uint64_t desc_b, int scale_d) {
    asm volatile("{\n.reg .pred p;\nsetp.ne.b32 p, %34, 0;\n"
                 "wgmma.mma_async.sync.aligned.m64n64k16.f32.bf16.bf16 {%0,%1,%2,%3,%4,%5,%6,%7,%8,%9,%10,%11,%12,%13,%14,%15,%16,%17,%18,%19,%20,%21,%22,%23,%24,%25,%26,%27,%28,%29,%30,%31}, %32, %33, p, 1, 1, 0, 1;\n}"
                 : "+f"(d[0]),"+f"(d[1]),"+f"(d[2]),"+f"(d[3]),"+f"(d[4]),"+f"(d[5]),"+f"(d[6]),"+f"(d[7]),"+f"(d[8]),"+f"(d[9]),"+f"(d[10]),"+f"(d[11]),"+f"(d[12]),"+f"(d[13]),"+f"(d[14]),"+f"(d[15]),"+f"(d[16]),"+f"(d[17]),"+f"(d[18]),"+f"(d[19]),"+f"(d[20]),"+f"(d[21]),"+f"(d[22]),"+f"(d[23]),"+f"(d[24]),"+f"(d[25]),"+f"(d[26]),"+f"(d[27]),"+f"(d[28]),"+f"(d[29]),"+f"(d[30]),"+f"(d[31])
                 : "l"(desc_a), "l"(desc_b), "r"(scale_d));
}

#define K1_GW 12
#define K1_THREADS ((K1_GW + 8) * 32)
#define P1_EPT 10
#define P1_CHUNK (256 * P1_EPT)
#define K1_WBYTES (65536 + 2 * 16384)
#define K1_SMEM (K1_WBYTES + 3 * MAXBINS * 4 + P1_CHUNK * 8)

__device__ __forceinline__ void p1_bar() { asm volatile("bar.sync 1, 256;" ::: "memory"); }

__global__ void __launch_bounds__(K1_THREADS, 1) k1_kernel(
    const __nv_bfloat16* __restrict__ x, const __nv_bfloat16* __restrict__ e_attr,
    const int* __restrict__ src, const int* __restrict__ dst,
    const __nv_bfloat16* __restrict__ w_b, const __nv_bfloat16* __restrict__ w_v,
    const __nv_bfloat16* __restrict__ w_a, const __nv_bfloat16* __restrict__ w_u,
    int N, int E, int chunk, int NB, int nbins, uint32_t magic)
{
    extern __shared__ __align__(1024) uint8_t smem[];
    asm volatile("griddepcontrol.launch_dependents;");

    const int warp = threadIdx.x >> 5, lane = threadIdx.x & 31;

    if (warp >= K1_GW) {
        const int tid = threadIdx.x - K1_GW * 32;
        if (blockIdx.x == 0 && tid < 32)
            g_T[(size_t)N * 32 + tid] = make_uint4(0xff80ff80u, 0xff80ff80u, 0u, 0u);
        int* hist = reinterpret_cast<int*>(smem + K1_WBYTES);
        int* loff = hist + MAXBINS;
        int* gbase = loff + MAXBINS;
        uint2* sorted = reinterpret_cast<uint2*>(smem + K1_WBYTES + 3 * MAXBINS * 4);
        for (int beg = blockIdx.x * chunk; beg < E; beg += gridDim.x * chunk) {
            const int end = min(E, beg + chunk);
            int d[P1_EPT]; uint32_t rec[P1_EPT]; int rk[P1_EPT]; int bn[P1_EPT];
            #pragma unroll
            for (int i = 0; i < P1_EPT; i++) {
                int e = beg + i * 256 + tid;
                d[i] = -1;
                if (e < end) {
                    d[i] = __ldg(dst + e);
                    uint32_t s = (uint32_t)__ldg(src + e);
                    uint32_t ev = (uint32_t)__ldg(reinterpret_cast<const unsigned short*>(e_attr) + e);
                    rec[i] = (ev << 16) | s;
                }
            }
            hist[tid] = 0;
            p1_bar();
            #pragma unroll
            for (int i = 0; i < P1_EPT; i++) {
                if (d[i] >= 0) {
                    bn[i] = (int)(((uint64_t)(uint32_t)d[i] * magic) >> 24);
                    rk[i] = atomicAdd(&hist[bn[i]], 1);
                }
            }
            p1_bar();
            {
                int h = hist[tid];
                if (tid < nbins && h > 0) gbase[tid] = atomicAdd(&g_bin_cnt[tid], h);
                if (tid < 32) {
                    int v[8]; int sum = 0;
                    #pragma unroll
                    for (int i = 0; i < 8; i++) { v[i] = hist[lane * 8 + i]; sum += v[i]; }
                    int inc = sum;
                    #pragma unroll
                    for (int o = 1; o < 32; o <<= 1) { int t = __shfl_up_sync(0xffffffffu, inc, o); if (lane >= o) inc += t; }
                    int run = inc - sum;
                    #pragma unroll
                    for (int i = 0; i < 8; i++) { loff[lane * 8 + i] = run; run += v[i]; }
                }
            }
            p1_bar();
            #pragma unroll
            for (int i = 0; i < P1_EPT; i++) {
                if (d[i] >= 0) sorted[loff[bn[i]] + rk[i]] = make_uint2(rec[i], (uint32_t)d[i]);
            }
            p1_bar();
            const int cnt = end - beg;
            for (int i = tid; i < cnt; i += 256) {
                uint2 r = sorted[i];
                int b = (int)(((uint64_t)r.y * magic) >> 24);
                int pos = gbase[b] + (i - loff[b]);
                if (pos < BINCAP) {
                    g_bins[b * BINCAP + pos] = make_uint2(r.x, r.y - (uint32_t)(b * NB));
                } else {
                    int p = atomicAdd(&g_ovf_cnt, 2);
                    g_ovf[p] = (int)r.y; g_ovf[p + 1] = (int)r.x;
                }
            }
            p1_bar();
        }
        return;
    }

    if (blockIdx.x < 4 && threadIdx.x < 128) {
        const char* pw = reinterpret_cast<const char*>((blockIdx.x & 2) ? w_u : w_a) + (blockIdx.x & 1) * 16384 + threadIdx.x * 128;
        asm volatile("prefetch.global.L2 [%0];" :: "l"(pw));
    }
    const int q = lane & 3;
    const int wg = warp >> 2;
    const int n_tasks = ((N + 63) >> 6) * 2;
    const uint32_t sbase = (uint32_t)__cvta_generic_to_shared(smem);
    const uint32_t xbase = sbase + 65536;
    bool w_staged = false;
    int t_beg = (int)(((long long)n_tasks * blockIdx.x) / gridDim.x);
    const int t_end = (int)(((long long)n_tasks * (blockIdx.x + 1)) / gridDim.x);
    while (t_beg < t_end) {
        const int tile0 = t_beg >> 1;
        const int t_stop = min(t_end, (tile0 + 2) << 1);
        stage_x_tile(xbase, x, tile0 * 64, N, threadIdx.x, K1_GW * 32);
        if (((t_stop - 1) >> 1) > tile0) stage_x_tile(xbase + 16384, x, tile0 * 64 + 64, N, threadIdx.x, K1_GW * 32);
        if (!w_staged) {
            stage_weight(sbase, w_b, 0, threadIdx.x, K1_GW * 32);
            stage_weight(sbase, w_v, 1, threadIdx.x, K1_GW * 32);
            w_staged = true;
        }
        asm volatile("cp.async.wait_all;" ::: "memory");
        asm volatile("fence.proxy.async.shared::cta;" ::: "memory");
        asm volatile("bar.sync 2, %0;" :: "n"(K1_GW * 32) : "memory");
        for (int task = t_beg + wg; task < t_stop; task += K1_GW / 4) {
            const int tile = task >> 1, hf = task & 1;
            const uint32_t baddr = sbase + hf * 1024;
            const uint64_t descb = (uint64_t)((baddr & 0x3FFFF) >> 4) | ((uint64_t)(2048 >> 4) << 16) |
                                   ((uint64_t)(4096 >> 4) << 32) | ((uint64_t)1 << 62);
            const uint32_t aaddr = xbase + (tile - tile0) * 16384;
            const uint64_t desca = (uint64_t)((aaddr & 0x3FFFF) >> 4) | ((uint64_t)1 << 16) |
                                   ((uint64_t)(1024 >> 4) << 32) | ((uint64_t)1 << 62);
            float d[64];
            asm volatile("wgmma.fence.sync.aligned;" ::: "memory");
            #pragma unroll
            for (int ks = 0; ks < 8; ks++) {
                wgmma_m64n128k16(d, desca + (uint64_t)(((ks >> 2) * 8192 + (ks & 3) * 32) >> 4),
                                 descb + (uint64_t)(ks * (8192 >> 4)), ks > 0 ? 1 : 0);
            }
            asm volatile("wgmma.commit_group.sync.aligned;" ::: "memory");
            asm volatile("wgmma.wait_group.sync.aligned 0;" ::: "memory");
            const int r0 = tile * 64 + (warp & 3) * 16 + (lane >> 2);
            #pragma unroll
            for (int mm = 0; mm < 4; mm++) {
                const int j0 = 2 * mm, j1 = 2 * mm + 1, j2 = 8 + 2 * mm, j3 = 9 + 2 * mm;
                uint4 o0 = make_uint4(pack_bf16(d[4 * j0], d[4 * j0 + 1]), pack_bf16(d[4 * j1], d[4 * j1 + 1]),
                                      pack_bf16(d[4 * j2], d[4 * j2 + 1]), pack_bf16(d[4 * j3], d[4 * j3 + 1]));
                uint4 o1 = make_uint4(pack_bf16(d[4 * j0 + 2], d[4 * j0 + 3]), pack_bf16(d[4 * j1 + 2], d[4 * j1 + 3]),
                                      pack_bf16(d[4 * j2 + 2], d[4 * j2 + 3]), pack_bf16(d[4 * j3 + 2], d[4 * j3 + 3]));
                const int m = 4 * hf + mm;
                if (r0 < N) g_T[(size_t)r0 * 32 + 4 * m + q] = o0;
                if (r0 + 8 < N) g_T[(size_t)(r0 + 8) * 32 + 4 * m + q] = o1;
            }
        }
        t_beg = t_stop;
        if (t_beg < t_end) asm volatile("bar.sync 2, %0;" :: "n"(K1_GW * 32) : "memory");
    }
}

__device__ __forceinline__ void edge_accum(const uint4 v, const float e, const float a[4], const float cc[4],
                                           float num[4], float den[4]) {
    float y0 = fmaf(bf_lo(v.x), -LOG2E, fmaf(e, cc[0], a[0]));
    float y1 = fmaf(bf_hi(v.x), -LOG2E, fmaf(e, cc[1], a[1]));
    float y2 = fmaf(bf_lo(v.y), -LOG2E, fmaf(e, cc[2], a[2]));
    float y3 = fmaf(bf_hi(v.y), -LOG2E, fmaf(e, cc[3], a[3]));
    float s0 = rcp_approx(1.f + ex2_approx(y0));
    float s1 = rcp_approx(1.f + ex2_approx(y1));
    float s2 = rcp_approx(1.f + ex2_approx(y2));
    float s3 = rcp_approx(1.f + ex2_approx(y3));
    den[0] += s0; den[1] += s1; den[2] += s2; den[3] += s3;
    num[0] = fmaf(s0, bf_lo(v.z), num[0]);
    num[1] = fmaf(s1, bf_hi(v.z), num[1]);
    num[2] = fmaf(s2, bf_lo(v.w), num[2]);
    num[3] = fmaf(s3, bf_hi(v.w), num[3]);
}

#define K2_THREADS 1024
#define K2_D 2
#define K2_GS 2
#define K2_RPT ((BINCAP + K2_THREADS - 1) / K2_THREADS)
#define K2_NW (K2_THREADS / 32)
#define SORT_WORDS (BINCAP + 4 * MAXNB)
#define K2_OFF_W 0
#define K2_OFF_X 65536
#define K2_OFF_A (K2_OFF_X + 32768)
#define K2_OFF_U (K2_OFF_A + MAXNB * 256)
#define K2_OFF_PART (K2_OFF_U + MAXNB * 256)
#define K2_OFF_SORT (K2_OFF_PART + K2_NW * 1024)
#define K2_OFF_HIST (K2_OFF_SORT + SORT_WORDS * 4)
#define K2_OFF_OFF (K2_OFF_HIST + MAXNB * 4)
#define K2_DYN_SMEM (K2_OFF_OFF + (MAXNB + 4) * 4)
#define K2_ST (K2_THREADS - 512)
#define K2_SRPT ((BINCAP + K2_ST - 1) / K2_ST)

struct Grp { uint4 v[K2_GS]; };

__device__ __forceinline__ const uint4* row_ptr(const char* Tl, uint32_t rec) {
    return reinterpret_cast<const uint4*>(Tl + (size_t)((rec & 0xffffu) * 512u));
}
__device__ __forceinline__ void grp_load(Grp& g, const uint32_t* sp, const char* Tl) {
    const uint2 t = *reinterpret_cast<const uint2*>(sp);
    g.v[0] = __ldg(row_ptr(Tl, t.x));
    g.v[1] = __ldg(row_ptr(Tl, t.y));
}
__device__ __forceinline__ void grp_consume(const Grp& g, const uint32_t* sp, const float a[4], const float cc[4],
                                            float num[4], float den[4]) {
    const uint2 t = *reinterpret_cast<const uint2*>(sp);
    edge_accum(g.v[0], bf_hi(t.x), a, cc, num, den);
    edge_accum(g.v[1], bf_hi(t.y), a, cc, num, den);
}

__device__ __forceinline__ void load_a(const uint8_t* smem, int ln, int lane, float a[4]) {
    const uint2 av = reinterpret_cast<const uint2*>(smem + K2_OFF_A)[ln * 32 + (lane ^ ((ln & 3) << 2))];
    a[0] = -LOG2E * bf_lo(av.x); a[1] = -LOG2E * bf_hi(av.x); a[2] = -LOG2E * bf_lo(av.y); a[3] = -LOG2E * bf_hi(av.y);
}
__device__ __forceinline__ void write_node(const uint8_t* smem, __nv_bfloat16* out, int ln, int n,
                                           int lane, const float num[4], const float den[4]) {
    const uint2 uv = reinterpret_cast<const uint2*>(smem + K2_OFF_U)[ln * 32 + (lane ^ ((ln & 3) << 2))];
    const int r = ln & 63, c16 = (lane >> 2) * 2;
    const uint8_t* xr = smem + K2_OFF_X + (ln >> 6) * 16384 + (c16 >> 3) * 8192 + r * 128 + (lane & 3) * 4;
    const uint32_t x0 = *reinterpret_cast<const uint32_t*>(xr + (((c16 & 7) ^ (r & 7)) << 4));
    const uint32_t x1 = *reinterpret_cast<const uint32_t*>(xr + ((((c16 + 1) & 7) ^ (r & 7)) << 4));
    const float u4[4] = { bf_lo(uv.x), bf_hi(uv.x), bf_lo(uv.y), bf_hi(uv.y) };
    const float x4[4] = { bf_lo(x0), bf_hi(x0), bf_lo(x1), bf_hi(x1) };
    float o[4];
    #pragma unroll
    for (int i = 0; i < 4; i++) {
        float agg = round_bf16(__fdividef(num[i], den[i] + 1e-6f));
        float z = round_bf16(u4[i] + agg);
        float rz = (z > 0.f) ? z : 0.f * z;
        o[i] = x4[i] + rz;
    }
    uint32_t* o32 = reinterpret_cast<uint32_t*>(out) + (size_t)n * 64 + (lane >> 2) * 8 + (lane & 3);
    o32[0] = pack_bf16(o[0], o[1]); o32[4] = pack_bf16(o[2], o[3]);
}

__device__ __noinline__ void slow_path(const uint8_t* smem, __nv_bfloat16* out, int node0, int nn, int ovf_n,
                                       float c0, float c1, float c2, float c3) {
    const uint32_t* s_sorted = reinterpret_cast<const uint32_t*>(smem + K2_OFF_SORT);
    const int* s_off = reinterpret_cast<const int*>(smem + K2_OFF_OFF);
    const int lane = threadIdx.x & 31, warp = threadIdx.x >> 5;
    const float cc[4] = { c0, c1, c2, c3 };
    const char* Tl = reinterpret_cast<const char*>(g_T) + lane * 16;
    for (int ln = warp; ln < nn; ln += K2_NW) {
        float a[4];
        load_a(smem, ln, lane, a);
        float num[4] = {0.f, 0.f, 0.f, 0.f}, den[4] = {0.f, 0.f, 0.f, 0.f};
        for (int i = s_off[ln]; i < s_off[ln + 1]; i++) {
            const uint32_t r = s_sorted[i];
            edge_accum(__ldg(row_ptr(Tl, r)), bf_hi(r), a, cc, num, den);
        }
        const int n = node0 + ln;
        for (int base = 0; base < ovf_n; base += 64) {
            int i2 = base + 2 * lane;
            int od = (i2 < ovf_n) ? g_ovf[i2] : -1;
            uint32_t orec = (i2 < ovf_n) ? (uint32_t)g_ovf[i2 + 1] : 0u;
            unsigned msk = __ballot_sync(0xffffffffu, od == n);
            while (msk) {
                int l = __ffs(msk) - 1; msk &= msk - 1;
                uint32_t r = __shfl_sync(0xffffffffu, orec, l);
                edge_accum(__ldg(row_ptr(Tl, r)), bf_hi(r), a, cc, num, den);
            }
        }
        write_node(smem, out, ln, n, lane, num, den);
    }
}

__global__ void __launch_bounds__(K2_THREADS, 1) k2_kernel(
    const __nv_bfloat16* __restrict__ x, const __nv_bfloat16* __restrict__ w_a, const __nv_bfloat16* __restrict__ w_u,
    const __nv_bfloat16* __restrict__ w_c, __nv_bfloat16* __restrict__ out, int N, int NB)
{
    extern __shared__ __align__(1024) uint8_t smem[];
    float4* s_part = reinterpret_cast<float4*>(smem + K2_OFF_PART);
    uint32_t* s_sorted = reinterpret_cast<uint32_t*>(smem + K2_OFF_SORT);
    int* s_hist = reinterpret_cast<int*>(smem + K2_OFF_HIST);
    int* s_off = reinterpret_cast<int*>(smem + K2_OFF_OFF);

    const int tid = threadIdx.x;
    const int lane = tid & 31, warp = tid >> 5;
    const int bin = blockIdx.x;
    const int node0 = bin * NB;
    const int nn = min(NB, N - node0);
    const uint32_t sb = (uint32_t)__cvta_generic_to_shared(smem);

    s_part[warp * 64 + lane] = make_float4(0.f, 0.f, 0.f, 0.f);
    s_part[warp * 64 + 32 + lane] = make_float4(0.f, 0.f, 0.f, 0.f);
    int ovf_n = 0;
    if (warp < 16) {
        stage_x_tile(sb + K2_OFF_X, x, node0, N, tid, 512);
        if (nn > 64) stage_x_tile(sb + K2_OFF_X + 16384, x, node0 + 64, N, tid, 512);
        stage_weight(sb + K2_OFF_W, w_a, 0, tid, 512);
        stage_weight(sb + K2_OFF_W, w_u, 1, tid, 512);
        asm volatile("cp.async.wait_all;" ::: "memory");
        asm volatile("fence.proxy.async.shared::cta;" ::: "memory");
        asm volatile("bar.sync 2, 512;" ::: "memory");
        const int wg = warp >> 2, tile = wg >> 1, mtx = wg & 1;
        if (tile * 64 < nn) {
            const uint32_t aaddr = sb + K2_OFF_X + tile * 16384;
            const uint64_t desca = (uint64_t)((aaddr & 0x3FFFF) >> 4) | ((uint64_t)1 << 16) |
                                   ((uint64_t)(1024 >> 4) << 32) | ((uint64_t)1 << 62);
            uint2* dst = reinterpret_cast<uint2*>(smem + (mtx ? K2_OFF_U : K2_OFF_A));
            const int r0 = tile * 64 + (warp & 3) * 16 + (lane >> 2);
            const int sw = (r0 & 3) << 2;
            #pragma unroll 1
            for (int hf = 0; hf < 2; hf++) {
                const uint32_t baddr = sb + K2_OFF_W + (mtx * 2 + hf) * 1024;
                const uint64_t descb = (uint64_t)((baddr & 0x3FFFF) >> 4) | ((uint64_t)(2048 >> 4) << 16) |
                                       ((uint64_t)(4096 >> 4) << 32) | ((uint64_t)1 << 62);
                float d[32];
                asm volatile("wgmma.fence.sync.aligned;" ::: "memory");
                #pragma unroll
                for (int ks = 0; ks < 8; ks++) {
                    wgmma_m64n64k16(d, desca + (uint64_t)(((ks >> 2) * 8192 + (ks & 3) * 32) >> 4),
                                    descb + (uint64_t)(ks * (8192 >> 4)), ks > 0 ? 1 : 0);
                }
                asm volatile("wgmma.commit_group.sync.aligned;" ::: "memory");
                asm volatile("wgmma.wait_group.sync.aligned 0;" ::: "memory");
                #pragma unroll
                for (int mm = 0; mm < 4; mm++) {
                    const int j0 = 2 * mm, j1 = 2 * mm + 1;
                    const int slot = (4 * (4 * hf + mm) + (lane & 3)) ^ sw;
                    dst[r0 * 32 + slot] = make_uint2(pack_bf16(d[4 * j0], d[4 * j0 + 1]), pack_bf16(d[4 * j1], d[4 * j1 + 1]));
                    dst[(r0 + 8) * 32 + slot] = make_uint2(pack_bf16(d[4 * j0 + 2], d[4 * j0 + 3]), pack_bf16(d[4 * j1 + 2], d[4 * j1 + 3]));
                }
            }
        }
        asm volatile("griddepcontrol.wait;" ::: "memory");
        ovf_n = g_ovf_cnt;
    } else {
        const int st = tid - 512;
        if (st < MAXNB) s_hist[st] = 0;
        for (int i = st; i < SORT_WORDS; i += K2_ST) s_sorted[i] = (uint32_t)N;
        asm volatile("bar.sync 1, %0;" :: "n"(K2_ST) : "memory");
        asm volatile("griddepcontrol.wait;" ::: "memory");
        uint2 r[K2_SRPT]; int rk[K2_SRPT];
        const int cnt = min(g_bin_cnt[bin], BINCAP);
        ovf_n = g_ovf_cnt;
        #pragma unroll
        for (int i = 0; i < K2_SRPT; i++) {
            int idx = i * K2_ST + st;
            if (idx < cnt) r[i] = g_bins[bin * BINCAP + idx];
        }
        #pragma unroll
        for (int i = 0; i < K2_SRPT; i++) {
            int idx = i * K2_ST + st;
            if (idx < cnt) rk[i] = atomicAdd(&s_hist[r[i].y], 1);
        }
        asm volatile("bar.sync 1, %0;" :: "n"(K2_ST) : "memory");
        if (warp == 16) {
            int v[4]; int sum = 0;
            #pragma unroll
            for (int i = 0; i < 4; i++) { v[i] = (s_hist[lane * 4 + i] + K2_GS - 1) & ~(K2_GS - 1); sum += v[i]; }
            int inc = sum;
            #pragma unroll
            for (int o = 1; o < 32; o <<= 1) { int t = __shfl_up_sync(0xffffffffu, inc, o); if (lane >= o) inc += t; }
            int run = inc - sum;
            #pragma unroll
            for (int i = 0; i < 4; i++) { s_off[lane * 4 + i] = run; run += v[i]; }
            if (lane == 31) s_off[MAXNB] = run;
        }
        if (st == 32) g_bin_cnt[bin] = 0;
        asm volatile("bar.sync 1, %0;" :: "n"(K2_ST) : "memory");
        #pragma unroll
        for (int i = 0; i < K2_SRPT; i++) {
            int idx = i * K2_ST + st;
            if (idx < cnt) s_sorted[s_off[r[i].y] + rk[i]] = r[i].x;
        }
    }
    const int fw = (lane >> 2) * 8 + (lane & 3);
    const uint2 wc = make_uint2(__ldg(reinterpret_cast<const uint32_t*>(w_c) + fw), __ldg(reinterpret_cast<const uint32_t*>(w_c) + fw + 4));
    float cc[4] = { -LOG2E * bf_lo(wc.x), -LOG2E * bf_hi(wc.x), -LOG2E * bf_lo(wc.y), -LOG2E * bf_hi(wc.y) };
    __syncthreads();

    if (ovf_n != 0) {
        slow_path(smem, out, node0, nn, ovf_n, cc[0], cc[1], cc[2], cc[3]);
        __syncthreads();
        if (tid == 0) {
            __threadfence();
            int t = atomicAdd(&g_done, 1);
            if (t == (int)gridDim.x - 1) { g_done = 0; __threadfence(); g_ovf_cnt = 0; }
        }
        return;
    }

    const char* Tl = reinterpret_cast<const char*>(g_T) + lane * 16;
    const int G = s_off[MAXNB] / K2_GS;
    int g = (G * warp) / K2_NW;
    const int g1 = (G * (warp + 1)) / K2_NW;
    int ln;
    {
        int c_lo = 0;
        #pragma unroll
        for (int i = 0; i < 4; i++) {
            int node = i * 32 + lane;
            int o = (node < nn) ? s_off[node] : 0x7fffffff;
            c_lo += __popc(__ballot_sync(0xffffffffu, o < g * K2_GS));
        }
        ln = c_lo;
    }
    bool head = ln > 0;
    if (head) ln--;
    float a[4], num[4] = {0.f, 0.f, 0.f, 0.f}, den[4] = {0.f, 0.f, 0.f, 0.f};
    int node_end;

    auto load_node = [&]() {
        load_a(smem, ln, lane, a);
        node_end = s_off[ln + 1] / K2_GS;
    };
    auto finish_node = [&]() { write_node(smem, out, ln, node0 + ln, lane, num, den); };
    auto close_node = [&]() {
        if (head) {
            s_part[warp * 64 + lane] = make_float4(num[0], num[1], num[2], num[3]);
            s_part[warp * 64 + 32 + lane] = make_float4(den[0], den[1], den[2], den[3]);
            head = false;
        } else {
            finish_node();
        }
        #pragma unroll
        for (int i = 0; i < 4; i++) { num[i] = 0.f; den[i] = 0.f; }
    };

    bool tail = false;
    if (g < g1 || warp == K2_NW - 1) {
        load_node();
        Grp b[K2_D];
        #pragma unroll
        for (int d = 0; d < K2_D; d++)
            if (g + d < g1) grp_load(b[d], s_sorted + K2_GS * (g + d), Tl);
        while (g < g1) {
            #pragma unroll
            for (int d = 0; d < K2_D; d++) {
                if (g < g1) {
                    while (g == node_end) { close_node(); ln++; load_node(); }
                    grp_consume(b[d], s_sorted + K2_GS * g, a, cc, num, den);
                    if (g + K2_D < g1) grp_load(b[d], s_sorted + K2_GS * (g + K2_D), Tl);
                    g++;
                }
            }
        }
        if (warp == K2_NW - 1) {
            while (true) { close_node(); ln++; if (ln >= nn) break; load_node(); }
        } else if (node_end == g1 || head) {
            close_node();
        } else {
            tail = true;
        }
    }
    __syncthreads();
    if (tail) {
        for (int w2 = warp + 1; w2 < K2_NW && (G * w2) / K2_NW < node_end; w2++) {
            const float4 pn = s_part[w2 * 64 + lane], pd = s_part[w2 * 64 + 32 + lane];
            num[0] += pn.x; num[1] += pn.y; num[2] += pn.z; num[3] += pn.w;
            den[0] += pd.x; den[1] += pd.y; den[2] += pd.z; den[3] += pd.w;
        }
        finish_node();
    }
}

extern "C" void kernel_launch(void* const* d_in, const int* in_sizes, int n_in,
                              void* d_out, int out_size) {
    const __nv_bfloat16* x      = (const __nv_bfloat16*)d_in[0];
    const __nv_bfloat16* e_attr = (const __nv_bfloat16*)d_in[1];
    const int* src = (const int*)d_in[2];
    const int* dst = (const int*)d_in[3];
    const __nv_bfloat16* w_a = (const __nv_bfloat16*)d_in[4];
    const __nv_bfloat16* w_b = (const __nv_bfloat16*)d_in[5];
    const __nv_bfloat16* w_c = (const __nv_bfloat16*)d_in[6];
    const __nv_bfloat16* w_u = (const __nv_bfloat16*)d_in[7];
    const __nv_bfloat16* w_v = (const __nv_bfloat16*)d_in[8];
    __nv_bfloat16* out = (__nv_bfloat16*)d_out;
    const int N = in_sizes[0] / D_FEAT;
    const int E = in_sizes[2];
    if (N > MAX_N || 2 * E > MAX_E || N <= 0) return;

    static int num_sms = 0;
    if (num_sms == 0) {
        int dev = 0;
        cudaGetDevice(&dev);
        cudaDeviceGetAttribute(&num_sms, cudaDevAttrMultiProcessorCount, dev);
        if (num_sms <= 0 || num_sms > MAXBINS) num_sms = 132;
        cudaFuncSetAttribute(k1_kernel, cudaFuncAttributeMaxDynamicSharedMemorySize, K1_SMEM);
        cudaFuncSetAttribute(k2_kernel, cudaFuncAttributeMaxDynamicSharedMemorySize, K2_DYN_SMEM);
    }
    cudaStream_t st = cudaStreamPerThread;
    int NB = (N + num_sms - 1) / num_sms;
    if (NB > MAXNB) NB = MAXNB;
    const int nbins = (N + NB - 1) / NB;
    const uint32_t magic = (uint32_t)(((1u << 24) + NB - 1) / NB);
    const int P = num_sms;
    int chunk = (E + P - 1) / P;
    if (chunk > P1_CHUNK) chunk = P1_CHUNK;
    if (chunk < 1) chunk = 1;
    k1_kernel<<<P, K1_THREADS, K1_SMEM, st>>>(x, e_attr, src, dst, w_b, w_v, w_a, w_u, N, E, chunk, NB, nbins, magic);

    cudaLaunchConfig_t cfg = {};
    cfg.gridDim = dim3(nbins);
    cfg.blockDim = dim3(K2_THREADS);
    cfg.dynamicSmemBytes = K2_DYN_SMEM;
    cfg.stream = st;
    cudaLaunchAttribute at[1];
    at[0].id = cudaLaunchAttributeProgrammaticStreamSerialization;
    at[0].val.programmaticStreamSerializationAllowed = 1;
    cfg.attrs = at; cfg.numAttrs = 1;
    cudaLaunchKernelEx(&cfg, k2_kernel, x, w_a, w_u, w_c, out, N, NB);
}
```

```cpp
#include <cuda_runtime.h>
#include <cuda_bf16.h>
#include <stdint.h>

#define D_FEAT 128
#define MAX_N 16384
#define MAX_E (1 << 20)
#define LOG2E 1.4426950408889634f

#define MAXBINS 256
#define MAXNB 128
#define BINCAP 3072
__device__ uint4 g_T[(MAX_N + 1) * 32];
#define MAXP 144
#define SLOTCAP 48
__device__ int g_cnt[MAXBINS * MAXP];
__device__ uint2 g_bins[MAXBINS * MAXP * SLOTCAP];
__device__ int g_ovf[MAX_E];
__device__ int g_ovf_cnt;
__device__ int g_done;

__device__ __forceinline__ float ex2_approx(float x) {
    float y; asm("ex2.approx.ftz.f32 %0, %1;" : "=f"(y) : "f"(x)); return y;
}
__device__ __forceinline__ float rcp_approx(float x) {
    float y; asm("rcp.approx.ftz.f32 %0, %1;" : "=f"(y) : "f"(x)); return y;
}
__device__ __forceinline__ uint32_t pack_bf16(float lo, float hi) {
    __nv_bfloat162 t = __floats2bfloat162_rn(lo, hi);
    return *reinterpret_cast<uint32_t*>(&t);
}
__device__ __forceinline__ float bf_lo(uint32_t v) { return __uint_as_float(v << 16); }
__device__ __forceinline__ float bf_hi(uint32_t v) { return __uint_as_float(v & 0xffff0000u); }
__device__ __forceinline__ float round_bf16(float x) { return __bfloat162float(__float2bfloat16_rn(x)); }

__device__ __forceinline__ void mma_bf16(float c[4], uint32_t a0, uint32_t a1, uint32_t a2, uint32_t a3,
                                         uint32_t b0, uint32_t b1) {
    asm volatile("mma.sync.aligned.m16n8k16.row.col.f32.bf16.bf16.f32 "
                 "{%0,%1,%2,%3}, {%4,%5,%6,%7}, {%8,%9}, {%0,%1,%2,%3};"
                 : "+f"(c[0]), "+f"(c[1]), "+f"(c[2]), "+f"(c[3])
                 : "r"(a0), "r"(a1), "r"(a2), "r"(a3), "r"(b0), "r"(b1));
}
__device__ __forceinline__ void ldmatrix_x4_trans(uint32_t& r0, uint32_t& r1, uint32_t& r2, uint32_t& r3, uint32_t addr) {
    asm volatile("ldmatrix.sync.aligned.m8n8.x4.trans.shared.b16 {%0,%1,%2,%3}, [%4];"
                 : "=r"(r0), "=r"(r1), "=r"(r2), "=r"(r3) : "r"(addr));
}

__device__ __forceinline__ void cp_async16(uint32_t saddr, const void* g) {
    asm volatile("cp.async.cg.shared.global [%0], [%1], 16;" :: "r"(saddr), "l"(g) : "memory");
}
__device__ __forceinline__ void cp_async16_zfill(uint32_t saddr, const void* g, int src_size) {
    asm volatile("cp.async.cg.shared.global [%0], [%1], 16, %2;" :: "r"(saddr), "l"(g), "r"(src_size) : "memory");
}
__device__ __forceinline__ void stage_weight(uint32_t sdst, const __nv_bfloat16* w, int mtx, int tid, int nthreads) {
    const uint4* W = reinterpret_cast<const uint4*>(w);
    for (int u = tid; u < 2048; u += nthreads) {
        int k = u >> 4, c16 = u & 15;
        int kg = k >> 3, rr = k & 7;
        int h = mtx * 2 + (c16 >> 3);
        cp_async16(sdst + kg * 4096 + h * 1024 + rr * 128 + (((c16 & 7) ^ rr) << 4), W + u);
    }
}
__device__ __forceinline__ void stage_x_tile(uint32_t sdst, const __nv_bfloat16* x, int row0, int N, int tid, int nthreads) {
    const uint4* X = reinterpret_cast<const uint4*>(x);
    for (int u = tid; u < 1024; u += nthreads) {
        int r = u >> 4, c16 = u & 15;
        int gr = row0 + r;
        bool ok = gr < N;
        cp_async16_zfill(sdst + (c16 >> 3) * 8192 + r * 128 + (((c16 & 7) ^ (r & 7)) << 4),
                         X + (size_t)(ok ? gr : 0) * 16 + c16, ok ? 16 : 0);
    }
}

__device__ __forceinline__ void wgmma_m64n128k16(float d[64], uint64_t desc_a, uint64_t desc_b, int scale_d) {
    asm volatile("{\n.reg .pred p;\nsetp.ne.b32 p, %66, 0;\n"
                 "wgmma.mma_async.sync.aligned.m64n128k16.f32.bf16.bf16 {%0,%1,%2,%3,%4,%5,%6,%7,%8,%9,%10,%11,%12,%13,%14,%15,%16,%17,%18,%19,%20,%21,%22,%23,%24,%25,%26,%27,%28,%29,%30,%31,%32,%33,%34,%35,%36,%37,%38,%39,%40,%41,%42,%43,%44,%45,%46,%47,%48,%49,%50,%51,%52,%53,%54,%55,%56,%57,%58,%59,%60,%61,%62,%63}, %64, %65, p, 1, 1, 0, 1;\n}"
                 : "+f"(d[0]),"+f"(d[1]),"+f"(d[2]),"+f"(d[3]),"+f"(d[4]),"+f"(d[5]),"+f"(d[6]),"+f"(d[7]),"+f"(d[8]),"+f"(d[9]),"+f"(d[10]),"+f"(d[11]),"+f"(d[12]),"+f"(d[13]),"+f"(d[14]),"+f"(d[15]),"+f"(d[16]),"+f"(d[17]),"+f"(d[18]),"+f"(d[19]),"+f"(d[20]),"+f"(d[21]),"+f"(d[22]),"+f"(d[23]),"+f"(d[24]),"+f"(d[25]),"+f"(d[26]),"+f"(d[27]),"+f"(d[28]),"+f"(d[29]),"+f"(d[30]),"+f"(d[31]),"+f"(d[32]),"+f"(d[33]),"+f"(d[34]),"+f"(d[35]),"+f"(d[36]),"+f"(d[37]),"+f"(d[38]),"+f"(d[39]),"+f"(d[40]),"+f"(d[41]),"+f"(d[42]),"+f"(d[43]),"+f"(d[44]),"+f"(d[45]),"+f"(d[46]),"+f"(d[47]),"+f"(d[48]),"+f"(d[49]),"+f"(d[50]),"+f"(d[51]),"+f"(d[52]),"+f"(d[53]),"+f"(d[54]),"+f"(d[55]),"+f"(d[56]),"+f"(d[57]),"+f"(d[58]),"+f"(d[59]),"+f"(d[60]),"+f"(d[61]),"+f"(d[62]),"+f"(d[63])
                 : "l"(desc_a), "l"(desc_b), "r"(scale_d));
}

__device__ __forceinline__ void wgmma_m64n64k16(float d[32], uint64_t desc_a, uint64_t desc_b, int scale_d) {
    asm volatile("{\n.reg .pred p;\nsetp.ne.b32 p, %34, 0;\n"
                 "wgmma.mma_async.sync.aligned.m64n64k16.f32.bf16.bf16 {%0,%1,%2,%3,%4,%5,%6,%7,%8,%9,%10,%11,%12,%13,%14,%15,%16,%17,%18,%19,%20,%21,%22,%23,%24,%25,%26,%27,%28,%29,%30,%31}, %32, %33, p, 1, 1, 0, 1;\n}"
                 : "+f"(d[0]),"+f"(d[1]),"+f"(d[2]),"+f"(d[3]),"+f"(d[4]),"+f"(d[5]),"+f"(d[6]),"+f"(d[7]),"+f"(d[8]),"+f"(d[9]),"+f"(d[10]),"+f"(d[11]),"+f"(d[12]),"+f"(d[13]),"+f"(d[14]),"+f"(d[15]),"+f"(d[16]),"+f"(d[17]),"+f"(d[18]),"+f"(d[19]),"+f"(d[20]),"+f"(d[21]),"+f"(d[22]),"+f"(d[23]),"+f"(d[24]),"+f"(d[25]),"+f"(d[26]),"+f"(d[27]),"+f"(d[28]),"+f"(d[29]),"+f"(d[30]),"+f"(d[31])
                 : "l"(desc_a), "l"(desc_b), "r"(scale_d));
}

#define K1_GW 12
#define K1_THREADS ((K1_GW + 8) * 32)
#define P1_EPT 10
#define P1_CHUNK (256 * P1_EPT)
#define K1_WBYTES (65536 + 2 * 16384)
#define K1_SMEM (K1_WBYTES + MAXBINS * 4)

__device__ __forceinline__ void p1_bar() { asm volatile("bar.sync 1, 256;" ::: "memory"); }

__global__ void __launch_bounds__(K1_THREADS, 1) k1_kernel(
    const __nv_bfloat16* __restrict__ x, const __nv_bfloat16* __restrict__ e_attr,
    const int* __restrict__ src, const int* __restrict__ dst,
    const __nv_bfloat16* __restrict__ w_b, const __nv_bfloat16* __restrict__ w_v,
    const __nv_bfloat16* __restrict__ w_a, const __nv_bfloat16* __restrict__ w_u,
    int N, int E, int chunk, int NB, int nbins, uint32_t magic)
{
    extern __shared__ __align__(1024) uint8_t smem[];
    asm volatile("griddepcontrol.launch_dependents;");

    const int warp = threadIdx.x >> 5, lane = threadIdx.x & 31;

    if (warp >= K1_GW) {
        const int tid = threadIdx.x - K1_GW * 32;
        if (blockIdx.x == 0 && tid < 32)
            g_T[(size_t)N * 32 + tid] = make_uint4(0xff80ff80u, 0xff80ff80u, 0u, 0u);
        int* hist = reinterpret_cast<int*>(smem + K1_WBYTES);
        const int P = gridDim.x;
        uint2* mybins = g_bins + (size_t)blockIdx.x * SLOTCAP;
        bool first = true;
        for (int beg = blockIdx.x * chunk; beg < E; beg += P * chunk) {
            const int end = min(E, beg + chunk);
            int d[P1_EPT]; uint32_t rec[P1_EPT];
            #pragma unroll
            for (int i = 0; i < P1_EPT; i++) {
                int e = beg + i * 256 + tid;
                d[i] = -1;
                if (e < end) {
                    d[i] = __ldg(dst + e);
                    uint32_t s = (uint32_t)__ldg(src + e);
                    uint32_t ev = (uint32_t)__ldg(reinterpret_cast<const unsigned short*>(e_attr) + e);
                    rec[i] = (ev << 16) | s;
                }
            }
            if (first) {
                hist[tid] = 0;
                p1_bar();
                first = false;
            }
            #pragma unroll
            for (int i = 0; i < P1_EPT; i++) {
                if (d[i] >= 0) {
                    const int bn = (int)(((uint64_t)(uint32_t)d[i] * magic) >> 24);
                    const int rk = atomicAdd(&hist[bn], 1);
                    if (rk < SLOTCAP) {
                        mybins[(size_t)bn * (P * SLOTCAP) + rk] = make_uint2(rec[i], (uint32_t)(d[i] - bn * NB));
                    } else {
                        int p = atomicAdd(&g_ovf_cnt, 2);
                        g_ovf[p] = d[i]; g_ovf[p + 1] = (int)rec[i];
                    }
                }
            }
        }
        if (first) { hist[tid] = 0; }
        p1_bar();
        if (tid < nbins) g_cnt[tid * P + blockIdx.x] = min(hist[tid], SLOTCAP);
        return;
    }

    if (blockIdx.x < 4 && threadIdx.x < 128) {
        const char* pw = reinterpret_cast<const char*>((blockIdx.x & 2) ? w_u : w_a) + (blockIdx.x & 1) * 16384 + threadIdx.x * 128;
        asm volatile("prefetch.global.L2 [%0];" :: "l"(pw));
    }
    const int q = lane & 3;
    const int wg = warp >> 2;
    const int n_tasks = ((N + 63) >> 6) * 2;
    const uint32_t sbase = (uint32_t)__cvta_generic_to_shared(smem);
    const uint32_t xbase = sbase + 65536;
    bool w_staged = false;
    int t_beg = (int)(((long long)n_tasks * blockIdx.x) / gridDim.x);
    const int t_end = (int)(((long long)n_tasks * (blockIdx.x + 1)) / gridDim.x);
    while (t_beg < t_end) {
        const int tile0 = t_beg >> 1;
        const int t_stop = min(t_end, (tile0 + 2) << 1);
        stage_x_tile(xbase, x, tile0 * 64, N, threadIdx.x, K1_GW * 32);
        if (((t_stop - 1) >> 1) > tile0) stage_x_tile(xbase + 16384, x, tile0 * 64 + 64, N, threadIdx.x, K1_GW * 32);
        if (!w_staged) {
            stage_weight(sbase, w_b, 0, threadIdx.x, K1_GW * 32);
            stage_weight(sbase, w_v, 1, threadIdx.x, K1_GW * 32);
            w_staged = true;
        }
        asm volatile("cp.async.wait_all;" ::: "memory");
        asm volatile("fence.proxy.async.shared::cta;" ::: "memory");
        asm volatile("bar.sync 2, %0;" :: "n"(K1_GW * 32) : "memory");
        for (int task = t_beg + wg; task < t_stop; task += K1_GW / 4) {
            const int tile = task >> 1, hf = task & 1;
            const uint32_t baddr = sbase + hf * 1024;
            const uint64_t descb = (uint64_t)((baddr & 0x3FFFF) >> 4) | ((uint64_t)(2048 >> 4) << 16) |
                                   ((uint64_t)(4096 >> 4) << 32) | ((uint64_t)1 << 62);
            const uint32_t aaddr = xbase + (tile - tile0) * 16384;
            const uint64_t desca = (uint64_t)((aaddr & 0x3FFFF) >> 4) | ((uint64_t)1 << 16) |
                                   ((uint64_t)(1024 >> 4) << 32) | ((uint64_t)1 << 62);
            float d[64];
            asm volatile("wgmma.fence.sync.aligned;" ::: "memory");
            #pragma unroll
            for (int ks = 0; ks < 8; ks++) {
                wgmma_m64n128k16(d, desca + (uint64_t)(((ks >> 2) * 8192 + (ks & 3) * 32) >> 4),
                                 descb + (uint64_t)(ks * (8192 >> 4)), ks > 0 ? 1 : 0);
            }
            asm volatile("wgmma.commit_group.sync.aligned;" ::: "memory");
            asm volatile("wgmma.wait_group.sync.aligned 0;" ::: "memory");
            const int r0 = tile * 64 + (warp & 3) * 16 + (lane >> 2);
            #pragma unroll
            for (int mm = 0; mm < 4; mm++) {
                const int j0 = 2 * mm, j1 = 2 * mm + 1, j2 = 8 + 2 * mm, j3 = 9 + 2 * mm;
                uint4 o0 = make_uint4(pack_bf16(d[4 * j0], d[4 * j0 + 1]), pack_bf16(d[4 * j1], d[4 * j1 + 1]),
                                      pack_bf16(d[4 * j2], d[4 * j2 + 1]), pack_bf16(d[4 * j3], d[4 * j3 + 1]));
                uint4 o1 = make_uint4(pack_bf16(d[4 * j0 + 2], d[4 * j0 + 3]), pack_bf16(d[4 * j1 + 2], d[4 * j1 + 3]),
                                      pack_bf16(d[4 * j2 + 2], d[4 * j2 + 3]), pack_bf16(d[4 * j3 + 2], d[4 * j3 + 3]));
                const int m = 4 * hf + mm;
                if (r0 < N) g_T[(size_t)r0 * 32 + 4 * m + q] = o0;
                if (r0 + 8 < N) g_T[(size_t)(r0 + 8) * 32 + 4 * m + q] = o1;
            }
        }
        t_beg = t_stop;
        if (t_beg < t_end) asm volatile("bar.sync 2, %0;" :: "n"(K1_GW * 32) : "memory");
    }
}

__device__ __forceinline__ void edge_accum(const uint4 v, const float e, const float a[4], const float cc[4],
                                           float num[4], float den[4]) {
    float y0 = fmaf(bf_lo(v.x), -LOG2E, fmaf(e, cc[0], a[0]));
    float y1 = fmaf(bf_hi(v.x), -LOG2E, fmaf(e, cc[1], a[1]));
    float y2 = fmaf(bf_lo(v.y), -LOG2E, fmaf(e, cc[2], a[2]));
    float y3 = fmaf(bf_hi(v.y), -LOG2E, fmaf(e, cc[3], a[3]));
    float s0 = rcp_approx(1.f + ex2_approx(y0));
    float s1 = rcp_approx(1.f + ex2_approx(y1));
    float s2 = rcp_approx(1.f + ex2_approx(y2));
    float s3 = rcp_approx(1.f + ex2_approx(y3));
    den[0] += s0; den[1] += s1; den[2] += s2; den[3] += s3;
    num[0] = fmaf(s0, bf_lo(v.z), num[0]);
    num[1] = fmaf(s1, bf_hi(v.z), num[1]);
    num[2] = fmaf(s2, bf_lo(v.w), num[2]);
    num[3] = fmaf(s3, bf_hi(v.w), num[3]);
}

#define K2_THREADS 1024
#define K2_D 2
#define K2_GS 2
#define K2_RPT ((BINCAP + K2_THREADS - 1) / K2_THREADS)
#define K2_NW (K2_THREADS / 32)
#define SORT_WORDS (BINCAP + 4 * MAXNB)
#define K2_OFF_W 0
#define K2_OFF_X 65536
#define K2_OFF_A (K2_OFF_X + 32768)
#define K2_OFF_U (K2_OFF_A + MAXNB * 256)
#define K2_OFF_PART (K2_OFF_U + MAXNB * 256)
#define K2_OFF_SORT (K2_OFF_PART + K2_NW * 1024)
#define K2_OFF_HIST (K2_OFF_SORT + SORT_WORDS * 4)
#define K2_OFF_OFF (K2_OFF_HIST + MAXNB * 4)
#define K2_XCAP 64
#define K2_OFF_EXTRA (K2_OFF_OFF + (MAXNB + 4) * 4)
#define K2_OFF_MISC (K2_OFF_EXTRA + K2_XCAP * 8)
#define K2_DYN_SMEM (K2_OFF_MISC + 16)
#define K2_RPW (MAXP / 16)
#define K2_ST (K2_THREADS - 512)
#define K2_SRPT ((BINCAP + K2_ST - 1) / K2_ST)

struct Grp { uint4 v[K2_GS]; };

__device__ __forceinline__ const uint4* row_ptr(const char* Tl, uint32_t rec) {
    return reinterpret_cast<const uint4*>(Tl + (size_t)((rec & 0xffffu) * 512u));
}
__device__ __forceinline__ void grp_load(Grp& g, const uint32_t* sp, const char* Tl) {
    const uint2 t = *reinterpret_cast<const uint2*>(sp);
    g.v[0] = __ldg(row_ptr(Tl, t.x));
    g.v[1] = __ldg(row_ptr(Tl, t.y));
}
__device__ __forceinline__ void grp_consume(const Grp& g, const uint32_t* sp, const float a[4], const float cc[4],
                                            float num[4], float den[4]) {
    const uint2 t = *reinterpret_cast<const uint2*>(sp);
    edge_accum(g.v[0], bf_hi(t.x), a, cc, num, den);
    edge_accum(g.v[1], bf_hi(t.y), a, cc, num, den);
}

__device__ __forceinline__ void load_a(const uint8_t* smem, int ln, int lane, float a[4]) {
    const uint2 av = reinterpret_cast<const uint2*>(smem + K2_OFF_A)[ln * 32 + (lane ^ ((ln & 3) << 2))];
    a[0] = -LOG2E * bf_lo(av.x); a[1] = -LOG2E * bf_hi(av.x); a[2] = -LOG2E * bf_lo(av.y); a[3] = -LOG2E * bf_hi(av.y);
}
__device__ __forceinline__ void write_node(const uint8_t* smem, __nv_bfloat16* out, int ln, int n,
                                           int lane, const float num[4], const float den[4]) {
    const uint2 uv = reinterpret_cast<const uint2*>(smem + K2_OFF_U)[ln * 32 + (lane ^ ((ln & 3) << 2))];
    const int r = ln & 63, c16 = (lane >> 2) * 2;
    const uint8_t* xr = smem + K2_OFF_X + (ln >> 6) * 16384 + (c16 >> 3) * 8192 + r * 128 + (lane & 3) * 4;
    const uint32_t x0 = *reinterpret_cast<const uint32_t*>(xr + (((c16 & 7) ^ (r & 7)) << 4));
    const uint32_t x1 = *reinterpret_cast<const uint32_t*>(xr + ((((c16 + 1) & 7) ^ (r & 7)) << 4));
    const float u4[4] = { bf_lo(uv.x), bf_hi(uv.x), bf_lo(uv.y), bf_hi(uv.y) };
    const float x4[4] = { bf_lo(x0), bf_hi(x0), bf_lo(x1), bf_hi(x1) };
    float o[4];
    #pragma unroll
    for (int i = 0; i < 4; i++) {
        float agg = round_bf16(__fdividef(num[i], den[i] + 1e-6f));
        float z = round_bf16(u4[i] + agg);
        float rz = (z > 0.f) ? z : 0.f * z;
        o[i] = x4[i] + rz;
    }
    uint32_t* o32 = reinterpret_cast<uint32_t*>(out) + (size_t)n * 64 + (lane >> 2) * 8 + (lane & 3);
    o32[0] = pack_bf16(o[0], o[1]); o32[4] = pack_bf16(o[2], o[3]);
}

__device__ __noinline__ void slow_path(const uint8_t* smem, __nv_bfloat16* out, int node0, int nn, int ovf_n, int P,
                                       float c0, float c1, float c2, float c3) {
    const int lane = threadIdx.x & 31, warp = threadIdx.x >> 5;
    const float cc[4] = { c0, c1, c2, c3 };
    const char* Tl = reinterpret_cast<const char*>(g_T) + lane * 16;
    for (int ln = warp; ln < nn; ln += K2_NW) {
        float a[4];
        load_a(smem, ln, lane, a);
        float num[4] = {0.f, 0.f, 0.f, 0.f}, den[4] = {0.f, 0.f, 0.f, 0.f};
        for (int c = 0; c < P; c++) {
            const int cnt = g_cnt[blockIdx.x * P + c];
            for (int j0 = 0; j0 < cnt; j0 += 32) {
                uint2 r = make_uint2(0u, 0xffffffffu);
                if (j0 + lane < cnt) r = g_bins[((size_t)blockIdx.x * P + c) * SLOTCAP + j0 + lane];
                unsigned msk = __ballot_sync(0xffffffffu, r.y == (uint32_t)ln);
                while (msk) {
                    int l = __ffs(msk) - 1; msk &= msk - 1;
                    uint32_t rr = __shfl_sync(0xffffffffu, r.x, l);
                    edge_accum(__ldg(row_ptr(Tl, rr)), bf_hi(rr), a, cc, num, den);
                }
            }
        }
        const int n = node0 + ln;
        for (int base = 0; base < ovf_n; base += 64) {
            int i2 = base + 2 * lane;
            int od = (i2 < ovf_n) ? g_ovf[i2] : -1;
            uint32_t orec = (i2 < ovf_n) ? (uint32_t)g_ovf[i2 + 1] : 0u;
            unsigned msk = __ballot_sync(0xffffffffu, od == n);
            while (msk) {
                int l = __ffs(msk) - 1; msk &= msk - 1;
                uint32_t r = __shfl_sync(0xffffffffu, orec, l);
                edge_accum(__ldg(row_ptr(Tl, r)), bf_hi(r), a, cc, num, den);
            }
        }
        write_node(smem, out, ln, n, lane, num, den);
    }
}

__global__ void __launch_bounds__(K2_THREADS, 1) k2_kernel(
    const __nv_bfloat16* __restrict__ x, const __nv_bfloat16* __restrict__ w_a, const __nv_bfloat16* __restrict__ w_u,
    const __nv_bfloat16* __restrict__ w_c, __nv_bfloat16* __restrict__ out, int N, int NB, int P)
{
    extern __shared__ __align__(1024) uint8_t smem[];
    float4* s_part = reinterpret_cast<float4*>(smem + K2_OFF_PART);
    uint32_t* s_sorted = reinterpret_cast<uint32_t*>(smem + K2_OFF_SORT);
    int* s_hist = reinterpret_cast<int*>(smem + K2_OFF_HIST);
    int* s_off = reinterpret_cast<int*>(smem + K2_OFF_OFF);
    uint2* s_extra = reinterpret_cast<uint2*>(smem + K2_OFF_EXTRA);
    int* s_misc = reinterpret_cast<int*>(smem + K2_OFF_MISC);

    const int tid = threadIdx.x;
    const int lane = tid & 31, warp = tid >> 5;
    const int bin = blockIdx.x;
    const int node0 = bin * NB;
    const int nn = min(NB, N - node0);
    const uint32_t sb = (uint32_t)__cvta_generic_to_shared(smem);

    s_part[warp * 64 + lane] = make_float4(0.f, 0.f, 0.f, 0.f);
    s_part[warp * 64 + 32 + lane] = make_float4(0.f, 0.f, 0.f, 0.f);
    int ovf_n = 0;
    if (warp < 16) {
        stage_x_tile(sb + K2_OFF_X, x, node0, N, tid, 512);
        if (nn > 64) stage_x_tile(sb + K2_OFF_X + 16384, x, node0 + 64, N, tid, 512);
        stage_weight(sb + K2_OFF_W, w_a, 0, tid, 512);
        stage_weight(sb + K2_OFF_W, w_u, 1, tid, 512);
        asm volatile("cp.async.wait_all;" ::: "memory");
        asm volatile("fence.proxy.async.shared::cta;" ::: "memory");
        asm volatile("bar.sync 2, 512;" ::: "memory");
        const int wg = warp >> 2, tile = wg >> 1, mtx = wg & 1;
        if (tile * 64 < nn) {
            const uint32_t aaddr = sb + K2_OFF_X + tile * 16384;
            const uint64_t desca = (uint64_t)((aaddr & 0x3FFFF) >> 4) | ((uint64_t)1 << 16) |
                                   ((uint64_t)(1024 >> 4) << 32) | ((uint64_t)1 << 62);
            uint2* dst = reinterpret_cast<uint2*>(smem + (mtx ? K2_OFF_U : K2_OFF_A));
            const int r0 = tile * 64 + (warp & 3) * 16 + (lane >> 2);
            const int sw = (r0 & 3) << 2;
            #pragma unroll 1
            for (int hf = 0; hf < 2; hf++) {
                const uint32_t baddr = sb + K2_OFF_W + (mtx * 2 + hf) * 1024;
                const uint64_t descb = (uint64_t)((baddr & 0x3FFFF) >> 4) | ((uint64_t)(2048 >> 4) << 16) |
                                       ((uint64_t)(4096 >> 4) << 32) | ((uint64_t)1 << 62);
                float d[32];
                asm volatile("wgmma.fence.sync.aligned;" ::: "memory");
                #pragma unroll
                for (int ks = 0; ks < 8; ks++) {
                    wgmma_m64n64k16(d, desca + (uint64_t)(((ks >> 2) * 8192 + (ks & 3) * 32) >> 4),
                                    descb + (uint64_t)(ks * (8192 >> 4)), ks > 0 ? 1 : 0);
                }
                asm volatile("wgmma.commit_group.sync.aligned;" ::: "memory");
                asm volatile("wgmma.wait_group.sync.aligned 0;" ::: "memory");
                #pragma unroll
                for (int mm = 0; mm < 4; mm++) {
                    const int j0 = 2 * mm, j1 = 2 * mm + 1;
                    const int slot = (4 * (4 * hf + mm) + (lane & 3)) ^ sw;
                    dst[r0 * 32 + slot] = make_uint2(pack_bf16(d[4 * j0], d[4 * j0 + 1]), pack_bf16(d[4 * j1], d[4 * j1 + 1]));
                    dst[(r0 + 8) * 32 + slot] = make_uint2(pack_bf16(d[4 * j0 + 2], d[4 * j0 + 3]), pack_bf16(d[4 * j1 + 2], d[4 * j1 + 3]));
                }
            }
        }
        asm volatile("griddepcontrol.wait;" ::: "memory");
        ovf_n = g_ovf_cnt;
    } else {
        const int st = tid - 512, sw = warp - 16;
        if (st < MAXNB) s_hist[st] = 0;
        if (st == MAXNB) { s_misc[0] = 0; s_misc[1] = 0; }
        for (int i = st; i < SORT_WORDS; i += K2_ST) s_sorted[i] = (uint32_t)N;
        asm volatile("bar.sync 1, %0;" :: "n"(K2_ST) : "memory");
        asm volatile("griddepcontrol.wait;" ::: "memory");
        const int c_l = sw + 16 * lane;
        const int cnt_l = (lane < K2_RPW && c_l < P) ? g_cnt[bin * P + c_l] : 0;
        ovf_n = g_ovf_cnt;
        const uint2* rb = g_bins + ((size_t)bin * P + sw) * SLOTCAP + lane;
        uint2 r[K2_RPW]; int rk[K2_RPW];
        #pragma unroll
        for (int i = 0; i < K2_RPW; i++) {
            const int cnt = __shfl_sync(0xffffffffu, cnt_l, i);
            r[i].y = 0xffffffffu;
            if (lane < cnt) r[i] = rb[(size_t)i * (16 * SLOTCAP)];
        }
        if (__any_sync(0xffffffffu, cnt_l > 32)) {
            for (int i = 0; i < K2_RPW; i++) {
                const int cnt = __shfl_sync(0xffffffffu, cnt_l, i);
                if (32 + lane < cnt) {
                    const uint2 rr = rb[(size_t)i * (16 * SLOTCAP) + 32];
                    const int k = atomicAdd(&s_hist[rr.y], 1);
                    const int p = atomicAdd(&s_misc[0], 1);
                    if (p < K2_XCAP) s_extra[p] = make_uint2(rr.x, rr.y | ((uint32_t)k << 16));
                }
            }
        }
        #pragma unroll
        for (int i = 0; i < K2_RPW; i++)
            if (r[i].y != 0xffffffffu) rk[i] = atomicAdd(&s_hist[r[i].y], 1);
        asm volatile("bar.sync 1, %0;" :: "n"(K2_ST) : "memory");
        if (warp == 16) {
            int v[4]; int sum = 0;
            #pragma unroll
            for (int i = 0; i < 4; i++) { v[i] = (s_hist[lane * 4 + i] + K2_GS - 1) & ~(K2_GS - 1); sum += v[i]; }
            int inc = sum;
            #pragma unroll
            for (int o = 1; o < 32; o <<= 1) { int t = __shfl_up_sync(0xffffffffu, inc, o); if (lane >= o) inc += t; }
            int run = inc - sum;
            #pragma unroll
            for (int i = 0; i < 4; i++) { s_off[lane * 4 + i] = run; run += v[i]; }
            if (lane == 31) {
                s_off[MAXNB] = run;
                if (run > SORT_WORDS || s_misc[0] > K2_XCAP) s_misc[1] = 1;
            }
        }
        asm volatile("bar.sync 1, %0;" :: "n"(K2_ST) : "memory");
        if (s_misc[1] == 0) {
            #pragma unroll
            for (int i = 0; i < K2_RPW; i++)
                if (r[i].y != 0xffffffffu) s_sorted[s_off[r[i].y] + rk[i]] = r[i].x;
            if (st < s_misc[0]) {
                const uint2 rr = s_extra[st];
                s_sorted[s_off[rr.y & 0xffffu] + (rr.y >> 16)] = rr.x;
            }
        }
    }
    const int fw = (lane >> 2) * 8 + (lane & 3);
    const uint2 wc = make_uint2(__ldg(reinterpret_cast<const uint32_t*>(w_c) + fw), __ldg(reinterpret_cast<const uint32_t*>(w_c) + fw + 4));
    float cc[4] = { -LOG2E * bf_lo(wc.x), -LOG2E * bf_hi(wc.x), -LOG2E * bf_lo(wc.y), -LOG2E * bf_hi(wc.y) };
    __syncthreads();

    if (ovf_n != 0 || s_misc[1] != 0) {
        slow_path(smem, out, node0, nn, ovf_n, P, cc[0], cc[1], cc[2], cc[3]);
        __syncthreads();
        if (tid == 0 && ovf_n != 0) {
            __threadfence();
            int t = atomicAdd(&g_done, 1);
            if (t == (int)gridDim.x - 1) { g_done = 0; __threadfence(); g_ovf_cnt = 0; }
        }
        return;
    }

    const char* Tl = reinterpret_cast<const char*>(g_T) + lane * 16;
    const int G = s_off[MAXNB] / K2_GS;
    int g = (G * warp) / K2_NW;
    const int g1 = (G * (warp + 1)) / K2_NW;
    int ln;
    {
        int c_lo = 0;
        #pragma unroll
        for (int i = 0; i < 4; i++) {
            int node = i * 32 + lane;
            int o = (node < nn) ? s_off[node] : 0x7fffffff;
            c_lo += __popc(__ballot_sync(0xffffffffu, o < g * K2_GS));
        }
        ln = c_lo;
    }
    bool head = ln > 0;
    if (head) ln--;
    float a[4], num[4] = {0.f, 0.f, 0.f, 0.f}, den[4] = {0.f, 0.f, 0.f, 0.f};
    int node_end;

    auto load_node = [&]() {
        load_a(smem, ln, lane, a);
        node_end = s_off[ln + 1] / K2_GS;
    };
    auto finish_node = [&]() { write_node(smem, out, ln, node0 + ln, lane, num, den); };
    auto close_node = [&]() {
        if (head) {
            s_part[warp * 64 + lane] = make_float4(num[0], num[1], num[2], num[3]);
            s_part[warp * 64 + 32 + lane] = make_float4(den[0], den[1], den[2], den[3]);
            head = false;
        } else {
            finish_node();
        }
        #pragma unroll
        for (int i = 0; i < 4; i++) { num[i] = 0.f; den[i] = 0.f; }
    };

    bool tail = false;
    if (g < g1 || warp == K2_NW - 1) {
        load_node();
        Grp b[K2_D];
        #pragma unroll
        for (int d = 0; d < K2_D; d++)
            if (g + d < g1) grp_load(b[d], s_sorted + K2_GS * (g + d), Tl);
        while (g < g1) {
            #pragma unroll
            for (int d = 0; d < K2_D; d++) {
                if (g < g1) {
                    while (g == node_end) { close_node(); ln++; load_node(); }
                    grp_consume(b[d], s_sorted + K2_GS * g, a, cc, num, den);
                    if (g + K2_D < g1) grp_load(b[d], s_sorted + K2_GS * (g + K2_D), Tl);
                    g++;
                }
            }
        }
        if (warp == K2_NW - 1) {
            while (true) { close_node(); ln++; if (ln >= nn) break; load_node(); }
        } else if (node_end == g1 || head) {
            close_node();
        } else {
            tail = true;
        }
    }
    __syncthreads();
    if (tail) {
        for (int w2 = warp + 1; w2 < K2_NW && (G * w2) / K2_NW < node_end; w2++) {
            const float4 pn = s_part[w2 * 64 + lane], pd = s_part[w2 * 64 + 32 + lane];
            num[0] += pn.x; num[1] += pn.y; num[2] += pn.z; num[3] += pn.w;
            den[0] += pd.x; den[1] += pd.y; den[2] += pd.z; den[3] += pd.w;
        }
        finish_node();
    }
}

extern "C" void kernel_launch(void* const* d_in, const int* in_sizes, int n_in,
                              void* d_out, int out_size) {
    const __nv_bfloat16* x      = (const __nv_bfloat16*)d_in[0];
    const __nv_bfloat16* e_attr = (const __nv_bfloat16*)d_in[1];
    const int* src = (const int*)d_in[2];
    const int* dst = (const int*)d_in[3];
    const __nv_bfloat16* w_a = (const __nv_bfloat16*)d_in[4];
    const __nv_bfloat16* w_b = (const __nv_bfloat16*)d_in[5];
    const __nv_bfloat16* w_c = (const __nv_bfloat16*)d_in[6];
    const __nv_bfloat16* w_u = (const __nv_bfloat16*)d_in[7];
    const __nv_bfloat16* w_v = (const __nv_bfloat16*)d_in[8];
    __nv_bfloat16* out = (__nv_bfloat16*)d_out;
    const int N = in_sizes[0] / D_FEAT;
    const int E = in_sizes[2];
    if (N > MAX_N || 2 * E > MAX_E || N <= 0) return;

    static int num_sms = 0;
    if (num_sms == 0) {
        int dev = 0;
        cudaGetDevice(&dev);
        cudaDeviceGetAttribute(&num_sms, cudaDevAttrMultiProcessorCount, dev);
        if (num_sms <= 0 || num_sms > MAXBINS) num_sms = 132;
        cudaFuncSetAttribute(k1_kernel, cudaFuncAttributeMaxDynamicSharedMemorySize, K1_SMEM);
        cudaFuncSetAttribute(k2_kernel, cudaFuncAttributeMaxDynamicSharedMemorySize, K2_DYN_SMEM);
    }
    cudaStream_t st = cudaStreamPerThread;
    int NB = (N + num_sms - 1) / num_sms;
    if (NB > MAXNB) NB = MAXNB;
    const int nbins = (N + NB - 1) / NB;
    const uint32_t magic = (uint32_t)(((1u << 24) + NB - 1) / NB);
    const int P = num_sms < MAXP ? num_sms : MAXP;
    int chunk = (E + P - 1) / P;
    if (chunk > P1_CHUNK) chunk = P1_CHUNK;
    if (chunk < 1) chunk = 1;
    k1_kernel<<<P, K1_THREADS, K1_SMEM, st>>>(x, e_attr, src, dst, w_b, w_v, w_a, w_u, N, E, chunk, NB, nbins, magic);

    cudaLaunchConfig_t cfg = {};
    cfg.gridDim = dim3(nbins);
    cfg.blockDim = dim3(K2_THREADS);
    cfg.dynamicSmemBytes = K2_DYN_SMEM;
    cfg.stream = st;
    cudaLaunchAttribute at[1];
    at[0].id = cudaLaunchAttributeProgrammaticStreamSerialization;
    at[0].val.programmaticStreamSerializationAllowed = 1;
    cfg.attrs = at; cfg.numAttrs = 1;
    cudaLaunchKernelEx(&cfg, k2_kernel, x, w_a, w_u, w_c, out, N, NB, P);
}
```

```cpp
#include <cuda_runtime.h>
#include <cuda_bf16.h>
#include <stdint.h>

#define D_FEAT 128
#define MAX_N 16384
#define MAX_E (1 << 20)
#define LOG2E 1.4426950408889634f

#define MAXBINS 256
#define MAXNB 128
#define BINCAP 3072
__device__ uint4 g_T[(MAX_N + 1) * 32];
#define CNT_STRIDE 32
__device__ int g_bin_cnt[MAXBINS * CNT_STRIDE];
__device__ uint2 g_bins[MAXBINS * BINCAP];
__device__ int g_ovf[MAX_E];
__device__ int g_ovf_cnt;
__device__ int g_done;

__device__ __forceinline__ float ex2_approx(float x) {
    float y; asm("ex2.approx.ftz.f32 %0, %1;" : "=f"(y) : "f"(x)); return y;
}
__device__ __forceinline__ float rcp_approx(float x) {
    float y; asm("rcp.approx.ftz.f32 %0, %1;" : "=f"(y) : "f"(x)); return y;
}
__device__ __forceinline__ uint32_t pack_bf16(float lo, float hi) {
    __nv_bfloat162 t = __floats2bfloat162_rn(lo, hi);
    return *reinterpret_cast<uint32_t*>(&t);
}
__device__ __forceinline__ float bf_lo(uint32_t v) { return __uint_as_float(v << 16); }
__device__ __forceinline__ float bf_hi(uint32_t v) { return __uint_as_float(v & 0xffff0000u); }
__device__ __forceinline__ float round_bf16(float x) { return __bfloat162float(__float2bfloat16_rn(x)); }

__device__ __forceinline__ void mma_bf16(float c[4], uint32_t a0, uint32_t a1, uint32_t a2, uint32_t a3,
                                         uint32_t b0, uint32_t b1) {
    asm volatile("mma.sync.aligned.m16n8k16.row.col.f32.bf16.bf16.f32 "
                 "{%0,%1,%2,%3}, {%4,%5,%6,%7}, {%8,%9}, {%0,%1,%2,%3};"
                 : "+f"(c[0]), "+f"(c[1]), "+f"(c[2]), "+f"(c[3])
                 : "r"(a0), "r"(a1), "r"(a2), "r"(a3), "r"(b0), "r"(b1));
}
__device__ __forceinline__ void ldmatrix_x4_trans(uint32_t& r0, uint32_t& r1, uint32_t& r2, uint32_t& r3, uint32_t addr) {
    asm volatile("ldmatrix.sync.aligned.m8n8.x4.trans.shared.b16 {%0,%1,%2,%3}, [%4];"
                 : "=r"(r0), "=r"(r1), "=r"(r2), "=r"(r3) : "r"(addr));
}

__device__ __forceinline__ void cp_async16(uint32_t saddr, const void* g) {
    asm volatile("cp.async.cg.shared.global [%0], [%1], 16;" :: "r"(saddr), "l"(g) : "memory");
}
__device__ __forceinline__ void cp_async16_zfill(uint32_t saddr, const void* g, int src_size) {
    asm volatile("cp.async.cg.shared.global [%0], [%1], 16, %2;" :: "r"(saddr), "l"(g), "r"(src_size) : "memory");
}
__device__ __forceinline__ void stage_weight(uint32_t sdst, const __nv_bfloat16* w, int mtx, int tid, int nthreads) {
    const uint4* W = reinterpret_cast<const uint4*>(w);
    for (int u = tid; u < 2048; u += nthreads) {
        int k = u >> 4, c16 = u & 15;
        int kg = k >> 3, rr = k & 7;
        int h = mtx * 2 + (c16 >> 3);
        cp_async16(sdst + kg * 4096 + h * 1024 + rr * 128 + (((c16 & 7) ^ rr) << 4), W + u);
    }
}
__device__ __forceinline__ void stage_x_tile(uint32_t sdst, const __nv_bfloat16* x, int row0, int N, int tid, int nthreads) {
    const uint4* X = reinterpret_cast<const uint4*>(x);
    for (int u = tid; u < 1024; u += nthreads) {
        int r = u >> 4, c16 = u & 15;
        int gr = row0 + r;
        bool ok = gr < N;
        cp_async16_zfill(sdst + (c16 >> 3) * 8192 + r * 128 + (((c16 & 7) ^ (r & 7)) << 4),
                         X + (size_t)(ok ? gr : 0) * 16 + c16, ok ? 16 : 0);
    }
}

__device__ __forceinline__ void wgmma_m64n128k16(float d[64], uint64_t desc_a, uint64_t desc_b, int scale_d) {
    asm volatile("{\n.reg .pred p;\nsetp.ne.b32 p, %66, 0;\n"
                 "wgmma.mma_async.sync.aligned.m64n128k16.f32.bf16.bf16 {%0,%1,%2,%3,%4,%5,%6,%7,%8,%9,%10,%11,%12,%13,%14,%15,%16,%17,%18,%19,%20,%21,%22,%23,%24,%25,%26,%27,%28,%29,%30,%31,%32,%33,%34,%35,%36,%37,%38,%39,%40,%41,%42,%43,%44,%45,%46,%47,%48,%49,%50,%51,%52,%53,%54,%55,%56,%57,%58,%59,%60,%61,%62,%63}, %64, %65, p, 1, 1, 0, 1;\n}"
                 : "+f"(d[0]),"+f"(d[1]),"+f"(d[2]),"+f"(d[3]),"+f"(d[4]),"+f"(d[5]),"+f"(d[6]),"+f"(d[7]),"+f"(d[8]),"+f"(d[9]),"+f"(d[10]),"+f"(d[11]),"+f"(d[12]),"+f"(d[13]),"+f"(d[14]),"+f"(d[15]),"+f"(d[16]),"+f"(d[17]),"+f"(d[18]),"+f"(d[19]),"+f"(d[20]),"+f"(d[21]),"+f"(d[22]),"+f"(d[23]),"+f"(d[24]),"+f"(d[25]),"+f"(d[26]),"+f"(d[27]),"+f"(d[28]),"+f"(d[29]),"+f"(d[30]),"+f"(d[31]),"+f"(d[32]),"+f"(d[33]),"+f"(d[34]),"+f"(d[35]),"+f"(d[36]),"+f"(d[37]),"+f"(d[38]),"+f"(d[39]),"+f"(d[40]),"+f"(d[41]),"+f"(d[42]),"+f"(d[43]),"+f"(d[44]),"+f"(d[45]),"+f"(d[46]),"+f"(d[47]),"+f"(d[48]),"+f"(d[49]),"+f"(d[50]),"+f"(d[51]),"+f"(d[52]),"+f"(d[53]),"+f"(d[54]),"+f"(d[55]),"+f"(d[56]),"+f"(d[57]),"+f"(d[58]),"+f"(d[59]),"+f"(d[60]),"+f"(d[61]),"+f"(d[62]),"+f"(d[63])
                 : "l"(desc_a), "l"(desc_b), "r"(scale_d));
}

__device__ __forceinline__ void wgmma_m64n64k16(float d[32], uint64_t desc_a, uint64_t desc_b, int scale_d) {
    asm volatile("{\n.reg .pred p;\nsetp.ne.b32 p, %34, 0;\n"
                 "wgmma.mma_async.sync.aligned.m64n64k16.f32.bf16.bf16 {%0,%1,%2,%3,%4,%5,%6,%7,%8,%9,%10,%11,%12,%13,%14,%15,%16,%17,%18,%19,%20,%21,%22,%23,%24,%25,%26,%27,%28,%29,%30,%31}, %32, %33, p, 1, 1, 0, 1;\n}"
                 : "+f"(d[0]),"+f"(d[1]),"+f"(d[2]),"+f"(d[3]),"+f"(d[4]),"+f"(d[5]),"+f"(d[6]),"+f"(d[7]),"+f"(d[8]),"+f"(d[9]),"+f"(d[10]),"+f"(d[11]),"+f"(d[12]),"+f"(d[13]),"+f"(d[14]),"+f"(d[15]),"+f"(d[16]),"+f"(d[17]),"+f"(d[18]),"+f"(d[19]),"+f"(d[20]),"+f"(d[21]),"+f"(d[22]),"+f"(d[23]),"+f"(d[24]),"+f"(d[25]),"+f"(d[26]),"+f"(d[27]),"+f"(d[28]),"+f"(d[29]),"+f"(d[30]),"+f"(d[31])
                 : "l"(desc_a), "l"(desc_b), "r"(scale_d));
}

#define K1_GW 12
#define K1_THREADS ((K1_GW + 8) * 32)
#define P1_EPT 10
#define P1_CHUNK (256 * P1_EPT)
#define K1_WBYTES (65536 + 2 * 16384)
#define K1_SMEM (K1_WBYTES + 3 * MAXBINS * 4 + P1_CHUNK * 8)

__device__ __forceinline__ void p1_bar() { asm volatile("bar.sync 1, 256;" ::: "memory"); }

__global__ void __launch_bounds__(K1_THREADS, 1) k1_kernel(
    const __nv_bfloat16* __restrict__ x, const __nv_bfloat16* __restrict__ e_attr,
    const int* __restrict__ src, const int* __restrict__ dst,
    const __nv_bfloat16* __restrict__ w_b, const __nv_bfloat16* __restrict__ w_v,
    const __nv_bfloat16* __restrict__ w_a, const __nv_bfloat16* __restrict__ w_u,
    int N, int E, int chunk, int NB, int nbins, uint32_t magic)
{
    extern __shared__ __align__(1024) uint8_t smem[];
    asm volatile("griddepcontrol.launch_dependents;");

    const int warp = threadIdx.x >> 5, lane = threadIdx.x & 31;

    if (warp >= K1_GW) {
        const int tid = threadIdx.x - K1_GW * 32;
        if (blockIdx.x == 0 && tid < 32)
            g_T[(size_t)N * 32 + tid] = make_uint4(0xff80ff80u, 0xff80ff80u, 0u, 0u);
        int* hist = reinterpret_cast<int*>(smem + K1_WBYTES);
        int* loff = hist + MAXBINS;
        int* gbase = loff + MAXBINS;
        uint2* sorted = reinterpret_cast<uint2*>(smem + K1_WBYTES + 3 * MAXBINS * 4);
        for (int beg = blockIdx.x * chunk; beg < E; beg += gridDim.x * chunk) {
            const int end = min(E, beg + chunk);
            int d[P1_EPT]; uint32_t rec[P1_EPT]; int rk[P1_EPT]; int bn[P1_EPT];
            #pragma unroll
            for (int i = 0; i < P1_EPT; i++) {
                int e = beg + i * 256 + tid;
                d[i] = -1;
                if (e < end) {
                    d[i] = __ldg(dst + e);
                    uint32_t s = (uint32_t)__ldg(src + e);
                    uint32_t ev = (uint32_t)__ldg(reinterpret_cast<const unsigned short*>(e_attr) + e);
                    rec[i] = (ev << 16) | s;
                }
            }
            hist[tid] = 0;
            p1_bar();
            #pragma unroll
            for (int i = 0; i < P1_EPT; i++) {
                if (d[i] >= 0) {
                    bn[i] = (int)(((uint64_t)(uint32_t)d[i] * magic) >> 24);
                    rk[i] = atomicAdd(&hist[bn[i]], 1);
                }
            }
            p1_bar();
            {
                int h = hist[tid];
                if (tid < nbins && h > 0) gbase[tid] = atomicAdd(&g_bin_cnt[tid * CNT_STRIDE], h);
                if (tid < 32) {
                    int v[8]; int sum = 0;
                    #pragma unroll
                    for (int i = 0; i < 8; i++) { v[i] = hist[lane * 8 + i]; sum += v[i]; }
                    int inc = sum;
                    #pragma unroll
                    for (int o = 1; o < 32; o <<= 1) { int t = __shfl_up_sync(0xffffffffu, inc, o); if (lane >= o) inc += t; }
                    int run = inc - sum;
                    #pragma unroll
                    for (int i = 0; i < 8; i++) { loff[lane * 8 + i] = run; run += v[i]; }
                }
            }
            p1_bar();
            #pragma unroll
            for (int i = 0; i < P1_EPT; i++) {
                if (d[i] >= 0) sorted[loff[bn[i]] + rk[i]] = make_uint2(rec[i], (uint32_t)d[i]);
            }
            p1_bar();
            const int cnt = end - beg;
            for (int i = tid; i < cnt; i += 256) {
                uint2 r = sorted[i];
                int b = (int)(((uint64_t)r.y * magic) >> 24);
                int pos = gbase[b] + (i - loff[b]);
                if (pos < BINCAP) {
                    g_bins[b * BINCAP + pos] = make_uint2(r.x, r.y - (uint32_t)(b * NB));
                } else {
                    int p = atomicAdd(&g_ovf_cnt, 2);
                    g_ovf[p] = (int)r.y; g_ovf[p + 1] = (int)r.x;
                }
            }
            p1_bar();
        }
        return;
    }

    if (blockIdx.x < 4 && threadIdx.x < 128) {
        const char* pw = reinterpret_cast<const char*>((blockIdx.x & 2) ? w_u : w_a) + (blockIdx.x & 1) * 16384 + threadIdx.x * 128;
        asm volatile("prefetch.global.L2 [%0];" :: "l"(pw));
    }
    const int q = lane & 3;
    const int wg = warp >> 2;
    const int n_tasks = ((N + 63) >> 6) * 2;
    const uint32_t sbase = (uint32_t)__cvta_generic_to_shared(smem);
    const uint32_t xbase = sbase + 65536;
    bool w_staged = false;
    int t_beg = (int)(((long long)n_tasks * blockIdx.x) / gridDim.x);
    const int t_end = (int)(((long long)n_tasks * (blockIdx.x + 1)) / gridDim.x);
    while (t_beg < t_end) {
        const int tile0 = t_beg >> 1;
        const int t_stop = min(t_end, (tile0 + 2) << 1);
        stage_x_tile(xbase, x, tile0 * 64, N, threadIdx.x, K1_GW * 32);
        if (((t_stop - 1) >> 1) > tile0) stage_x_tile(xbase + 16384, x, tile0 * 64 + 64, N, threadIdx.x, K1_GW * 32);
        if (!w_staged) {
            stage_weight(sbase, w_b, 0, threadIdx.x, K1_GW * 32);
            stage_weight(sbase, w_v, 1, threadIdx.x, K1_GW * 32);
            w_staged = true;
        }
        asm volatile("cp.async.wait_all;" ::: "memory");
        asm volatile("fence.proxy.async.shared::cta;" ::: "memory");
        asm volatile("bar.sync 2, %0;" :: "n"(K1_GW * 32) : "memory");
        for (int task = t_beg + wg; task < t_stop; task += K1_GW / 4) {
            const int tile = task >> 1, hf = task & 1;
            const uint32_t baddr = sbase + hf * 1024;
            const uint64_t descb = (uint64_t)((baddr & 0x3FFFF) >> 4) | ((uint64_t)(2048 >> 4) << 16) |
                                   ((uint64_t)(4096 >> 4) << 32) | ((uint64_t)1 << 62);
            const uint32_t aaddr = xbase + (tile - tile0) * 16384;
            const uint64_t desca = (uint64_t)((aaddr & 0x3FFFF) >> 4) | ((uint64_t)1 << 16) |
                                   ((uint64_t)(1024 >> 4) << 32) | ((uint64_t)1 << 62);
            float d[64];
            asm volatile("wgmma.fence.sync.aligned;" ::: "memory");
            #pragma unroll
            for (int ks = 0; ks < 8; ks++) {
                wgmma_m64n128k16(d, desca + (uint64_t)(((ks >> 2) * 8192 + (ks & 3) * 32) >> 4),
                                 descb + (uint64_t)(ks * (8192 >> 4)), ks > 0 ? 1 : 0);
            }
            asm volatile("wgmma.commit_group.sync.aligned;" ::: "memory");
            asm volatile("wgmma.wait_group.sync.aligned 0;" ::: "memory");
            const int r0 = tile * 64 + (warp & 3) * 16 + (lane >> 2);
            #pragma unroll
            for (int mm = 0; mm < 4; mm++) {
                const int j0 = 2 * mm, j1 = 2 * mm + 1, j2 = 8 + 2 * mm, j3 = 9 + 2 * mm;
                uint4 o0 = make_uint4(pack_bf16(d[4 * j0], d[4 * j0 + 1]), pack_bf16(d[4 * j1], d[4 * j1 + 1]),
                                      pack_bf16(d[4 * j2], d[4 * j2 + 1]), pack_bf16(d[4 * j3], d[4 * j3 + 1]));
                uint4 o1 = make_uint4(pack_bf16(d[4 * j0 + 2], d[4 * j0 + 3]), pack_bf16(d[4 * j1 + 2], d[4 * j1 + 3]),
                                      pack_bf16(d[4 * j2 + 2], d[4 * j2 + 3]), pack_bf16(d[4 * j3 + 2], d[4 * j3 + 3]));
                const int m = 4 * hf + mm;
                if (r0 < N) g_T[(size_t)r0 * 32 + 4 * m + q] = o0;
                if (r0 + 8 < N) g_T[(size_t)(r0 + 8) * 32 + 4 * m + q] = o1;
            }
        }
        t_beg = t_stop;
        if (t_beg < t_end) asm volatile("bar.sync 2, %0;" :: "n"(K1_GW * 32) : "memory");
    }
}

__device__ __forceinline__ void edge_accum(const uint4 v, const float e, const float a[4], const float cc[4],
                                           float num[4], float den[4]) {
    float y0 = fmaf(bf_lo(v.x), -LOG2E, fmaf(e, cc[0], a[0]));
    float y1 = fmaf(bf_hi(v.x), -LOG2E, fmaf(e, cc[1], a[1]));
    float y2 = fmaf(bf_lo(v.y), -LOG2E, fmaf(e, cc[2], a[2]));
    float y3 = fmaf(bf_hi(v.y), -LOG2E, fmaf(e, cc[3], a[3]));
    float s0 = rcp_approx(1.f + ex2_approx(y0));
    float s1 = rcp_approx(1.f + ex2_approx(y1));
    float s2 = rcp_approx(1.f + ex2_approx(y2));
    float s3 = rcp_approx(1.f + ex2_approx(y3));
    den[0] += s0; den[1] += s1; den[2] += s2; den[3] += s3;
    num[0] = fmaf(s0, bf_lo(v.z), num[0]);
    num[1] = fmaf(s1, bf_hi(v.z), num[1]);
    num[2] = fmaf(s2, bf_lo(v.w), num[2]);
    num[3] = fmaf(s3, bf_hi(v.w), num[3]);
}

#define K2_THREADS 1024
#define K2_D 2
#define K2_GS 2
#define K2_RPT ((BINCAP + K2_THREADS - 1) / K2_THREADS)
#define K2_NW (K2_THREADS / 32)
#define SORT_WORDS (BINCAP + 4 * MAXNB)
#define K2_OFF_W 0
#define K2_OFF_X 65536
#define K2_OFF_A (K2_OFF_X + 32768)
#define K2_OFF_U (K2_OFF_A + MAXNB * 256)
#define K2_OFF_PART (K2_OFF_U + MAXNB * 256)
#define K2_OFF_SORT (K2_OFF_PART + K2_NW * 1024)
#define K2_OFF_HIST (K2_OFF_SORT + SORT_WORDS * 4)
#define K2_OFF_OFF (K2_OFF_HIST + MAXNB * 4)
#define K2_DYN_SMEM (K2_OFF_OFF + (MAXNB + 4) * 4)
#define K2_ST (K2_THREADS - 512)
#define K2_SRPT ((BINCAP + K2_ST - 1) / K2_ST)

struct Grp { uint4 v[K2_GS]; };

__device__ __forceinline__ const uint4* row_ptr(const char* Tl, uint32_t rec) {
    return reinterpret_cast<const uint4*>(Tl + (size_t)((rec & 0xffffu) * 512u));
}
__device__ __forceinline__ void grp_load(Grp& g, const uint32_t* sp, const char* Tl) {
    const uint2 t = *reinterpret_cast<const uint2*>(sp);
    g.v[0] = __ldg(row_ptr(Tl, t.x));
    g.v[1] = __ldg(row_ptr(Tl, t.y));
}
__device__ __forceinline__ void grp_consume(const Grp& g, const uint32_t* sp, const float a[4], const float cc[4],
                                            float num[4], float den[4]) {
    const uint2 t = *reinterpret_cast<const uint2*>(sp);
    edge_accum(g.v[0], bf_hi(t.x), a, cc, num, den);
    edge_accum(g.v[1], bf_hi(t.y), a, cc, num, den);
}

__device__ __forceinline__ void load_a(const uint8_t* smem, int ln, int lane, float a[4]) {
    const uint2 av = reinterpret_cast<const uint2*>(smem + K2_OFF_A)[ln * 32 + (lane ^ ((ln & 3) << 2))];
    a[0] = -LOG2E * bf_lo(av.x); a[1] = -LOG2E * bf_hi(av.x); a[2] = -LOG2E * bf_lo(av.y); a[3] = -LOG2E * bf_hi(av.y);
}
__device__ __forceinline__ void write_node(const uint8_t* smem, __nv_bfloat16* out, int ln, int n,
                                           int lane, const float num[4], const float den[4]) {
    const uint2 uv = reinterpret_cast<const uint2*>(smem + K2_OFF_U)[ln * 32 + (lane ^ ((ln & 3) << 2))];
    const int r = ln & 63, c16 = (lane >> 2) * 2;
    const uint8_t* xr = smem + K2_OFF_X + (ln >> 6) * 16384 + (c16 >> 3) * 8192 + r * 128 + (lane & 3) * 4;
    const uint32_t x0 = *reinterpret_cast<const uint32_t*>(xr + (((c16 & 7) ^ (r & 7)) << 4));
    const uint32_t x1 = *reinterpret_cast<const uint32_t*>(xr + ((((c16 + 1) & 7) ^ (r & 7)) << 4));
    const float u4[4] = { bf_lo(uv.x), bf_hi(uv.x), bf_lo(uv.y), bf_hi(uv.y) };
    const float x4[4] = { bf_lo(x0), bf_hi(x0), bf_lo(x1), bf_hi(x1) };
    float o[4];
    #pragma unroll
    for (int i = 0; i < 4; i++) {
        float agg = round_bf16(__fdividef(num[i], den[i] + 1e-6f));
        float z = round_bf16(u4[i] + agg);
        float rz = (z > 0.f) ? z : 0.f * z;
        o[i] = x4[i] + rz;
    }
    uint32_t* o32 = reinterpret_cast<uint32_t*>(out) + (size_t)n * 64 + (lane >> 2) * 8 + (lane & 3);
    o32[0] = pack_bf16(o[0], o[1]); o32[4] = pack_bf16(o[2], o[3]);
}

__device__ __noinline__ void slow_path(const uint8_t* smem, __nv_bfloat16* out, int node0, int nn, int ovf_n,
                                       float c0, float c1, float c2, float c3) {
    const uint32_t* s_sorted = reinterpret_cast<const uint32_t*>(smem + K2_OFF_SORT);
    const int* s_off = reinterpret_cast<const int*>(smem + K2_OFF_OFF);
    const int lane = threadIdx.x & 31, warp = threadIdx.x >> 5;
    const float cc[4] = { c0, c1, c2, c3 };
    const char* Tl = reinterpret_cast<const char*>(g_T) + lane * 16;
    for (int ln = warp; ln < nn; ln += K2_NW) {
        float a[4];
        load_a(smem, ln, lane, a);
        float num[4] = {0.f, 0.f, 0.f, 0.f}, den[4] = {0.f, 0.f, 0.f, 0.f};
        for (int i = s_off[ln]; i < s_off[ln + 1]; i++) {
            const uint32_t r = s_sorted[i];
            edge_accum(__ldg(row_ptr(Tl, r)), bf_hi(r), a, cc, num, den);
        }
        const int n = node0 + ln;
        for (int base = 0; base < ovf_n; base += 64) {
            int i2 = base + 2 * lane;
            int od = (i2 < ovf_n) ? g_ovf[i2] : -1;
            uint32_t orec = (i2 < ovf_n) ? (uint32_t)g_ovf[i2 + 1] : 0u;
            unsigned msk = __ballot_sync(0xffffffffu, od == n);
            while (msk) {
                int l = __ffs(msk) - 1; msk &= msk - 1;
                uint32_t r = __shfl_sync(0xffffffffu, orec, l);
                edge_accum(__ldg(row_ptr(Tl, r)), bf_hi(r), a, cc, num, den);
            }
        }
        write_node(smem, out, ln, n, lane, num, den);
    }
}

__global__ void __launch_bounds__(K2_THREADS, 1) k2_kernel(
    const __nv_bfloat16* __restrict__ x, const __nv_bfloat16* __restrict__ w_a, const __nv_bfloat16* __restrict__ w_u,
    const __nv_bfloat16* __restrict__ w_c, __nv_bfloat16* __restrict__ out, int N, int NB)
{
    extern __shared__ __align__(1024) uint8_t smem[];
    float4* s_part = reinterpret_cast<float4*>(smem + K2_OFF_PART);
    uint32_t* s_sorted = reinterpret_cast<uint32_t*>(smem + K2_OFF_SORT);
    int* s_hist = reinterpret_cast<int*>(smem + K2_OFF_HIST);
    int* s_off = reinterpret_cast<int*>(smem + K2_OFF_OFF);

    const int tid = threadIdx.x;
    const int lane = tid & 31, warp = tid >> 5;
    const int bin = blockIdx.x;
    const int node0 = bin * NB;
    const int nn = min(NB, N - node0);
    const uint32_t sb = (uint32_t)__cvta_generic_to_shared(smem);

    s_part[warp * 64 + lane] = make_float4(0.f, 0.f, 0.f, 0.f);
    s_part[warp * 64 + 32 + lane] = make_float4(0.f, 0.f, 0.f, 0.f);
    int ovf_n = 0;
    if (warp < 16) {
        stage_x_tile(sb + K2_OFF_X, x, node0, N, tid, 512);
        if (nn > 64) stage_x_tile(sb + K2_OFF_X + 16384, x, node0 + 64, N, tid, 512);
        stage_weight(sb + K2_OFF_W, w_a, 0, tid, 512);
        stage_weight(sb + K2_OFF_W, w_u, 1, tid, 512);
        asm volatile("cp.async.wait_all;" ::: "memory");
        asm volatile("fence.proxy.async.shared::cta;" ::: "memory");
        asm volatile("bar.sync 2, 512;" ::: "memory");
        const int wg = warp >> 2, tile = wg >> 1, mtx = wg & 1;
        if (tile * 64 < nn) {
            const uint32_t aaddr = sb + K2_OFF_X + tile * 16384;
            const uint64_t desca = (uint64_t)((aaddr & 0x3FFFF) >> 4) | ((uint64_t)1 << 16) |
                                   ((uint64_t)(1024 >> 4) << 32) | ((uint64_t)1 << 62);
            uint2* dst = reinterpret_cast<uint2*>(smem + (mtx ? K2_OFF_U : K2_OFF_A));
            const int r0 = tile * 64 + (warp & 3) * 16 + (lane >> 2);
            const int sw = (r0 & 3) << 2;
            #pragma unroll 1
            for (int hf = 0; hf < 2; hf++) {
                const uint32_t baddr = sb + K2_OFF_W + (mtx * 2 + hf) * 1024;
                const uint64_t descb = (uint64_t)((baddr & 0x3FFFF) >> 4) | ((uint64_t)(2048 >> 4) << 16) |
                                       ((uint64_t)(4096 >> 4) << 32) | ((uint64_t)1 << 62);
                float d[32];
                asm volatile("wgmma.fence.sync.aligned;" ::: "memory");
                #pragma unroll
                for (int ks = 0; ks < 8; ks++) {
                    wgmma_m64n64k16(d, desca + (uint64_t)(((ks >> 2) * 8192 + (ks & 3) * 32) >> 4),
                                    descb + (uint64_t)(ks * (8192 >> 4)), ks > 0 ? 1 : 0);
                }
                asm volatile("wgmma.commit_group.sync.aligned;" ::: "memory");
                asm volatile("wgmma.wait_group.sync.aligned 0;" ::: "memory");
                #pragma unroll
                for (int mm = 0; mm < 4; mm++) {
                    const int j0 = 2 * mm, j1 = 2 * mm + 1;
                    const int slot = (4 * (4 * hf + mm) + (lane & 3)) ^ sw;
                    dst[r0 * 32 + slot] = make_uint2(pack_bf16(d[4 * j0], d[4 * j0 + 1]), pack_bf16(d[4 * j1], d[4 * j1 + 1]));
                    dst[(r0 + 8) * 32 + slot] = make_uint2(pack_bf16(d[4 * j0 + 2], d[4 * j0 + 3]), pack_bf16(d[4 * j1 + 2], d[4 * j1 + 3]));
                }
            }
        }
        asm volatile("griddepcontrol.wait;" ::: "memory");
        ovf_n = g_ovf_cnt;
    } else {
        const int st = tid - 512;
        if (st < MAXNB) s_hist[st] = 0;
        for (int i = st; i < SORT_WORDS; i += K2_ST) s_sorted[i] = (uint32_t)N;
        asm volatile("bar.sync 1, %0;" :: "n"(K2_ST) : "memory");
        asm volatile("griddepcontrol.wait;" ::: "memory");
        uint2 r[K2_SRPT]; int rk[K2_SRPT];
        const int cnt = min(g_bin_cnt[bin * CNT_STRIDE], BINCAP);
        ovf_n = g_ovf_cnt;
        #pragma unroll
        for (int i = 0; i < K2_SRPT; i++) {
            int idx = i * K2_ST + st;
            if (idx < cnt) r[i] = g_bins[bin * BINCAP + idx];
        }
        #pragma unroll
        for (int i = 0; i < K2_SRPT; i++) {
            int idx = i * K2_ST + st;
            if (idx < cnt) rk[i] = atomicAdd(&s_hist[r[i].y], 1);
        }
        asm volatile("bar.sync 1, %0;" :: "n"(K2_ST) : "memory");
        if (warp == 16) {
            int v[4]; int sum = 0;
            #pragma unroll
            for (int i = 0; i < 4; i++) { v[i] = (s_hist[lane * 4 + i] + K2_GS - 1) & ~(K2_GS - 1); sum += v[i]; }
            int inc = sum;
            #pragma unroll
            for (int o = 1; o < 32; o <<= 1) { int t = __shfl_up_sync(0xffffffffu, inc, o); if (lane >= o) inc += t; }
            int run = inc - sum;
            #pragma unroll
            for (int i = 0; i < 4; i++) { s_off[lane * 4 + i] = run; run += v[i]; }
            if (lane == 31) s_off[MAXNB] = run;
        }
        if (st == 32) g_bin_cnt[bin * CNT_STRIDE] = 0;
        asm volatile("bar.sync 1, %0;" :: "n"(K2_ST) : "memory");
        #pragma unroll
        for (int i = 0; i < K2_SRPT; i++) {
            int idx = i * K2_ST + st;
            if (idx < cnt) s_sorted[s_off[r[i].y] + rk[i]] = r[i].x;
        }
    }
    const int fw = (lane >> 2) * 8 + (lane & 3);
    const uint2 wc = make_uint2(__ldg(reinterpret_cast<const uint32_t*>(w_c) + fw), __ldg(reinterpret_cast<const uint32_t*>(w_c) + fw + 4));
    float cc[4] = { -LOG2E * bf_lo(wc.x), -LOG2E * bf_hi(wc.x), -LOG2E * bf_lo(wc.y), -LOG2E * bf_hi(wc.y) };
    __syncthreads();

    if (ovf_n != 0) {
        slow_path(smem, out, node0, nn, ovf_n, cc[0], cc[1], cc[2], cc[3]);
        __syncthreads();
        if (tid == 0) {
            __threadfence();
            int t = atomicAdd(&g_done, 1);
            if (t == (int)gridDim.x - 1) { g_done = 0; __threadfence(); g_ovf_cnt = 0; }
        }
        return;
    }

    const char* Tl = reinterpret_cast<const char*>(g_T) + lane * 16;
    const int G = s_off[MAXNB] / K2_GS;
    int g = (G * warp) / K2_NW;
    const int g1 = (G * (warp + 1)) / K2_NW;
    int ln;
    {
        int c_lo = 0;
        #pragma unroll
        for (int i = 0; i < 4; i++) {
            int node = i * 32 + lane;
            int o = (node < nn) ? s_off[node] : 0x7fffffff;
            c_lo += __popc(__ballot_sync(0xffffffffu, o < g * K2_GS));
        }
        ln = c_lo;
    }
    bool head = ln > 0;
    if (head) ln--;
    float a[4], num[4] = {0.f, 0.f, 0.f, 0.f}, den[4] = {0.f, 0.f, 0.f, 0.f};
    int node_end;

    auto load_node = [&]() {
        load_a(smem, ln, lane, a);
        node_end = s_off[ln + 1] / K2_GS;
    };
    auto finish_node = [&]() { write_node(smem, out, ln, node0 + ln, lane, num, den); };
    auto close_node = [&]() {
        if (head) {
            s_part[warp * 64 + lane] = make_float4(num[0], num[1], num[2], num[3]);
            s_part[warp * 64 + 32 + lane] = make_float4(den[0], den[1], den[2], den[3]);
            head = false;
        } else {
            finish_node();
        }
        #pragma unroll
        for (int i = 0; i < 4; i++) { num[i] = 0.f; den[i] = 0.f; }
    };

    bool tail = false;
    if (g < g1 || warp == K2_NW - 1) {
        load_node();
        Grp b[K2_D];
        #pragma unroll
        for (int d = 0; d < K2_D; d++)
            if (g + d < g1) grp_load(b[d], s_sorted + K2_GS * (g + d), Tl);
        while (g < g1) {
            #pragma unroll
            for (int d = 0; d < K2_D; d++) {
                if (g < g1) {
                    while (g == node_end) { close_node(); ln++; load_node(); }
                    grp_consume(b[d], s_sorted + K2_GS * g, a, cc, num, den);
                    if (g + K2_D < g1) grp_load(b[d], s_sorted + K2_GS * (g + K2_D), Tl);
                    g++;
                }
            }
        }
        if (warp == K2_NW - 1) {
            while (true) { close_node(); ln++; if (ln >= nn) break; load_node(); }
        } else if (node_end == g1 || head) {
            close_node();
        } else {
            tail = true;
        }
    }
    __syncthreads();
    if (tail) {
        for (int w2 = warp + 1; w2 < K2_NW && (G * w2) / K2_NW < node_end; w2++) {
            const float4 pn = s_part[w2 * 64 + lane], pd = s_part[w2 * 64 + 32 + lane];
            num[0] += pn.x; num[1] += pn.y; num[2] += pn.z; num[3] += pn.w;
            den[0] += pd.x; den[1] += pd.y; den[2] += pd.z; den[3] += pd.w;
        }
        finish_node();
    }
}

extern "C" void kernel_launch(void* const* d_in, const int* in_sizes, int n_in,
                              void* d_out, int out_size) {
    const __nv_bfloat16* x      = (const __nv_bfloat16*)d_in[0];
    const __nv_bfloat16* e_attr = (const __nv_bfloat16*)d_in[1];
    const int* src = (const int*)d_in[2];
    const int* dst = (const int*)d_in[3];
    const __nv_bfloat16* w_a = (const __nv_bfloat16*)d_in[4];
    const __nv_bfloat16* w_b = (const __nv_bfloat16*)d_in[5];
    const __nv_bfloat16* w_c = (const __nv_bfloat16*)d_in[6];
    const __nv_bfloat16* w_u = (const __nv_bfloat16*)d_in[7];
    const __nv_bfloat16* w_v = (const __nv_bfloat16*)d_in[8];
    __nv_bfloat16* out = (__nv_bfloat16*)d_out;
    const int N = in_sizes[0] / D_FEAT;
    const int E = in_sizes[2];
    if (N > MAX_N || 2 * E > MAX_E || N <= 0) return;

    static int num_sms = 0;
    if (num_sms == 0) {
        int dev = 0;
        cudaGetDevice(&dev);
        cudaDeviceGetAttribute(&num_sms, cudaDevAttrMultiProcessorCount, dev);
        if (num_sms <= 0 || num_sms > MAXBINS) num_sms = 132;
        cudaFuncSetAttribute(k1_kernel, cudaFuncAttributeMaxDynamicSharedMemorySize, K1_SMEM);
        cudaFuncSetAttribute(k2_kernel, cudaFuncAttributeMaxDynamicSharedMemorySize, K2_DYN_SMEM);
    }
    cudaStream_t st = cudaStreamPerThread;
    int NB = (N + num_sms - 1) / num_sms;
    if (NB > MAXNB) NB = MAXNB;
    const int nbins = (N + NB - 1) / NB;
    const uint32_t magic = (uint32_t)(((1u << 24) + NB - 1) / NB);
    const int P = num_sms;
    int chunk = (E + P - 1) / P;
    if (chunk > P1_CHUNK) chunk = P1_CHUNK;
    if (chunk < 1) chunk = 1;
    k1_kernel<<<P, K1_THREADS, K1_SMEM, st>>>(x, e_attr, src, dst, w_b, w_v, w_a, w_u, N, E, chunk, NB, nbins, magic);

    cudaLaunchConfig_t cfg = {};
    cfg.gridDim = dim3(nbins);
    cfg.blockDim = dim3(K2_THREADS);
    cfg.dynamicSmemBytes = K2_DYN_SMEM;
    cfg.stream = st;
    cudaLaunchAttribute at[1];
    at[0].id = cudaLaunchAttributeProgrammaticStreamSerialization;
    at[0].val.programmaticStreamSerializationAllowed = 1;
    cfg.attrs = at; cfg.numAttrs = 1;
    cudaLaunchKernelEx(&cfg, k2_kernel, x, w_a, w_u, w_c, out, N, NB);
}
```

```cpp
#include <cuda_runtime.h>
#include <cuda_bf16.h>
#include <stdint.h>

#define D_FEAT 128
#define MAX_N 16384
#define MAX_E (1 << 20)
#define LOG2E 1.4426950408889634f

#define MAXBINS 256
#define MAXNB 128
#define BINCAP 3072
__device__ uint4 g_T[(MAX_N + 1) * 32];
#define CNT_STRIDE 1
__device__ int g_bin_cnt[MAXBINS * CNT_STRIDE];
__device__ uint2 g_bins[MAXBINS * BINCAP];
__device__ int g_ovf[MAX_E];
__device__ int g_ovf_cnt;
__device__ int g_done;

__device__ __forceinline__ float ex2_approx(float x) {
    float y; asm("ex2.approx.ftz.f32 %0, %1;" : "=f"(y) : "f"(x)); return y;
}
__device__ __forceinline__ float rcp_approx(float x) {
    float y; asm("rcp.approx.ftz.f32 %0, %1;" : "=f"(y) : "f"(x)); return y;
}
__device__ __forceinline__ uint32_t pack_bf16(float lo, float hi) {
    __nv_bfloat162 t = __floats2bfloat162_rn(lo, hi);
    return *reinterpret_cast<uint32_t*>(&t);
}
__device__ __forceinline__ float bf_lo(uint32_t v) { return __uint_as_float(v << 16); }
__device__ __forceinline__ float bf_hi(uint32_t v) { return __uint_as_float(v & 0xffff0000u); }
__device__ __forceinline__ float round_bf16(float x) { return __bfloat162float(__float2bfloat16_rn(x)); }

__device__ __forceinline__ void mma_bf16(float c[4], uint32_t a0, uint32_t a1, uint32_t a2, uint32_t a3,
                                         uint32_t b0, uint32_t b1) {
    asm volatile("mma.sync.aligned.m16n8k16.row.col.f32.bf16.bf16.f32 "
                 "{%0,%1,%2,%3}, {%4,%5,%6,%7}, {%8,%9}, {%0,%1,%2,%3};"
                 : "+f"(c[0]), "+f"(c[1]), "+f"(c[2]), "+f"(c[3])
                 : "r"(a0), "r"(a1), "r"(a2), "r"(a3), "r"(b0), "r"(b1));
}
__device__ __forceinline__ void ldmatrix_x4_trans(uint32_t& r0, uint32_t& r1, uint32_t& r2, uint32_t& r3, uint32_t addr) {
    asm volatile("ldmatrix.sync.aligned.m8n8.x4.trans.shared.b16 {%0,%1,%2,%3}, [%4];"
                 : "=r"(r0), "=r"(r1), "=r"(r2), "=r"(r3) : "r"(addr));
}

__device__ __forceinline__ void cp_async16(uint32_t saddr, const void* g) {
    asm volatile("cp.async.cg.shared.global [%0], [%1], 16;" :: "r"(saddr), "l"(g) : "memory");
}
__device__ __forceinline__ void cp_async16_zfill(uint32_t saddr, const void* g, int src_size) {
    asm volatile("cp.async.cg.shared.global [%0], [%1], 16, %2;" :: "r"(saddr), "l"(g), "r"(src_size) : "memory");
}
__device__ __forceinline__ void stage_weight(uint32_t sdst, const __nv_bfloat16* w, int mtx, int tid, int nthreads) {
    const uint4* W = reinterpret_cast<const uint4*>(w);
    for (int u = tid; u < 2048; u += nthreads) {
        int k = u >> 4, c16 = u & 15;
        int kg = k >> 3, rr = k & 7;
        int h = mtx * 2 + (c16 >> 3);
        cp_async16(sdst + kg * 4096 + h * 1024 + rr * 128 + (((c16 & 7) ^ rr) << 4), W + u);
    }
}
__device__ __forceinline__ void stage_x_tile(uint32_t sdst, const __nv_bfloat16* x, int row0, int N, int tid, int nthreads) {
    const uint4* X = reinterpret_cast<const uint4*>(x);
    for (int u = tid; u < 1024; u += nthreads) {
        int r = u >> 4, c16 = u & 15;
        int gr = row0 + r;
        bool ok = gr < N;
        cp_async16_zfill(sdst + (c16 >> 3) * 8192 + r * 128 + (((c16 & 7) ^ (r & 7)) << 4),
                         X + (size_t)(ok ? gr : 0) * 16 + c16, ok ? 16 : 0);
    }
}

__device__ __forceinline__ void wgmma_m64n128k16(float d[64], uint64_t desc_a, uint64_t desc_b, int scale_d) {
    asm volatile("{\n.reg .pred p;\nsetp.ne.b32 p, %66, 0;\n"
                 "wgmma.mma_async.sync.aligned.m64n128k16.f32.bf16.bf16 {%0,%1,%2,%3,%4,%5,%6,%7,%8,%9,%10,%11,%12,%13,%14,%15,%16,%17,%18,%19,%20,%21,%22,%23,%24,%25,%26,%27,%28,%29,%30,%31,%32,%33,%34,%35,%36,%37,%38,%39,%40,%41,%42,%43,%44,%45,%46,%47,%48,%49,%50,%51,%52,%53,%54,%55,%56,%57,%58,%59,%60,%61,%62,%63}, %64, %65, p, 1, 1, 0, 1;\n}"
                 : "+f"(d[0]),"+f"(d[1]),"+f"(d[2]),"+f"(d[3]),"+f"(d[4]),"+f"(d[5]),"+f"(d[6]),"+f"(d[7]),"+f"(d[8]),"+f"(d[9]),"+f"(d[10]),"+f"(d[11]),"+f"(d[12]),"+f"(d[13]),"+f"(d[14]),"+f"(d[15]),"+f"(d[16]),"+f"(d[17]),"+f"(d[18]),"+f"(d[19]),"+f"(d[20]),"+f"(d[21]),"+f"(d[22]),"+f"(d[23]),"+f"(d[24]),"+f"(d[25]),"+f"(d[26]),"+f"(d[27]),"+f"(d[28]),"+f"(d[29]),"+f"(d[30]),"+f"(d[31]),"+f"(d[32]),"+f"(d[33]),"+f"(d[34]),"+f"(d[35]),"+f"(d[36]),"+f"(d[37]),"+f"(d[38]),"+f"(d[39]),"+f"(d[40]),"+f"(d[41]),"+f"(d[42]),"+f"(d[43]),"+f"(d[44]),"+f"(d[45]),"+f"(d[46]),"+f"(d[47]),"+f"(d[48]),"+f"(d[49]),"+f"(d[50]),"+f"(d[51]),"+f"(d[52]),"+f"(d[53]),"+f"(d[54]),"+f"(d[55]),"+f"(d[56]),"+f"(d[57]),"+f"(d[58]),"+f"(d[59]),"+f"(d[60]),"+f"(d[61]),"+f"(d[62]),"+f"(d[63])
                 : "l"(desc_a), "l"(desc_b), "r"(scale_d));
}

__device__ __forceinline__ void wgmma_m64n64k16(float d[32], uint64_t desc_a, uint64_t desc_b, int scale_d) {
    asm volatile("{\n.reg .pred p;\nsetp.ne.b32 p, %34, 0;\n"
                 "wgmma.mma_async.sync.aligned.m64n64k16.f32.bf16.bf16 {%0,%1,%2,%3,%4,%5,%6,%7,%8,%9,%10,%11,%12,%13,%14,%15,%16,%17,%18,%19,%20,%21,%22,%23,%24,%25,%26,%27,%28,%29,%30,%31}, %32, %33, p, 1, 1, 0, 1;\n}"
                 : "+f"(d[0]),"+f"(d[1]),"+f"(d[2]),"+f"(d[3]),"+f"(d[4]),"+f"(d[5]),"+f"(d[6]),"+f"(d[7]),"+f"(d[8]),"+f"(d[9]),"+f"(d[10]),"+f"(d[11]),"+f"(d[12]),"+f"(d[13]),"+f"(d[14]),"+f"(d[15]),"+f"(d[16]),"+f"(d[17]),"+f"(d[18]),"+f"(d[19]),"+f"(d[20]),"+f"(d[21]),"+f"(d[22]),"+f"(d[23]),"+f"(d[24]),"+f"(d[25]),"+f"(d[26]),"+f"(d[27]),"+f"(d[28]),"+f"(d[29]),"+f"(d[30]),"+f"(d[31])
                 : "l"(desc_a), "l"(desc_b), "r"(scale_d));
}

#define K1_GW 12
#define K1_THREADS ((K1_GW + 8) * 32)
#define P1_EPT 10
#define P1_CHUNK (256 * P1_EPT)
#define K1_WBYTES (65536 + 2 * 16384)
#define K1_SMEM (K1_WBYTES + 3 * MAXBINS * 4 + P1_CHUNK * 8)

__device__ __forceinline__ void p1_bar() { asm volatile("bar.sync 1, 256;" ::: "memory"); }

__global__ void __launch_bounds__(K1_THREADS, 1) k1_kernel(
    const __nv_bfloat16* __restrict__ x, const __nv_bfloat16* __restrict__ e_attr,
    const int* __restrict__ src, const int* __restrict__ dst,
    const __nv_bfloat16* __restrict__ w_b, const __nv_bfloat16* __restrict__ w_v,
    const __nv_bfloat16* __restrict__ w_a, const __nv_bfloat16* __restrict__ w_u,
    int N, int E, int chunk, int NB, int nbins, uint32_t magic)
{
    extern __shared__ __align__(1024) uint8_t smem[];
    asm volatile("griddepcontrol.launch_dependents;");

    const int warp = threadIdx.x >> 5, lane = threadIdx.x & 31;

    if (warp >= K1_GW) {
        const int tid = threadIdx.x - K1_GW * 32;
        if (blockIdx.x == 0 && tid < 32)
            g_T[(size_t)N * 32 + tid] = make_uint4(0xff80ff80u, 0xff80ff80u, 0u, 0u);
        int* hist = reinterpret_cast<int*>(smem + K1_WBYTES);
        int* loff = hist + MAXBINS;
        int* gbase = loff + MAXBINS;
        uint2* sorted = reinterpret_cast<uint2*>(smem + K1_WBYTES + 3 * MAXBINS * 4);
        for (int beg = blockIdx.x * chunk; beg < E; beg += gridDim.x * chunk) {
            const int end = min(E, beg + chunk);
            int d[P1_EPT]; uint32_t rec[P1_EPT]; int rk[P1_EPT]; int bn[P1_EPT];
            #pragma unroll
            for (int i = 0; i < P1_EPT; i++) {
                int e = beg + i * 256 + tid;
                d[i] = -1;
                if (e < end) {
                    d[i] = __ldg(dst + e);
                    uint32_t s = (uint32_t)__ldg(src + e);
                    uint32_t ev = (uint32_t)__ldg(reinterpret_cast<const unsigned short*>(e_attr) + e);
                    rec[i] = (ev << 16) | s;
                }
            }
            hist[tid] = 0;
            p1_bar();
            #pragma unroll
            for (int i = 0; i < P1_EPT; i++) {
                if (d[i] >= 0) {
                    bn[i] = (int)(((uint64_t)(uint32_t)d[i] * magic) >> 24);
                    rk[i] = atomicAdd(&hist[bn[i]], 1);
                }
            }
            p1_bar();
            {
                int h = hist[tid];
                if (tid < nbins && h > 0) gbase[tid] = atomicAdd(&g_bin_cnt[tid * CNT_STRIDE], h);
                if (tid < 32) {
                    int v[8]; int sum = 0;
                    #pragma unroll
                    for (int i = 0; i < 8; i++) { v[i] = hist[lane * 8 + i]; sum += v[i]; }
                    int inc = sum;
                    #pragma unroll
                    for (int o = 1; o < 32; o <<= 1) { int t = __shfl_up_sync(0xffffffffu, inc, o); if (lane >= o) inc += t; }
                    int run = inc - sum;
                    #pragma unroll
                    for (int i = 0; i < 8; i++) { loff[lane * 8 + i] = run; run += v[i]; }
                }
            }
            p1_bar();
            #pragma unroll
            for (int i = 0; i < P1_EPT; i++) {
                if (d[i] >= 0) sorted[loff[bn[i]] + rk[i]] = make_uint2(rec[i], (uint32_t)d[i]);
            }
            p1_bar();
            const int cnt = end - beg;
            for (int i = tid; i < cnt; i += 256) {
                uint2 r = sorted[i];
                int b = (int)(((uint64_t)r.y * magic) >> 24);
                int pos = gbase[b] + (i - loff[b]);
                if (pos < BINCAP) {
                    g_bins[b * BINCAP + pos] = make_uint2(r.x, r.y - (uint32_t)(b * NB));
                } else {
                    int p = atomicAdd(&g_ovf_cnt, 2);
                    g_ovf[p] = (int)r.y; g_ovf[p + 1] = (int)r.x;
                }
            }
            p1_bar();
        }
        return;
    }

    if (blockIdx.x < 4 && threadIdx.x < 128) {
        const char* pw = reinterpret_cast<const char*>((blockIdx.x & 2) ? w_u : w_a) + (blockIdx.x & 1) * 16384 + threadIdx.x * 128;
        asm volatile("prefetch.global.L2 [%0];" :: "l"(pw));
    }
    const int q = lane & 3;
    const int wg = warp >> 2;
    const int n_tasks = ((N + 63) >> 6) * 2;
    const uint32_t sbase = (uint32_t)__cvta_generic_to_shared(smem);
    const uint32_t xbase = sbase + 65536;
    bool w_staged = false;
    int t_beg = (int)(((long long)n_tasks * blockIdx.x) / gridDim.x);
    const int t_end = (int)(((long long)n_tasks * (blockIdx.x + 1)) / gridDim.x);
    while (t_beg < t_end) {
        const int tile0 = t_beg >> 1;
        const int t_stop = min(t_end, (tile0 + 2) << 1);
        stage_x_tile(xbase, x, tile0 * 64, N, threadIdx.x, K1_GW * 32);
        if (((t_stop - 1) >> 1) > tile0) stage_x_tile(xbase + 16384, x, tile0 * 64 + 64, N, threadIdx.x, K1_GW * 32);
        if (!w_staged) {
            stage_weight(sbase, w_b, 0, threadIdx.x, K1_GW * 32);
            stage_weight(sbase, w_v, 1, threadIdx.x, K1_GW * 32);
            w_staged = true;
        }
        asm volatile("cp.async.wait_all;" ::: "memory");
        asm volatile("fence.proxy.async.shared::cta;" ::: "memory");
        asm volatile("bar.sync 2, %0;" :: "n"(K1_GW * 32) : "memory");
        for (int task = t_beg + wg; task < t_stop; task += K1_GW / 4) {
            const int tile = task >> 1, hf = task & 1;
            const uint32_t baddr = sbase + hf * 1024;
            const uint64_t descb = (uint64_t)((baddr & 0x3FFFF) >> 4) | ((uint64_t)(2048 >> 4) << 16) |
                                   ((uint64_t)(4096 >> 4) << 32) | ((uint64_t)1 << 62);
            const uint32_t aaddr = xbase + (tile - tile0) * 16384;
            const uint64_t desca = (uint64_t)((aaddr & 0x3FFFF) >> 4) | ((uint64_t)1 << 16) |
                                   ((uint64_t)(1024 >> 4) << 32) | ((uint64_t)1 << 62);
            float d[64];
            asm volatile("wgmma.fence.sync.aligned;" ::: "memory");
            #pragma unroll
            for (int ks = 0; ks < 8; ks++) {
                wgmma_m64n128k16(d, desca + (uint64_t)(((ks >> 2) * 8192 + (ks & 3) * 32) >> 4),
                                 descb + (uint64_t)(ks * (8192 >> 4)), ks > 0 ? 1 : 0);
            }
            asm volatile("wgmma.commit_group.sync.aligned;" ::: "memory");
            asm volatile("wgmma.wait_group.sync.aligned 0;" ::: "memory");
            const int r0 = tile * 64 + (warp & 3) * 16 + (lane >> 2);
            #pragma unroll
            for (int mm = 0; mm < 4; mm++) {
                const int j0 = 2 * mm, j1 = 2 * mm + 1, j2 = 8 + 2 * mm, j3 = 9 + 2 * mm;
                uint4 o0 = make_uint4(pack_bf16(d[4 * j0], d[4 * j0 + 1]), pack_bf16(d[4 * j1], d[4 * j1 + 1]),
                                      pack_bf16(d[4 * j2], d[4 * j2 + 1]), pack_bf16(d[4 * j3], d[4 * j3 + 1]));
                uint4 o1 = make_uint4(pack_bf16(d[4 * j0 + 2], d[4 * j0 + 3]), pack_bf16(d[4 * j1 + 2], d[4 * j1 + 3]),
                                      pack_bf16(d[4 * j2 + 2], d[4 * j2 + 3]), pack_bf16(d[4 * j3 + 2], d[4 * j3 + 3]));
                const int m = 4 * hf + mm;
                if (r0 < N) g_T[(size_t)r0 * 32 + 4 * m + q] = o0;
                if (r0 + 8 < N) g_T[(size_t)(r0 + 8) * 32 + 4 * m + q] = o1;
            }
        }
        t_beg = t_stop;
        if (t_beg < t_end) asm volatile("bar.sync 2, %0;" :: "n"(K1_GW * 32) : "memory");
    }
}

__device__ __forceinline__ void edge_accum(const uint4 v, const float e, const float a[4], const float cc[4],
                                           float num[4], float den[4]) {
    float y0 = fmaf(bf_lo(v.x), -LOG2E, fmaf(e, cc[0], a[0]));
    float y1 = fmaf(bf_hi(v.x), -LOG2E, fmaf(e, cc[1], a[1]));
    float y2 = fmaf(bf_lo(v.y), -LOG2E, fmaf(e, cc[2], a[2]));
    float y3 = fmaf(bf_hi(v.y), -LOG2E, fmaf(e, cc[3], a[3]));
    float s0 = rcp_approx(1.f + ex2_approx(y0));
    float s1 = rcp_approx(1.f + ex2_approx(y1));
    float s2 = rcp_approx(1.f + ex2_approx(y2));
    float s3 = rcp_approx(1.f + ex2_approx(y3));
    den[0] += s0; den[1] += s1; den[2] += s2; den[3] += s3;
    num[0] = fmaf(s0, bf_lo(v.z), num[0]);
    num[1] = fmaf(s1, bf_hi(v.z), num[1]);
    num[2] = fmaf(s2, bf_lo(v.w), num[2]);
    num[3] = fmaf(s3, bf_hi(v.w), num[3]);
}

#define K2_THREADS 1024
#define K2_D 2
#define K2_GS 2
#define K2_RPT ((BINCAP + K2_THREADS - 1) / K2_THREADS)
#define K2_NW (K2_THREADS / 32)
#define SORT_WORDS (BINCAP + 4 * MAXNB)
#define K2_OFF_W 0
#define K2_OFF_X 65536
#define K2_OFF_A (K2_OFF_X + 32768)
#define K2_OFF_U (K2_OFF_A + MAXNB * 256)
#define K2_OFF_PART (K2_OFF_U + MAXNB * 256)
#define K2_OFF_SORT (K2_OFF_PART + K2_NW * 1024)
#define K2_OFF_HIST (K2_OFF_SORT + SORT_WORDS * 4)
#define K2_OFF_OFF (K2_OFF_HIST + MAXNB * 4)
#define K2_DYN_SMEM (K2_OFF_OFF + (MAXNB + 4) * 4)
#define K2_ST (K2_THREADS - 512)
#define K2_SRPT ((BINCAP + K2_ST - 1) / K2_ST)

struct Grp { uint4 v[K2_GS]; };

__device__ __forceinline__ const uint4* row_ptr(const char* Tl, uint32_t rec) {
    return reinterpret_cast<const uint4*>(Tl + (size_t)((rec & 0xffffu) * 512u));
}
__device__ __forceinline__ void grp_load(Grp& g, const uint32_t* sp, const char* Tl) {
    const uint2 t = *reinterpret_cast<const uint2*>(sp);
    g.v[0] = __ldg(row_ptr(Tl, t.x));
    g.v[1] = __ldg(row_ptr(Tl, t.y));
}
__device__ __forceinline__ void grp_consume(const Grp& g, const uint32_t* sp, const float a[4], const float cc[4],
                                            float num[4], float den[4]) {
    const uint2 t = *reinterpret_cast<const uint2*>(sp);
    edge_accum(g.v[0], bf_hi(t.x), a, cc, num, den);
    edge_accum(g.v[1], bf_hi(t.y), a, cc, num, den);
}

__device__ __forceinline__ void load_a(const uint8_t* smem, int ln, int lane, float a[4]) {
    const uint2 av = reinterpret_cast<const uint2*>(smem + K2_OFF_A)[ln * 32 + (lane ^ ((ln & 3) << 2))];
    a[0] = -LOG2E * bf_lo(av.x); a[1] = -LOG2E * bf_hi(av.x); a[2] = -LOG2E * bf_lo(av.y); a[3] = -LOG2E * bf_hi(av.y);
}
__device__ __forceinline__ void write_node(const uint8_t* smem, __nv_bfloat16* out, int ln, int n,
                                           int lane, const float num[4], const float den[4]) {
    const uint2 uv = reinterpret_cast<const uint2*>(smem + K2_OFF_U)[ln * 32 + (lane ^ ((ln & 3) << 2))];
    const int r = ln & 63, c16 = (lane >> 2) * 2;
    const uint8_t* xr = smem + K2_OFF_X + (ln >> 6) * 16384 + (c16 >> 3) * 8192 + r * 128 + (lane & 3) * 4;
    const uint32_t x0 = *reinterpret_cast<const uint32_t*>(xr + (((c16 & 7) ^ (r & 7)) << 4));
    const uint32_t x1 = *reinterpret_cast<const uint32_t*>(xr + ((((c16 + 1) & 7) ^ (r & 7)) << 4));
    const float u4[4] = { bf_lo(uv.x), bf_hi(uv.x), bf_lo(uv.y), bf_hi(uv.y) };
    const float x4[4] = { bf_lo(x0), bf_hi(x0), bf_lo(x1), bf_hi(x1) };
    float o[4];
    #pragma unroll
    for (int i = 0; i < 4; i++) {
        float agg = round_bf16(__fdividef(num[i], den[i] + 1e-6f));
        float z = round_bf16(u4[i] + agg);
        float rz = (z > 0.f) ? z : 0.f * z;
        o[i] = x4[i] + rz;
    }
    uint32_t* o32 = reinterpret_cast<uint32_t*>(out) + (size_t)n * 64 + (lane >> 2) * 8 + (lane & 3);
    o32[0] = pack_bf16(o[0], o[1]); o32[4] = pack_bf16(o[2], o[3]);
}

__device__ __noinline__ void slow_path(const uint8_t* smem, __nv_bfloat16* out, int node0, int nn, int ovf_n,
                                       float c0, float c1, float c2, float c3) {
    const uint32_t* s_sorted = reinterpret_cast<const uint32_t*>(smem + K2_OFF_SORT);
    const int* s_off = reinterpret_cast<const int*>(smem + K2_OFF_OFF);
    const int lane = threadIdx.x & 31, warp = threadIdx.x >> 5;
    const float cc[4] = { c0, c1, c2, c3 };
    const char* Tl = reinterpret_cast<const char*>(g_T) + lane * 16;
    for (int ln = warp; ln < nn; ln += K2_NW) {
        float a[4];
        load_a(smem, ln, lane, a);
        float num[4] = {0.f, 0.f, 0.f, 0.f}, den[4] = {0.f, 0.f, 0.f, 0.f};
        for (int i = s_off[ln]; i < s_off[ln + 1]; i++) {
            const uint32_t r = s_sorted[i];
            edge_accum(__ldg(row_ptr(Tl, r)), bf_hi(r), a, cc, num, den);
        }
        const int n = node0 + ln;
        for (int base = 0; base < ovf_n; base += 64) {
            int i2 = base + 2 * lane;
            int od = (i2 < ovf_n) ? g_ovf[i2] : -1;
            uint32_t orec = (i2 < ovf_n) ? (uint32_t)g_ovf[i2 + 1] : 0u;
            unsigned msk = __ballot_sync(0xffffffffu, od == n);
            while (msk) {
                int l = __ffs(msk) - 1; msk &= msk - 1;
                uint32_t r = __shfl_sync(0xffffffffu, orec, l);
                edge_accum(__ldg(row_ptr(Tl, r)), bf_hi(r), a, cc, num, den);
            }
        }
        write_node(smem, out, ln, n, lane, num, den);
    }
}

__global__ void __launch_bounds__(K2_THREADS, 1) k2_kernel(
    const __nv_bfloat16* __restrict__ x, const __nv_bfloat16* __restrict__ w_a, const __nv_bfloat16* __restrict__ w_u,
    const __nv_bfloat16* __restrict__ w_c, __nv_bfloat16* __restrict__ out, int N, int NB)
{
    extern __shared__ __align__(1024) uint8_t smem[];
    float4* s_part = reinterpret_cast<float4*>(smem + K2_OFF_PART);
    uint32_t* s_sorted = reinterpret_cast<uint32_t*>(smem + K2_OFF_SORT);
    int* s_hist = reinterpret_cast<int*>(smem + K2_OFF_HIST);
    int* s_off = reinterpret_cast<int*>(smem + K2_OFF_OFF);

    const int tid = threadIdx.x;
    const int lane = tid & 31, warp = tid >> 5;
    const int bin = blockIdx.x;
    const int node0 = bin * NB;
    const int nn = min(NB, N - node0);
    const uint32_t sb = (uint32_t)__cvta_generic_to_shared(smem);

    const int fw = (lane >> 2) * 8 + (lane & 3);
    const uint2 wc = make_uint2(__ldg(reinterpret_cast<const uint32_t*>(w_c) + fw), __ldg(reinterpret_cast<const uint32_t*>(w_c) + fw + 4));
    s_part[warp * 64 + lane] = make_float4(0.f, 0.f, 0.f, 0.f);
    s_part[warp * 64 + 32 + lane] = make_float4(0.f, 0.f, 0.f, 0.f);
    if (warp < 16) {
        stage_x_tile(sb + K2_OFF_X, x, node0, N, tid, 512);
        if (nn > 64) stage_x_tile(sb + K2_OFF_X + 16384, x, node0 + 64, N, tid, 512);
        stage_weight(sb + K2_OFF_W, w_a, 0, tid, 512);
        stage_weight(sb + K2_OFF_W, w_u, 1, tid, 512);
        asm volatile("cp.async.wait_all;" ::: "memory");
        asm volatile("fence.proxy.async.shared::cta;" ::: "memory");
        asm volatile("bar.sync 2, 512;" ::: "memory");
        const int wg = warp >> 2, tile = wg >> 1, mtx = wg & 1;
        if (tile * 64 < nn) {
            const uint32_t aaddr = sb + K2_OFF_X + tile * 16384;
            const uint64_t desca = (uint64_t)((aaddr & 0x3FFFF) >> 4) | ((uint64_t)1 << 16) |
                                   ((uint64_t)(1024 >> 4) << 32) | ((uint64_t)1 << 62);
            uint2* dst = reinterpret_cast<uint2*>(smem + (mtx ? K2_OFF_U : K2_OFF_A));
            const int r0 = tile * 64 + (warp & 3) * 16 + (lane >> 2);
            const int sw = (r0 & 3) << 2;
            #pragma unroll 1
            for (int hf = 0; hf < 2; hf++) {
                const uint32_t baddr = sb + K2_OFF_W + (mtx * 2 + hf) * 1024;
                const uint64_t descb = (uint64_t)((baddr & 0x3FFFF) >> 4) | ((uint64_t)(2048 >> 4) << 16) |
                                       ((uint64_t)(4096 >> 4) << 32) | ((uint64_t)1 << 62);
                float d[32];
                asm volatile("wgmma.fence.sync.aligned;" ::: "memory");
                #pragma unroll
                for (int ks = 0; ks < 8; ks++) {
                    wgmma_m64n64k16(d, desca + (uint64_t)(((ks >> 2) * 8192 + (ks & 3) * 32) >> 4),
                                    descb + (uint64_t)(ks * (8192 >> 4)), ks > 0 ? 1 : 0);
                }
                asm volatile("wgmma.commit_group.sync.aligned;" ::: "memory");
                asm volatile("wgmma.wait_group.sync.aligned 0;" ::: "memory");
                #pragma unroll
                for (int mm = 0; mm < 4; mm++) {
                    const int j0 = 2 * mm, j1 = 2 * mm + 1;
                    const int slot = (4 * (4 * hf + mm) + (lane & 3)) ^ sw;
                    dst[r0 * 32 + slot] = make_uint2(pack_bf16(d[4 * j0], d[4 * j0 + 1]), pack_bf16(d[4 * j1], d[4 * j1 + 1]));
                    dst[(r0 + 8) * 32 + slot] = make_uint2(pack_bf16(d[4 * j0 + 2], d[4 * j0 + 3]), pack_bf16(d[4 * j1 + 2], d[4 * j1 + 3]));
                }
            }
        }
        asm volatile("griddepcontrol.wait;" ::: "memory");
    } else {
        const int st = tid - 512;
        if (st < MAXNB) s_hist[st] = 0;
        for (int i = st; i < SORT_WORDS; i += K2_ST) s_sorted[i] = (uint32_t)N;
        asm volatile("bar.sync 1, %0;" :: "n"(K2_ST) : "memory");
        asm volatile("griddepcontrol.wait;" ::: "memory");
        uint2 r[K2_SRPT]; int rk[K2_SRPT];
        const int cnt = min(g_bin_cnt[bin * CNT_STRIDE], BINCAP);
        if (st == 64) s_off[MAXNB + 1] = g_ovf_cnt;
        #pragma unroll
        for (int i = 0; i < K2_SRPT; i++) {
            int idx = i * K2_ST + st;
            if (idx < cnt) r[i] = g_bins[bin * BINCAP + idx];
        }
        #pragma unroll
        for (int i = 0; i < K2_SRPT; i++) {
            int idx = i * K2_ST + st;
            if (idx < cnt) rk[i] = atomicAdd(&s_hist[r[i].y], 1);
        }
        asm volatile("bar.sync 1, %0;" :: "n"(K2_ST) : "memory");
        if (warp == 16) {
            int v[4]; int sum = 0;
            #pragma unroll
            for (int i = 0; i < 4; i++) { v[i] = (s_hist[lane * 4 + i] + K2_GS - 1) & ~(K2_GS - 1); sum += v[i]; }
            int inc = sum;
            #pragma unroll
            for (int o = 1; o < 32; o <<= 1) { int t = __shfl_up_sync(0xffffffffu, inc, o); if (lane >= o) inc += t; }
            int run = inc - sum;
            #pragma unroll
            for (int i = 0; i < 4; i++) { s_off[lane * 4 + i] = run; run += v[i]; }
            if (lane == 31) s_off[MAXNB] = run;
        }
        if (st == 32) g_bin_cnt[bin * CNT_STRIDE] = 0;
        asm volatile("bar.sync 1, %0;" :: "n"(K2_ST) : "memory");
        #pragma unroll
        for (int i = 0; i < K2_SRPT; i++) {
            int idx = i * K2_ST + st;
            if (idx < cnt) s_sorted[s_off[r[i].y] + rk[i]] = r[i].x;
        }
    }
    __syncthreads();
    const float cc[4] = { -LOG2E * bf_lo(wc.x), -LOG2E * bf_hi(wc.x), -LOG2E * bf_lo(wc.y), -LOG2E * bf_hi(wc.y) };
    const int ovf_n = s_off[MAXNB + 1];

    if (ovf_n != 0) {
        slow_path(smem, out, node0, nn, ovf_n, cc[0], cc[1], cc[2], cc[3]);
        __syncthreads();
        if (tid == 0) {
            __threadfence();
            int t = atomicAdd(&g_done, 1);
            if (t == (int)gridDim.x - 1) { g_done = 0; __threadfence(); g_ovf_cnt = 0; }
        }
        return;
    }

    const char* Tl = reinterpret_cast<const char*>(g_T) + lane * 16;
    const int G = s_off[MAXNB] / K2_GS;
    int g = (G * warp) / K2_NW;
    const int g1 = (G * (warp + 1)) / K2_NW;
    int ln;
    {
        int c_lo = 0;
        #pragma unroll
        for (int i = 0; i < 4; i++) {
            int node = i * 32 + lane;
            int o = (node < nn) ? s_off[node] : 0x7fffffff;
            c_lo += __popc(__ballot_sync(0xffffffffu, o < g * K2_GS));
        }
        ln = c_lo;
    }
    bool head = ln > 0;
    if (head) ln--;
    float a[4], num[4] = {0.f, 0.f, 0.f, 0.f}, den[4] = {0.f, 0.f, 0.f, 0.f};
    int node_end;

    auto load_node = [&]() {
        load_a(smem, ln, lane, a);
        node_end = s_off[ln + 1] / K2_GS;
    };
    auto finish_node = [&]() { write_node(smem, out, ln, node0 + ln, lane, num, den); };
    auto close_node = [&]() {
        if (head) {
            s_part[warp * 64 + lane] = make_float4(num[0], num[1], num[2], num[3]);
            s_part[warp * 64 + 32 + lane] = make_float4(den[0], den[1], den[2], den[3]);
            head = false;
        } else {
            finish_node();
        }
        #pragma unroll
        for (int i = 0; i < 4; i++) { num[i] = 0.f; den[i] = 0.f; }
    };

    bool tail = false;
    if (g < g1 || warp == K2_NW - 1) {
        load_node();
        Grp b[K2_D];
        #pragma unroll
        for (int d = 0; d < K2_D; d++)
            if (g + d < g1) grp_load(b[d], s_sorted + K2_GS * (g + d), Tl);
        while (g < g1) {
            #pragma unroll
            for (int d = 0; d < K2_D; d++) {
                if (g < g1) {
                    while (g == node_end) { close_node(); ln++; load_node(); }
                    grp_consume(b[d], s_sorted + K2_GS * g, a, cc, num, den);
                    if (g + K2_D < g1) grp_load(b[d], s_sorted + K2_GS * (g + K2_D), Tl);
                    g++;
                }
            }
        }
        if (warp == K2_NW - 1) {
            while (true) { close_node(); ln++; if (ln >= nn) break; load_node(); }
        } else if (node_end == g1 || head) {
            close_node();
        } else {
            tail = true;
        }
    }
    __syncthreads();
    if (tail) {
        for (int w2 = warp + 1; w2 < K2_NW && (G * w2) / K2_NW < node_end; w2++) {
            const float4 pn = s_part[w2 * 64 + lane], pd = s_part[w2 * 64 + 32 + lane];
            num[0] += pn.x; num[1] += pn.y; num[2] += pn.z; num[3] += pn.w;
            den[0] += pd.x; den[1] += pd.y; den[2] += pd.z; den[3] += pd.w;
        }
        finish_node();
    }
}

extern "C" void kernel_launch(void* const* d_in, const int* in_sizes, int n_in,
                              void* d_out, int out_size) {
    const __nv_bfloat16* x      = (const __nv_bfloat16*)d_in[0];
    const __nv_bfloat16* e_attr = (const __nv_bfloat16*)d_in[1];
    const int* src = (const int*)d_in[2];
    const int* dst = (const int*)d_in[3];
    const __nv_bfloat16* w_a = (const __nv_bfloat16*)d_in[4];
    const __nv_bfloat16* w_b = (const __nv_bfloat16*)d_in[5];
    const __nv_bfloat16* w_c = (const __nv_bfloat16*)d_in[6];
    const __nv_bfloat16* w_u = (const __nv_bfloat16*)d_in[7];
    const __nv_bfloat16* w_v = (const __nv_bfloat16*)d_in[8];
    __nv_bfloat16* out = (__nv_bfloat16*)d_out;
    const int N = in_sizes[0] / D_FEAT;
    const int E = in_sizes[2];
    if (N > MAX_N || 2 * E > MAX_E || N <= 0) return;

    static int num_sms = 0;
    if (num_sms == 0) {
        int dev = 0;
        cudaGetDevice(&dev);
        cudaDeviceGetAttribute(&num_sms, cudaDevAttrMultiProcessorCount, dev);
        if (num_sms <= 0 || num_sms > MAXBINS) num_sms = 132;
        cudaFuncSetAttribute(k1_kernel, cudaFuncAttributeMaxDynamicSharedMemorySize, K1_SMEM);
        cudaFuncSetAttribute(k2_kernel, cudaFuncAttributeMaxDynamicSharedMemorySize, K2_DYN_SMEM);
    }
    cudaStream_t st = cudaStreamPerThread;
    int NB = (N + num_sms - 1) / num_sms;
    if (NB > MAXNB) NB = MAXNB;
    const int nbins = (N + NB - 1) / NB;
    const uint32_t magic = (uint32_t)(((1u << 24) + NB - 1) / NB);
    const int P = num_sms;
    int chunk = (E + P - 1) / P;
    if (chunk > P1_CHUNK) chunk = P1_CHUNK;
    if (chunk < 1) chunk = 1;
    k1_kernel<<<P, K1_THREADS, K1_SMEM, st>>>(x, e_attr, src, dst, w_b, w_v, w_a, w_u, N, E, chunk, NB, nbins, magic);

    cudaLaunchConfig_t cfg = {};
    cfg.gridDim = dim3(nbins);
    cfg.blockDim = dim3(K2_THREADS);
    cfg.dynamicSmemBytes = K2_DYN_SMEM;
    cfg.stream = st;
    cudaLaunchAttribute at[1];
    at[0].id = cudaLaunchAttributeProgrammaticStreamSerialization;
    at[0].val.programmaticStreamSerializationAllowed = 1;
    cfg.attrs = at; cfg.numAttrs = 1;
    cudaLaunchKernelEx(&cfg, k2_kernel, x, w_a, w_u, w_c, out, N, NB);
}
```

```cpp
#include <cuda_runtime.h>
#include <cuda_bf16.h>
#include <stdint.h>

#define D_FEAT 128
#define MAX_N 16384
#define MAX_E (1 << 20)
#define LOG2E 1.4426950408889634f

#define MAXBINS 256
#define MAXNB 128
#define BINCAP 3072
__device__ uint4 g_T[(MAX_N + 1) * 32];
#define CNT_STRIDE 1
__device__ int g_bin_cnt[MAXBINS * CNT_STRIDE];
__device__ uint2 g_bins[MAXBINS * BINCAP];
__device__ int g_ovf[MAX_E];
__device__ int g_ovf_cnt;
__device__ int g_done;

#define TSM(cond, i)
__device__ __forceinline__ float ex2_approx(float x) {
    float y; asm("ex2.approx.ftz.f32 %0, %1;" : "=f"(y) : "f"(x)); return y;
}
__device__ __forceinline__ float rcp_approx(float x) {
    float y; asm("rcp.approx.ftz.f32 %0, %1;" : "=f"(y) : "f"(x)); return y;
}
__device__ __forceinline__ uint32_t pack_bf16(float lo, float hi) {
    __nv_bfloat162 t = __floats2bfloat162_rn(lo, hi);
    return *reinterpret_cast<uint32_t*>(&t);
}
__device__ __forceinline__ float bf_lo(uint32_t v) { return __uint_as_float(v << 16); }
__device__ __forceinline__ float bf_hi(uint32_t v) { return __uint_as_float(v & 0xffff0000u); }
__device__ __forceinline__ float round_bf16(float x) { return __bfloat162float(__float2bfloat16_rn(x)); }

__device__ __forceinline__ void mma_bf16(float c[4], uint32_t a0, uint32_t a1, uint32_t a2, uint32_t a3,
                                         uint32_t b0, uint32_t b1) {
    asm volatile("mma.sync.aligned.m16n8k16.row.col.f32.bf16.bf16.f32 "
                 "{%0,%1,%2,%3}, {%4,%5,%6,%7}, {%8,%9}, {%0,%1,%2,%3};"
                 : "+f"(c[0]), "+f"(c[1]), "+f"(c[2]), "+f"(c[3])
                 : "r"(a0), "r"(a1), "r"(a2), "r"(a3), "r"(b0), "r"(b1));
}
__device__ __forceinline__ void ldmatrix_x4_trans(uint32_t& r0, uint32_t& r1, uint32_t& r2, uint32_t& r3, uint32_t addr) {
    asm volatile("ldmatrix.sync.aligned.m8n8.x4.trans.shared.b16 {%0,%1,%2,%3}, [%4];"
                 : "=r"(r0), "=r"(r1), "=r"(r2), "=r"(r3) : "r"(addr));
}

__device__ __forceinline__ void cp_async16(uint32_t saddr, const void* g) {
    asm volatile("cp.async.cg.shared.global [%0], [%1], 16;" :: "r"(saddr), "l"(g) : "memory");
}
__device__ __forceinline__ void cp_async16_zfill(uint32_t saddr, const void* g, int src_size) {
    asm volatile("cp.async.cg.shared.global [%0], [%1], 16, %2;" :: "r"(saddr), "l"(g), "r"(src_size) : "memory");
}
__device__ __forceinline__ void stage_weight(uint32_t sdst, const __nv_bfloat16* w, int mtx, int tid, int nthreads) {
    const uint4* W = reinterpret_cast<const uint4*>(w);
    for (int u = tid; u < 2048; u += nthreads) {
        int k = u >> 4, c16 = u & 15;
        int kg = k >> 3, rr = k & 7;
        int h = mtx * 2 + (c16 >> 3);
        cp_async16(sdst + kg * 4096 + h * 1024 + rr * 128 + (((c16 & 7) ^ rr) << 4), W + u);
    }
}
__device__ __forceinline__ void stage_x_tile(uint32_t sdst, const __nv_bfloat16* x, int row0, int N, int tid, int nthreads) {
    const uint4* X = reinterpret_cast<const uint4*>(x);
    for (int u = tid; u < 1024; u += nthreads) {
        int r = u >> 4, c16 = u & 15;
        int gr = row0 + r;
        bool ok = gr < N;
        cp_async16_zfill(sdst + (c16 >> 3) * 8192 + r * 128 + (((c16 & 7) ^ (r & 7)) << 4),
                         X + (size_t)(ok ? gr : 0) * 16 + c16, ok ? 16 : 0);
    }
}

__device__ __forceinline__ void wgmma_m64n128k16(float d[64], uint64_t desc_a, uint64_t desc_b, int scale_d) {
    asm volatile("{\n.reg .pred p;\nsetp.ne.b32 p, %66, 0;\n"
                 "wgmma.mma_async.sync.aligned.m64n128k16.f32.bf16.bf16 {%0,%1,%2,%3,%4,%5,%6,%7,%8,%9,%10,%11,%12,%13,%14,%15,%16,%17,%18,%19,%20,%21,%22,%23,%24,%25,%26,%27,%28,%29,%30,%31,%32,%33,%34,%35,%36,%37,%38,%39,%40,%41,%42,%43,%44,%45,%46,%47,%48,%49,%50,%51,%52,%53,%54,%55,%56,%57,%58,%59,%60,%61,%62,%63}, %64, %65, p, 1, 1, 0, 1;\n}"
                 : "+f"(d[0]),"+f"(d[1]),"+f"(d[2]),"+f"(d[3]),"+f"(d[4]),"+f"(d[5]),"+f"(d[6]),"+f"(d[7]),"+f"(d[8]),"+f"(d[9]),"+f"(d[10]),"+f"(d[11]),"+f"(d[12]),"+f"(d[13]),"+f"(d[14]),"+f"(d[15]),"+f"(d[16]),"+f"(d[17]),"+f"(d[18]),"+f"(d[19]),"+f"(d[20]),"+f"(d[21]),"+f"(d[22]),"+f"(d[23]),"+f"(d[24]),"+f"(d[25]),"+f"(d[26]),"+f"(d[27]),"+f"(d[28]),"+f"(d[29]),"+f"(d[30]),"+f"(d[31]),"+f"(d[32]),"+f"(d[33]),"+f"(d[34]),"+f"(d[35]),"+f"(d[36]),"+f"(d[37]),"+f"(d[38]),"+f"(d[39]),"+f"(d[40]),"+f"(d[41]),"+f"(d[42]),"+f"(d[43]),"+f"(d[44]),"+f"(d[45]),"+f"(d[46]),"+f"(d[47]),"+f"(d[48]),"+f"(d[49]),"+f"(d[50]),"+f"(d[51]),"+f"(d[52]),"+f"(d[53]),"+f"(d[54]),"+f"(d[55]),"+f"(d[56]),"+f"(d[57]),"+f"(d[58]),"+f"(d[59]),"+f"(d[60]),"+f"(d[61]),"+f"(d[62]),"+f"(d[63])
                 : "l"(desc_a), "l"(desc_b), "r"(scale_d));
}

__device__ __forceinline__ void wgmma_m64n64k16(float d[32], uint64_t desc_a, uint64_t desc_b, int scale_d) {
    asm volatile("{\n.reg .pred p;\nsetp.ne.b32 p, %34, 0;\n"
                 "wgmma.mma_async.sync.aligned.m64n64k16.f32.bf16.bf16 {%0,%1,%2,%3,%4,%5,%6,%7,%8,%9,%10,%11,%12,%13,%14,%15,%16,%17,%18,%19,%20,%21,%22,%23,%24,%25,%26,%27,%28,%29,%30,%31}, %32, %33, p, 1, 1, 0, 1;\n}"
                 : "+f"(d[0]),"+f"(d[1]),"+f"(d[2]),"+f"(d[3]),"+f"(d[4]),"+f"(d[5]),"+f"(d[6]),"+f"(d[7]),"+f"(d[8]),"+f"(d[9]),"+f"(d[10]),"+f"(d[11]),"+f"(d[12]),"+f"(d[13]),"+f"(d[14]),"+f"(d[15]),"+f"(d[16]),"+f"(d[17]),"+f"(d[18]),"+f"(d[19]),"+f"(d[20]),"+f"(d[21]),"+f"(d[22]),"+f"(d[23]),"+f"(d[24]),"+f"(d[25]),"+f"(d[26]),"+f"(d[27]),"+f"(d[28]),"+f"(d[29]),"+f"(d[30]),"+f"(d[31])
                 : "l"(desc_a), "l"(desc_b), "r"(scale_d));
}

#define K1_GW 12
#define K1_THREADS ((K1_GW + 8) * 32)
#define P1_EPT 10
#define P1_CHUNK (256 * P1_EPT)
#define K1_WBYTES (65536 + 2 * 16384)
#define K1_SMEM (K1_WBYTES + 3 * MAXBINS * 4 + P1_CHUNK * 8)

__device__ __forceinline__ void p1_bar() { asm volatile("bar.sync 1, 256;" ::: "memory"); }

__global__ void __launch_bounds__(K1_THREADS, 1) k1_kernel(
    const __nv_bfloat16* __restrict__ x, const __nv_bfloat16* __restrict__ e_attr,
    const int* __restrict__ src, const int* __restrict__ dst,
    const __nv_bfloat16* __restrict__ w_b, const __nv_bfloat16* __restrict__ w_v,
    const __nv_bfloat16* __restrict__ w_a, const __nv_bfloat16* __restrict__ w_u,
    int N, int E, int chunk, int NB, int nbins, uint32_t magic)
{
    extern __shared__ __align__(1024) uint8_t smem[];
    asm volatile("griddepcontrol.launch_dependents;");
    TSM(threadIdx.x == 0, 0);

    const int warp = threadIdx.x >> 5, lane = threadIdx.x & 31;

    if (warp >= K1_GW) {
        const int tid = threadIdx.x - K1_GW * 32;
        if (blockIdx.x == 0 && tid < 32)
            g_T[(size_t)N * 32 + tid] = make_uint4(0xff80ff80u, 0xff80ff80u, 0u, 0u);
        int* hist = reinterpret_cast<int*>(smem + K1_WBYTES);
        int* loff = hist + MAXBINS;
        int* gbase = loff + MAXBINS;
        uint2* sorted = reinterpret_cast<uint2*>(smem + K1_WBYTES + 3 * MAXBINS * 4);
        for (int beg = blockIdx.x * chunk; beg < E; beg += gridDim.x * chunk) {
            const int end = min(E, beg + chunk);
            int d[P1_EPT]; uint32_t rec[P1_EPT]; int rk[P1_EPT]; int bn[P1_EPT];
            #pragma unroll
            for (int i = 0; i < P1_EPT; i++) {
                int e = beg + i * 256 + tid;
                d[i] = -1;
                if (e < end) {
                    d[i] = __ldg(dst + e);
                    uint32_t s = (uint32_t)__ldg(src + e);
                    uint32_t ev = (uint32_t)__ldg(reinterpret_cast<const unsigned short*>(e_attr) + e);
                    rec[i] = (ev << 16) | s;
                }
            }
            hist[tid] = 0;
            TSM(tid == 0 && d[P1_EPT - 2] != -5 && rec[P1_EPT - 2] != 0xfffffff5u, 14);
            p1_bar();
            #pragma unroll
            for (int i = 0; i < P1_EPT; i++) {
                if (d[i] >= 0) {
                    bn[i] = (int)(((uint64_t)(uint32_t)d[i] * magic) >> 24);
                    rk[i] = atomicAdd(&hist[bn[i]], 1);
                }
            }
            p1_bar();
            TSM(tid == 0, 3);
            {
                int h = hist[tid];
                if (tid < nbins && h > 0) gbase[tid] = atomicAdd(&g_bin_cnt[tid * CNT_STRIDE], h);
                if (tid < 32) {
                    int v[8]; int sum = 0;
                    #pragma unroll
                    for (int i = 0; i < 8; i++) { v[i] = hist[lane * 8 + i]; sum += v[i]; }
                    int inc = sum;
                    #pragma unroll
                    for (int o = 1; o < 32; o <<= 1) { int t = __shfl_up_sync(0xffffffffu, inc, o); if (lane >= o) inc += t; }
                    int run = inc - sum;
                    #pragma unroll
                    for (int i = 0; i < 8; i++) { loff[lane * 8 + i] = run; run += v[i]; }
                }
            }
            p1_bar();
            #pragma unroll
            for (int i = 0; i < P1_EPT; i++) {
                if (d[i] >= 0) sorted[loff[bn[i]] + rk[i]] = make_uint2(rec[i], (uint32_t)d[i]);
            }
            p1_bar();
            const int cnt = end - beg;
            for (int i = tid; i < cnt; i += 256) {
                uint2 r = sorted[i];
                int b = (int)(((uint64_t)r.y * magic) >> 24);
                int pos = gbase[b] + (i - loff[b]);
                if (pos < BINCAP) {
                    g_bins[b * BINCAP + pos] = make_uint2(r.x, r.y - (uint32_t)(b * NB));
                } else {
                    int p = atomicAdd(&g_ovf_cnt, 2);
                    g_ovf[p] = (int)r.y; g_ovf[p + 1] = (int)r.x;
                }
            }
            p1_bar();
        }
        TSM(tid == 0, 4);
        return;
    }

    if (blockIdx.x < 4 && threadIdx.x < 128) {
        const char* pw = reinterpret_cast<const char*>((blockIdx.x & 2) ? w_u : w_a) + (blockIdx.x & 1) * 16384 + threadIdx.x * 128;
        asm volatile("prefetch.global.L2 [%0];" :: "l"(pw));
    }
    const int q = lane & 3;
    const int wg = warp >> 2;
    const int n_tasks = ((N + 63) >> 6) * 2;
    const uint32_t sbase = (uint32_t)__cvta_generic_to_shared(smem);
    const uint32_t xbase = sbase + 65536;
    bool w_staged = false;
    int t_beg = (int)(((long long)n_tasks * blockIdx.x) / gridDim.x);
    const int t_end = (int)(((long long)n_tasks * (blockIdx.x + 1)) / gridDim.x);
    while (t_beg < t_end) {
        const int tile0 = t_beg >> 1;
        const int t_stop = min(t_end, (tile0 + 2) << 1);
        stage_x_tile(xbase, x, tile0 * 64, N, threadIdx.x, K1_GW * 32);
        if (((t_stop - 1) >> 1) > tile0) stage_x_tile(xbase + 16384, x, tile0 * 64 + 64, N, threadIdx.x, K1_GW * 32);
        if (!w_staged) {
            stage_weight(sbase, w_b, 0, threadIdx.x, K1_GW * 32);
            stage_weight(sbase, w_v, 1, threadIdx.x, K1_GW * 32);
            w_staged = true;
        }
        asm volatile("cp.async.wait_all;" ::: "memory");
        asm volatile("fence.proxy.async.shared::cta;" ::: "memory");
        asm volatile("bar.sync 2, %0;" :: "n"(K1_GW * 32) : "memory");
        TSM(threadIdx.x == 0, 1);
        for (int task = t_beg + wg; task < t_stop; task += K1_GW / 4) {
            const int tile = task >> 1, hf = task & 1;
            const uint32_t baddr = sbase + hf * 1024;
            const uint64_t descb = (uint64_t)((baddr & 0x3FFFF) >> 4) | ((uint64_t)(2048 >> 4) << 16) |
                                   ((uint64_t)(4096 >> 4) << 32) | ((uint64_t)1 << 62);
            const uint32_t aaddr = xbase + (tile - tile0) * 16384;
            const uint64_t desca = (uint64_t)((aaddr & 0x3FFFF) >> 4) | ((uint64_t)1 << 16) |
                                   ((uint64_t)(1024 >> 4) << 32) | ((uint64_t)1 << 62);
            float d[64];
            asm volatile("wgmma.fence.sync.aligned;" ::: "memory");
            #pragma unroll
            for (int ks = 0; ks < 8; ks++) {
                wgmma_m64n128k16(d, desca + (uint64_t)(((ks >> 2) * 8192 + (ks & 3) * 32) >> 4),
                                 descb + (uint64_t)(ks * (8192 >> 4)), ks > 0 ? 1 : 0);
            }
            asm volatile("wgmma.commit_group.sync.aligned;" ::: "memory");
            asm volatile("wgmma.wait_group.sync.aligned 0;" ::: "memory");
            TSM(threadIdx.x == 0, 13);
            const int r0 = tile * 64 + (warp & 3) * 16 + (lane >> 2);
            #pragma unroll
            for (int mm = 0; mm < 4; mm++) {
                const int j0 = 2 * mm, j1 = 2 * mm + 1, j2 = 8 + 2 * mm, j3 = 9 + 2 * mm;
                uint4 o0 = make_uint4(pack_bf16(d[4 * j0], d[4 * j0 + 1]), pack_bf16(d[4 * j1], d[4 * j1 + 1]),
                                      pack_bf16(d[4 * j2], d[4 * j2 + 1]), pack_bf16(d[4 * j3], d[4 * j3 + 1]));
                uint4 o1 = make_uint4(pack_bf16(d[4 * j0 + 2], d[4 * j0 + 3]), pack_bf16(d[4 * j1 + 2], d[4 * j1 + 3]),
                                      pack_bf16(d[4 * j2 + 2], d[4 * j2 + 3]), pack_bf16(d[4 * j3 + 2], d[4 * j3 + 3]));
                const int m = 4 * hf + mm;
                if (r0 < N) g_T[(size_t)r0 * 32 + 4 * m + q] = o0;
                if (r0 + 8 < N) g_T[(size_t)(r0 + 8) * 32 + 4 * m + q] = o1;
            }
        }
        t_beg = t_stop;
        if (t_beg < t_end) asm volatile("bar.sync 2, %0;" :: "n"(K1_GW * 32) : "memory");
    }
    TSM(threadIdx.x == 0, 2);
}

__device__ __forceinline__ void edge_accum(const uint4 v, const float e, const float a[4], const float cc[4],
                                           float num[4], float den[4]) {
    float y0 = fmaf(bf_lo(v.x), -LOG2E, fmaf(e, cc[0], a[0]));
    float y1 = fmaf(bf_hi(v.x), -LOG2E, fmaf(e, cc[1], a[1]));
    float y2 = fmaf(bf_lo(v.y), -LOG2E, fmaf(e, cc[2], a[2]));
    float y3 = fmaf(bf_hi(v.y), -LOG2E, fmaf(e, cc[3], a[3]));
    float s0 = rcp_approx(1.f + ex2_approx(y0));
    float s1 = rcp_approx(1.f + ex2_approx(y1));
    float s2 = rcp_approx(1.f + ex2_approx(y2));
    float s3 = rcp_approx(1.f + ex2_approx(y3));
    den[0] += s0; den[1] += s1; den[2] += s2; den[3] += s3;
    num[0] = fmaf(s0, bf_lo(v.z), num[0]);
    num[1] = fmaf(s1, bf_hi(v.z), num[1]);
    num[2] = fmaf(s2, bf_lo(v.w), num[2]);
    num[3] = fmaf(s3, bf_hi(v.w), num[3]);
}

#define K2_THREADS 1024
#define K2_D 2
#define K2_GS 2
#define K2_RPT ((BINCAP + K2_THREADS - 1) / K2_THREADS)
#define K2_NW (K2_THREADS / 32)
#define SORT_WORDS (BINCAP + 4 * MAXNB)
#define K2_OFF_W 0
#define K2_OFF_X 65536
#define K2_OFF_A (K2_OFF_X + 32768)
#define K2_OFF_U (K2_OFF_A + MAXNB * 256)
#define K2_OFF_PART (K2_OFF_U + MAXNB * 256)
#define K2_OFF_SORT (K2_OFF_PART + K2_NW * 1024)
#define K2_OFF_HIST (K2_OFF_SORT + SORT_WORDS * 4)
#define K2_OFF_OFF (K2_OFF_HIST + MAXNB * 4)
#define K2_DYN_SMEM (K2_OFF_OFF + (MAXNB + 4) * 4)
#define K2_ST (K2_THREADS - 512)
#define K2_SRPT ((BINCAP + K2_ST - 1) / K2_ST)

struct Grp { uint4 v[K2_GS]; };

__device__ __forceinline__ const uint4* row_ptr(const char* Tl, uint32_t rec) {
    return reinterpret_cast<const uint4*>(Tl + (size_t)((rec & 0xffffu) * 512u));
}
__device__ __forceinline__ void grp_load(Grp& g, const uint32_t* sp, const char* Tl) {
    const uint2 t = *reinterpret_cast<const uint2*>(sp);
    g.v[0] = __ldg(row_ptr(Tl, t.x));
    g.v[1] = __ldg(row_ptr(Tl, t.y));
}
__device__ __forceinline__ void grp_consume(const Grp& g, const uint32_t* sp, const float a[4], const float cc[4],
                                            float num[4], float den[4]) {
    const uint2 t = *reinterpret_cast<const uint2*>(sp);
    edge_accum(g.v[0], bf_hi(t.x), a, cc, num, den);
    edge_accum(g.v[1], bf_hi(t.y), a, cc, num, den);
}

__device__ __forceinline__ void load_a(const uint8_t* smem, int ln, int lane, float a[4]) {
    const uint2 av = reinterpret_cast<const uint2*>(smem + K2_OFF_A)[ln * 32 + (lane ^ ((ln & 3) << 2))];
    a[0] = -LOG2E * bf_lo(av.x); a[1] = -LOG2E * bf_hi(av.x); a[2] = -LOG2E * bf_lo(av.y); a[3] = -LOG2E * bf_hi(av.y);
}
__device__ __forceinline__ void write_node(const uint8_t* smem, __nv_bfloat16* out, int ln, int n,
                                           int lane, const float num[4], const float den[4]) {
    const uint2 uv = reinterpret_cast<const uint2*>(smem + K2_OFF_U)[ln * 32 + (lane ^ ((ln & 3) << 2))];
    const int r = ln & 63, c16 = (lane >> 2) * 2;
    const uint8_t* xr = smem + K2_OFF_X + (ln >> 6) * 16384 + (c16 >> 3) * 8192 + r * 128 + (lane & 3) * 4;
    const uint32_t x0 = *reinterpret_cast<const uint32_t*>(xr + (((c16 & 7) ^ (r & 7)) << 4));
    const uint32_t x1 = *reinterpret_cast<const uint32_t*>(xr + ((((c16 + 1) & 7) ^ (r & 7)) << 4));
    const float u4[4] = { bf_lo(uv.x), bf_hi(uv.x), bf_lo(uv.y), bf_hi(uv.y) };
    const float x4[4] = { bf_lo(x0), bf_hi(x0), bf_lo(x1), bf_hi(x1) };
    float o[4];
    #pragma unroll
    for (int i = 0; i < 4; i++) {
        float agg = round_bf16(__fdividef(num[i], den[i] + 1e-6f));
        float z = round_bf16(u4[i] + agg);
        float rz = (z > 0.f) ? z : 0.f * z;
        o[i] = x4[i] + rz;
    }
    uint32_t* o32 = reinterpret_cast<uint32_t*>(out) + (size_t)n * 64 + (lane >> 2) * 8 + (lane & 3);
    o32[0] = pack_bf16(o[0], o[1]); o32[4] = pack_bf16(o[2], o[3]);
}

__device__ __noinline__ void slow_path(const uint8_t* smem, __nv_bfloat16* out, int node0, int nn, int ovf_n,
                                       float c0, float c1, float c2, float c3) {
    const uint32_t* s_sorted = reinterpret_cast<const uint32_t*>(smem + K2_OFF_SORT);
    const int* s_off = reinterpret_cast<const int*>(smem + K2_OFF_OFF);
    const int lane = threadIdx.x & 31, warp = threadIdx.x >> 5;
    const float cc[4] = { c0, c1, c2, c3 };
    const char* Tl = reinterpret_cast<const char*>(g_T) + lane * 16;
    for (int ln = warp; ln < nn; ln += K2_NW) {
        float a[4];
        load_a(smem, ln, lane, a);
        float num[4] = {0.f, 0.f, 0.f, 0.f}, den[4] = {0.f, 0.f, 0.f, 0.f};
        for (int i = s_off[ln]; i < s_off[ln + 1]; i++) {
            const uint32_t r = s_sorted[i];
            edge_accum(__ldg(row_ptr(Tl, r)), bf_hi(r), a, cc, num, den);
        }
        const int n = node0 + ln;
        for (int base = 0; base < ovf_n; base += 64) {
            int i2 = base + 2 * lane;
            int od = (i2 < ovf_n) ? g_ovf[i2] : -1;
            uint32_t orec = (i2 < ovf_n) ? (uint32_t)g_ovf[i2 + 1] : 0u;
            unsigned msk = __ballot_sync(0xffffffffu, od == n);
            while (msk) {
                int l = __ffs(msk) - 1; msk &= msk - 1;
                uint32_t r = __shfl_sync(0xffffffffu, orec, l);
                edge_accum(__ldg(row_ptr(Tl, r)), bf_hi(r), a, cc, num, den);
            }
        }
        write_node(smem, out, ln, n, lane, num, den);
    }
}

__global__ void __launch_bounds__(K2_THREADS, 1) k2_kernel(
    const __nv_bfloat16* __restrict__ x, const __nv_bfloat16* __restrict__ w_a, const __nv_bfloat16* __restrict__ w_u,
    const __nv_bfloat16* __restrict__ w_c, __nv_bfloat16* __restrict__ out, int N, int NB)
{
    extern __shared__ __align__(1024) uint8_t smem[];
    float4* s_part = reinterpret_cast<float4*>(smem + K2_OFF_PART);
    uint32_t* s_sorted = reinterpret_cast<uint32_t*>(smem + K2_OFF_SORT);
    int* s_hist = reinterpret_cast<int*>(smem + K2_OFF_HIST);
    int* s_off = reinterpret_cast<int*>(smem + K2_OFF_OFF);

    const int tid = threadIdx.x;
    const int lane = tid & 31, warp = tid >> 5;
    const int bin = blockIdx.x;
    const int node0 = bin * NB;
    const int nn = min(NB, N - node0);
    const uint32_t sb = (uint32_t)__cvta_generic_to_shared(smem);
    TSM(tid == 0, 5);

    const int fw = (lane >> 2) * 8 + (lane & 3);
    const uint2 wc = make_uint2(__ldg(reinterpret_cast<const uint32_t*>(w_c) + fw), __ldg(reinterpret_cast<const uint32_t*>(w_c) + fw + 4));
    s_part[warp * 64 + lane] = make_float4(0.f, 0.f, 0.f, 0.f);
    s_part[warp * 64 + 32 + lane] = make_float4(0.f, 0.f, 0.f, 0.f);
    if (warp < 16) {
        stage_x_tile(sb + K2_OFF_X, x, node0, N, tid, 512);
        if (nn > 64) stage_x_tile(sb + K2_OFF_X + 16384, x, node0 + 64, N, tid, 512);
        stage_weight(sb + K2_OFF_W, w_a, 0, tid, 512);
        stage_weight(sb + K2_OFF_W, w_u, 1, tid, 512);
        asm volatile("cp.async.wait_all;" ::: "memory");
        asm volatile("fence.proxy.async.shared::cta;" ::: "memory");
        asm volatile("bar.sync 2, 512;" ::: "memory");
        TSM(tid == 0, 6);
        const int wg = warp >> 2, tile = wg >> 1, mtx = wg & 1;
        if (tile * 64 < nn) {
            const uint32_t aaddr = sb + K2_OFF_X + tile * 16384;
            const uint64_t desca = (uint64_t)((aaddr & 0x3FFFF) >> 4) | ((uint64_t)1 << 16) |
                                   ((uint64_t)(1024 >> 4) << 32) | ((uint64_t)1 << 62);
            uint2* dst = reinterpret_cast<uint2*>(smem + (mtx ? K2_OFF_U : K2_OFF_A));
            const int r0 = tile * 64 + (warp & 3) * 16 + (lane >> 2);
            const int sw = (r0 & 3) << 2;
            #pragma unroll 1
            for (int hf = 0; hf < 2; hf++) {
                const uint32_t baddr = sb + K2_OFF_W + (mtx * 2 + hf) * 1024;
                const uint64_t descb = (uint64_t)((baddr & 0x3FFFF) >> 4) | ((uint64_t)(2048 >> 4) << 16) |
                                       ((uint64_t)(4096 >> 4) << 32) | ((uint64_t)1 << 62);
                float d[32];
                asm volatile("wgmma.fence.sync.aligned;" ::: "memory");
                #pragma unroll
                for (int ks = 0; ks < 8; ks++) {
                    wgmma_m64n64k16(d, desca + (uint64_t)(((ks >> 2) * 8192 + (ks & 3) * 32) >> 4),
                                    descb + (uint64_t)(ks * (8192 >> 4)), ks > 0 ? 1 : 0);
                }
                asm volatile("wgmma.commit_group.sync.aligned;" ::: "memory");
                asm volatile("wgmma.wait_group.sync.aligned 0;" ::: "memory");
                TSM(tid == 0 && hf == 0, 15);
                #pragma unroll
                for (int mm = 0; mm < 4; mm++) {
                    const int j0 = 2 * mm, j1 = 2 * mm + 1;
                    const int slot = (4 * (4 * hf + mm) + (lane & 3)) ^ sw;
                    dst[r0 * 32 + slot] = make_uint2(pack_bf16(d[4 * j0], d[4 * j0 + 1]), pack_bf16(d[4 * j1], d[4 * j1 + 1]));
                    dst[(r0 + 8) * 32 + slot] = make_uint2(pack_bf16(d[4 * j0 + 2], d[4 * j0 + 3]), pack_bf16(d[4 * j1 + 2], d[4 * j1 + 3]));
                }
            }
        }
        TSM(tid == 0, 7);
        asm volatile("griddepcontrol.wait;" ::: "memory");
    } else {
        const int st = tid - 512;
        if (st < MAXNB) s_hist[st] = 0;
        for (int i = st; i < SORT_WORDS; i += K2_ST) s_sorted[i] = (uint32_t)N;
        asm volatile("bar.sync 1, %0;" :: "n"(K2_ST) : "memory");
        asm volatile("griddepcontrol.wait;" ::: "memory");
        TSM(st == 0, 8);
        uint2 r[K2_SRPT]; int rk[K2_SRPT];
        const int cnt = min(g_bin_cnt[bin * CNT_STRIDE], BINCAP);
        if (st == 64) s_off[MAXNB + 1] = g_ovf_cnt;
        #pragma unroll
        for (int i = 0; i < K2_SRPT; i++) {
            int idx = i * K2_ST + st;
            if (idx < cnt) r[i] = g_bins[bin * BINCAP + idx];
        }
        #pragma unroll
        for (int i = 0; i < K2_SRPT; i++) {
            int idx = i * K2_ST + st;
            if (idx < cnt) rk[i] = atomicAdd(&s_hist[r[i].y], 1);
        }
        asm volatile("bar.sync 1, %0;" :: "n"(K2_ST) : "memory");
        if (warp == 16) {
            int v[4]; int sum = 0;
            #pragma unroll
            for (int i = 0; i < 4; i++) { v[i] = (s_hist[lane * 4 + i] + K2_GS - 1) & ~(K2_GS - 1); sum += v[i]; }
            int inc = sum;
            #pragma unroll
            for (int o = 1; o < 32; o <<= 1) { int t = __shfl_up_sync(0xffffffffu, inc, o); if (lane >= o) inc += t; }
            int run = inc - sum;
            #pragma unroll
            for (int i = 0; i < 4; i++) { s_off[lane * 4 + i] = run; run += v[i]; }
            if (lane == 31) s_off[MAXNB] = run;
        }
        if (st == 32) g_bin_cnt[bin * CNT_STRIDE] = 0;
        asm volatile("bar.sync 1, %0;" :: "n"(K2_ST) : "memory");
        #pragma unroll
        for (int i = 0; i < K2_SRPT; i++) {
            int idx = i * K2_ST + st;
            if (idx < cnt) s_sorted[s_off[r[i].y] + rk[i]] = r[i].x;
        }
        TSM(st == 0, 9);
    }
    __syncthreads();
    TSM(tid == 0, 10);
    const float cc[4] = { -LOG2E * bf_lo(wc.x), -LOG2E * bf_hi(wc.x), -LOG2E * bf_lo(wc.y), -LOG2E * bf_hi(wc.y) };
    const int ovf_n = s_off[MAXNB + 1];

    if (ovf_n != 0) {
        slow_path(smem, out, node0, nn, ovf_n, cc[0], cc[1], cc[2], cc[3]);
        __syncthreads();
        if (tid == 0) {
            __threadfence();
            int t = atomicAdd(&g_done, 1);
            if (t == (int)gridDim.x - 1) { g_done = 0; __threadfence(); g_ovf_cnt = 0; }
        }
        return;
    }

    const char* Tl = reinterpret_cast<const char*>(g_T) + lane * 16;
    const int G = s_off[MAXNB] / K2_GS;
    int g = (G * warp) / K2_NW;
    const int g1 = (G * (warp + 1)) / K2_NW;
    int ln;
    {
        int c_lo = 0;
        #pragma unroll
        for (int i = 0; i < 4; i++) {
            int node = i * 32 + lane;
            int o = (node < nn) ? s_off[node] : 0x7fffffff;
            c_lo += __popc(__ballot_sync(0xffffffffu, o < g * K2_GS));
        }
        ln = c_lo;
    }
    bool head = ln > 0;
    if (head) ln--;
    float a[4], num[4] = {0.f, 0.f, 0.f, 0.f}, den[4] = {0.f, 0.f, 0.f, 0.f};
    int node_end;

    auto load_node = [&]() {
        load_a(smem, ln, lane, a);
        node_end = s_off[ln + 1] / K2_GS;
    };
    auto finish_node = [&]() { write_node(smem, out, ln, node0 + ln, lane, num, den); };
    auto close_node = [&]() {
        if (head) {
            s_part[warp * 64 + lane] = make_float4(num[0], num[1], num[2], num[3]);
            s_part[warp * 64 + 32 + lane] = make_float4(den[0], den[1], den[2], den[3]);
            head = false;
        } else {
            finish_node();
        }
        #pragma unroll
        for (int i = 0; i < 4; i++) { num[i] = 0.f; den[i] = 0.f; }
    };

    bool tail = false;
    if (g < g1 || warp == K2_NW - 1) {
        load_node();
        Grp b[K2_D];
        #pragma unroll
        for (int d = 0; d < K2_D; d++)
            if (g + d < g1) grp_load(b[d], s_sorted + K2_GS * (g + d), Tl);
        while (g < g1) {
            #pragma unroll
            for (int d = 0; d < K2_D; d++) {
                if (g < g1) {
                    while (g == node_end) { close_node(); ln++; load_node(); }
                    grp_consume(b[d], s_sorted + K2_GS * g, a, cc, num, den);
                    if (g + K2_D < g1) grp_load(b[d], s_sorted + K2_GS * (g + K2_D), Tl);
                    g++;
                }
            }
        }
        if (warp == K2_NW - 1) {
            while (true) { close_node(); ln++; if (ln >= nn) break; load_node(); }
        } else if (node_end == g1 || head) {
            close_node();
        } else {
            tail = true;
        }
    }
    TSM(tid == 0, 11);
    __syncthreads();
    TSM(tid == 0, 12);
    if (tail) {
        for (int w2 = warp + 1; w2 < K2_NW && (G * w2) / K2_NW < node_end; w2++) {
            const float4 pn = s_part[w2 * 64 + lane], pd = s_part[w2 * 64 + 32 + lane];
            num[0] += pn.x; num[1] += pn.y; num[2] += pn.z; num[3] += pn.w;
            den[0] += pd.x; den[1] += pd.y; den[2] += pd.z; den[3] += pd.w;
        }
        finish_node();
    }
}

extern "C" void kernel_launch(void* const* d_in, const int* in_sizes, int n_in,
                              void* d_out, int out_size) {
    const __nv_bfloat16* x      = (const __nv_bfloat16*)d_in[0];
    const __nv_bfloat16* e_attr = (const __nv_bfloat16*)d_in[1];
    const int* src = (const int*)d_in[2];
    const int* dst = (const int*)d_in[3];
    const __nv_bfloat16* w_a = (const __nv_bfloat16*)d_in[4];
    const __nv_bfloat16* w_b = (const __nv_bfloat16*)d_in[5];
    const __nv_bfloat16* w_c = (const __nv_bfloat16*)d_in[6];
    const __nv_bfloat16* w_u = (const __nv_bfloat16*)d_in[7];
    const __nv_bfloat16* w_v = (const __nv_bfloat16*)d_in[8];
    __nv_bfloat16* out = (__nv_bfloat16*)d_out;
    const int N = in_sizes[0] / D_FEAT;
    const int E = in_sizes[2];
    if (N > MAX_N || 2 * E > MAX_E || N <= 0) return;

    static int num_sms = 0;
    if (num_sms == 0) {
        int dev = 0;
        cudaGetDevice(&dev);
        cudaDeviceGetAttribute(&num_sms, cudaDevAttrMultiProcessorCount, dev);
        if (num_sms <= 0 || num_sms > MAXBINS) num_sms = 132;
        cudaFuncSetAttribute(k1_kernel, cudaFuncAttributeMaxDynamicSharedMemorySize, K1_SMEM);
        cudaFuncSetAttribute(k2_kernel, cudaFuncAttributeMaxDynamicSharedMemorySize, K2_DYN_SMEM);
    }
    cudaStream_t st = cudaStreamPerThread;
    int NB = (N + num_sms - 1) / num_sms;
    if (NB > MAXNB) NB = MAXNB;
    const int nbins = (N + NB - 1) / NB;
    const uint32_t magic = (uint32_t)(((1u << 24) + NB - 1) / NB);
    const int P = num_sms;
    int chunk = (E + P - 1) / P;
    if (chunk > P1_CHUNK) chunk = P1_CHUNK;
    if (chunk < 1) chunk = 1;
    k1_kernel<<<P, K1_THREADS, K1_SMEM, st>>>(x, e_attr, src, dst, w_b, w_v, w_a, w_u, N, E, chunk, NB, nbins, magic);

    cudaLaunchConfig_t cfg = {};
    cfg.gridDim = dim3(nbins);
    cfg.blockDim = dim3(K2_THREADS);
    cfg.dynamicSmemBytes = K2_DYN_SMEM;
    cfg.stream = st;
    cudaLaunchAttribute at[1];
    at[0].id = cudaLaunchAttributeProgrammaticStreamSerialization;
    at[0].val.programmaticStreamSerializationAllowed = 1;
    cfg.attrs = at; cfg.numAttrs = 1;
    cudaLaunchKernelEx(&cfg, k2_kernel, x, w_a, w_u, w_c, out, N, NB);
}
```

```cpp
#include <cuda_runtime.h>
#include <cuda_bf16.h>
#include <stdint.h>

#define D_FEAT 128
#define MAX_N 16384
#define MAX_E (1 << 20)
#define LOG2E 1.4426950408889634f

#define MAXBINS 256
#define MAXNB 128
#define BINCAP 3072
__device__ uint4 g_AU[MAX_N * 32];
__device__ uint4 g_T[(MAX_N + 1) * 32];
#define CNT_STRIDE 1
__device__ int g_bin_cnt[MAXBINS * CNT_STRIDE];
__device__ uint2 g_bins[MAXBINS * BINCAP];
__device__ int g_ovf[MAX_E];
__device__ int g_ovf_cnt;
__device__ int g_done;

#define TSM(cond, i)
__device__ __forceinline__ float ex2_approx(float x) {
    float y; asm("ex2.approx.ftz.f32 %0, %1;" : "=f"(y) : "f"(x)); return y;
}
__device__ __forceinline__ float rcp_approx(float x) {
    float y; asm("rcp.approx.ftz.f32 %0, %1;" : "=f"(y) : "f"(x)); return y;
}
__device__ __forceinline__ uint32_t pack_bf16(float lo, float hi) {
    __nv_bfloat162 t = __floats2bfloat162_rn(lo, hi);
    return *reinterpret_cast<uint32_t*>(&t);
}
__device__ __forceinline__ float bf_lo(uint32_t v) { return __uint_as_float(v << 16); }
__device__ __forceinline__ float bf_hi(uint32_t v) { return __uint_as_float(v & 0xffff0000u); }
__device__ __forceinline__ float round_bf16(float x) { return __bfloat162float(__float2bfloat16_rn(x)); }

__device__ __forceinline__ void mma_bf16(float c[4], uint32_t a0, uint32_t a1, uint32_t a2, uint32_t a3,
                                         uint32_t b0, uint32_t b1) {
    asm volatile("mma.sync.aligned.m16n8k16.row.col.f32.bf16.bf16.f32 "
                 "{%0,%1,%2,%3}, {%4,%5,%6,%7}, {%8,%9}, {%0,%1,%2,%3};"
                 : "+f"(c[0]), "+f"(c[1]), "+f"(c[2]), "+f"(c[3])
                 : "r"(a0), "r"(a1), "r"(a2), "r"(a3), "r"(b0), "r"(b1));
}
__device__ __forceinline__ void ldmatrix_x4_trans(uint32_t& r0, uint32_t& r1, uint32_t& r2, uint32_t& r3, uint32_t addr) {
    asm volatile("ldmatrix.sync.aligned.m8n8.x4.trans.shared.b16 {%0,%1,%2,%3}, [%4];"
                 : "=r"(r0), "=r"(r1), "=r"(r2), "=r"(r3) : "r"(addr));
}

__device__ __forceinline__ void cp_async16(uint32_t saddr, const void* g) {
    asm volatile("cp.async.cg.shared.global [%0], [%1], 16;" :: "r"(saddr), "l"(g) : "memory");
}
__device__ __forceinline__ void cp_async16_zfill(uint32_t saddr, const void* g, int src_size) {
    asm volatile("cp.async.cg.shared.global [%0], [%1], 16, %2;" :: "r"(saddr), "l"(g), "r"(src_size) : "memory");
}
__device__ __forceinline__ void stage_weight(uint32_t sdst, const __nv_bfloat16* w, int mtx, int tid, int nthreads) {
    const uint4* W = reinterpret_cast<const uint4*>(w);
    for (int u = tid; u < 2048; u += nthreads) {
        int k = u >> 4, c16 = u & 15;
        int kg = k >> 3, rr = k & 7;
        int h = mtx * 2 + (c16 >> 3);
        cp_async16(sdst + kg * 4096 + h * 1024 + rr * 128 + (((c16 & 7) ^ rr) << 4), W + u);
    }
}
__device__ __forceinline__ void stage_x_tile(uint32_t sdst, const __nv_bfloat16* x, int row0, int N, int tid, int nthreads) {
    const uint4* X = reinterpret_cast<const uint4*>(x);
    for (int u = tid; u < 1024; u += nthreads) {
        int r = u >> 4, c16 = u & 15;
        int gr = row0 + r;
        bool ok = gr < N;
        cp_async16_zfill(sdst + (c16 >> 3) * 8192 + r * 128 + (((c16 & 7) ^ (r & 7)) << 4),
                         X + (size_t)(ok ? gr : 0) * 16 + c16, ok ? 16 : 0);
    }
}

__device__ __forceinline__ void wgmma_m64n128k16(float d[64], uint64_t desc_a, uint64_t desc_b, int scale_d) {
    asm volatile("{\n.reg .pred p;\nsetp.ne.b32 p, %66, 0;\n"
                 "wgmma.mma_async.sync.aligned.m64n128k16.f32.bf16.bf16 {%0,%1,%2,%3,%4,%5,%6,%7,%8,%9,%10,%11,%12,%13,%14,%15,%16,%17,%18,%19,%20,%21,%22,%23,%24,%25,%26,%27,%28,%29,%30,%31,%32,%33,%34,%35,%36,%37,%38,%39,%40,%41,%42,%43,%44,%45,%46,%47,%48,%49,%50,%51,%52,%53,%54,%55,%56,%57,%58,%59,%60,%61,%62,%63}, %64, %65, p, 1, 1, 0, 1;\n}"
                 : "+f"(d[0]),"+f"(d[1]),"+f"(d[2]),"+f"(d[3]),"+f"(d[4]),"+f"(d[5]),"+f"(d[6]),"+f"(d[7]),"+f"(d[8]),"+f"(d[9]),"+f"(d[10]),"+f"(d[11]),"+f"(d[12]),"+f"(d[13]),"+f"(d[14]),"+f"(d[15]),"+f"(d[16]),"+f"(d[17]),"+f"(d[18]),"+f"(d[19]),"+f"(d[20]),"+f"(d[21]),"+f"(d[22]),"+f"(d[23]),"+f"(d[24]),"+f"(d[25]),"+f"(d[26]),"+f"(d[27]),"+f"(d[28]),"+f"(d[29]),"+f"(d[30]),"+f"(d[31]),"+f"(d[32]),"+f"(d[33]),"+f"(d[34]),"+f"(d[35]),"+f"(d[36]),"+f"(d[37]),"+f"(d[38]),"+f"(d[39]),"+f"(d[40]),"+f"(d[41]),"+f"(d[42]),"+f"(d[43]),"+f"(d[44]),"+f"(d[45]),"+f"(d[46]),"+f"(d[47]),"+f"(d[48]),"+f"(d[49]),"+f"(d[50]),"+f"(d[51]),"+f"(d[52]),"+f"(d[53]),"+f"(d[54]),"+f"(d[55]),"+f"(d[56]),"+f"(d[57]),"+f"(d[58]),"+f"(d[59]),"+f"(d[60]),"+f"(d[61]),"+f"(d[62]),"+f"(d[63])
                 : "l"(desc_a), "l"(desc_b), "r"(scale_d));
}

__device__ __forceinline__ void wgmma_m64n64k16(float d[32], uint64_t desc_a, uint64_t desc_b, int scale_d) {
    asm volatile("{\n.reg .pred p;\nsetp.ne.b32 p, %34, 0;\n"
                 "wgmma.mma_async.sync.aligned.m64n64k16.f32.bf16.bf16 {%0,%1,%2,%3,%4,%5,%6,%7,%8,%9,%10,%11,%12,%13,%14,%15,%16,%17,%18,%19,%20,%21,%22,%23,%24,%25,%26,%27,%28,%29,%30,%31}, %32, %33, p, 1, 1, 0, 1;\n}"
                 : "+f"(d[0]),"+f"(d[1]),"+f"(d[2]),"+f"(d[3]),"+f"(d[4]),"+f"(d[5]),"+f"(d[6]),"+f"(d[7]),"+f"(d[8]),"+f"(d[9]),"+f"(d[10]),"+f"(d[11]),"+f"(d[12]),"+f"(d[13]),"+f"(d[14]),"+f"(d[15]),"+f"(d[16]),"+f"(d[17]),"+f"(d[18]),"+f"(d[19]),"+f"(d[20]),"+f"(d[21]),"+f"(d[22]),"+f"(d[23]),"+f"(d[24]),"+f"(d[25]),"+f"(d[26]),"+f"(d[27]),"+f"(d[28]),"+f"(d[29]),"+f"(d[30]),"+f"(d[31])
                 : "l"(desc_a), "l"(desc_b), "r"(scale_d));
}

#define K1_GW 12
#define K1_THREADS ((K1_GW + 8) * 32)
#define P1_EPT 10
#define P1_CHUNK (256 * P1_EPT)
#define K1_WBYTES (131072 + 2 * 16384)
#define K1_SMEM (K1_WBYTES + 3 * MAXBINS * 4 + P1_CHUNK * 8)

__device__ __forceinline__ void p1_bar() { asm volatile("bar.sync 1, 256;" ::: "memory"); }

__global__ void __launch_bounds__(K1_THREADS, 1) k1_kernel(
    const __nv_bfloat16* __restrict__ x, const __nv_bfloat16* __restrict__ e_attr,
    const int* __restrict__ src, const int* __restrict__ dst,
    const __nv_bfloat16* __restrict__ w_b, const __nv_bfloat16* __restrict__ w_v,
    const __nv_bfloat16* __restrict__ w_a, const __nv_bfloat16* __restrict__ w_u,
    int N, int E, int chunk, int NB, int nbins, uint32_t magic)
{
    extern __shared__ __align__(1024) uint8_t smem[];
    asm volatile("griddepcontrol.launch_dependents;");
    TSM(threadIdx.x == 0, 0);

    const int warp = threadIdx.x >> 5, lane = threadIdx.x & 31;

    if (warp >= K1_GW) {
        const int tid = threadIdx.x - K1_GW * 32;
        if (blockIdx.x == 0 && tid < 32)
            g_T[(size_t)N * 32 + tid] = make_uint4(0xff80ff80u, 0xff80ff80u, 0u, 0u);
        int* hist = reinterpret_cast<int*>(smem + K1_WBYTES);
        int* loff = hist + MAXBINS;
        int* gbase = loff + MAXBINS;
        uint2* sorted = reinterpret_cast<uint2*>(smem + K1_WBYTES + 3 * MAXBINS * 4);
        for (int beg = blockIdx.x * chunk; beg < E; beg += gridDim.x * chunk) {
            const int end = min(E, beg + chunk);
            int d[P1_EPT]; uint32_t rec[P1_EPT]; int rk[P1_EPT]; int bn[P1_EPT];
            #pragma unroll
            for (int i = 0; i < P1_EPT; i++) {
                int e = beg + i * 256 + tid;
                d[i] = -1;
                if (e < end) {
                    d[i] = __ldg(dst + e);
                    uint32_t s = (uint32_t)__ldg(src + e);
                    uint32_t ev = (uint32_t)__ldg(reinterpret_cast<const unsigned short*>(e_attr) + e);
                    rec[i] = (ev << 16) | s;
                }
            }
            hist[tid] = 0;
            TSM(tid == 0 && d[P1_EPT - 2] != -5 && rec[P1_EPT - 2] != 0xfffffff5u, 14);
            p1_bar();
            #pragma unroll
            for (int i = 0; i < P1_EPT; i++) {
                if (d[i] >= 0) {
                    bn[i] = (int)(((uint64_t)(uint32_t)d[i] * magic) >> 24);
                    rk[i] = atomicAdd(&hist[bn[i]], 1);
                }
            }
            p1_bar();
            TSM(tid == 0, 3);
            {
                int h = hist[tid];
                if (tid < nbins && h > 0) gbase[tid] = atomicAdd(&g_bin_cnt[tid * CNT_STRIDE], h);
                if (tid < 32) {
                    int v[8]; int sum = 0;
                    #pragma unroll
                    for (int i = 0; i < 8; i++) { v[i] = hist[lane * 8 + i]; sum += v[i]; }
                    int inc = sum;
                    #pragma unroll
                    for (int o = 1; o < 32; o <<= 1) { int t = __shfl_up_sync(0xffffffffu, inc, o); if (lane >= o) inc += t; }
                    int run = inc - sum;
                    #pragma unroll
                    for (int i = 0; i < 8; i++) { loff[lane * 8 + i] = run; run += v[i]; }
                }
            }
            p1_bar();
            #pragma unroll
            for (int i = 0; i < P1_EPT; i++) {
                if (d[i] >= 0) sorted[loff[bn[i]] + rk[i]] = make_uint2(rec[i], (uint32_t)d[i]);
            }
            p1_bar();
            const int cnt = end - beg;
            for (int i = tid; i < cnt; i += 256) {
                uint2 r = sorted[i];
                int b = (int)(((uint64_t)r.y * magic) >> 24);
                int pos = gbase[b] + (i - loff[b]);
                if (pos < BINCAP) {
                    g_bins[b * BINCAP + pos] = make_uint2(r.x, r.y - (uint32_t)(b * NB));
                } else {
                    int p = atomicAdd(&g_ovf_cnt, 2);
                    g_ovf[p] = (int)r.y; g_ovf[p + 1] = (int)r.x;
                }
            }
            p1_bar();
        }
        TSM(tid == 0, 4);
        return;
    }

    const int q = lane & 3;
    const int wg = warp >> 2;
    const int n_tasks = ((N + 63) >> 6) * 2;
    const uint32_t sbase = (uint32_t)__cvta_generic_to_shared(smem);
    const uint32_t xbase = sbase + 131072;
    bool w_staged = false;
    int t_beg = (int)(((long long)n_tasks * blockIdx.x) / gridDim.x);
    const int t_end = (int)(((long long)n_tasks * (blockIdx.x + 1)) / gridDim.x);
    while (t_beg < t_end) {
        const int tile0 = t_beg >> 1;
        const int t_stop = min(t_end, (tile0 + 2) << 1);
        stage_x_tile(xbase, x, tile0 * 64, N, threadIdx.x, K1_GW * 32);
        if (((t_stop - 1) >> 1) > tile0) stage_x_tile(xbase + 16384, x, tile0 * 64 + 64, N, threadIdx.x, K1_GW * 32);
        if (!w_staged) {
            stage_weight(sbase, w_b, 0, threadIdx.x, K1_GW * 32);
            stage_weight(sbase, w_v, 1, threadIdx.x, K1_GW * 32);
        }
        asm volatile("cp.async.commit_group;" ::: "memory");
        if (!w_staged) {
            stage_weight(sbase + 65536, w_a, 0, threadIdx.x, K1_GW * 32);
            stage_weight(sbase + 65536, w_u, 1, threadIdx.x, K1_GW * 32);
            w_staged = true;
        }
        asm volatile("cp.async.commit_group;" ::: "memory");
        #pragma unroll 1
        for (int type = 0; type < 2; type++) {
            if (type == 0) asm volatile("cp.async.wait_group 1;" ::: "memory");
            else asm volatile("cp.async.wait_group 0;" ::: "memory");
            asm volatile("fence.proxy.async.shared::cta;" ::: "memory");
            asm volatile("bar.sync 2, %0;" :: "n"(K1_GW * 32) : "memory");
            TSM(threadIdx.x == 0 && type == 0, 1);
            uint4* outp = type ? g_AU : g_T;
            for (int task = t_beg + wg; task < t_stop; task += K1_GW / 4) {
                const int tile = task >> 1, hf = task & 1;
                const uint32_t baddr = sbase + type * 65536 + hf * 1024;
                const uint64_t descb = (uint64_t)((baddr & 0x3FFFF) >> 4) | ((uint64_t)(2048 >> 4) << 16) |
                                       ((uint64_t)(4096 >> 4) << 32) | ((uint64_t)1 << 62);
                const uint32_t aaddr = xbase + (tile - tile0) * 16384;
                const uint64_t desca = (uint64_t)((aaddr & 0x3FFFF) >> 4) | ((uint64_t)1 << 16) |
                                       ((uint64_t)(1024 >> 4) << 32) | ((uint64_t)1 << 62);
                float d[64];
                asm volatile("wgmma.fence.sync.aligned;" ::: "memory");
                #pragma unroll
                for (int ks = 0; ks < 8; ks++) {
                    wgmma_m64n128k16(d, desca + (uint64_t)(((ks >> 2) * 8192 + (ks & 3) * 32) >> 4),
                                     descb + (uint64_t)(ks * (8192 >> 4)), ks > 0 ? 1 : 0);
                }
                asm volatile("wgmma.commit_group.sync.aligned;" ::: "memory");
                asm volatile("wgmma.wait_group.sync.aligned 0;" ::: "memory");
                TSM(threadIdx.x == 0 && type == 0, 13);
                const int r0 = tile * 64 + (warp & 3) * 16 + (lane >> 2);
                #pragma unroll
                for (int mm = 0; mm < 4; mm++) {
                    const int j0 = 2 * mm, j1 = 2 * mm + 1, j2 = 8 + 2 * mm, j3 = 9 + 2 * mm;
                    uint4 o0 = make_uint4(pack_bf16(d[4 * j0], d[4 * j0 + 1]), pack_bf16(d[4 * j1], d[4 * j1 + 1]),
                                          pack_bf16(d[4 * j2], d[4 * j2 + 1]), pack_bf16(d[4 * j3], d[4 * j3 + 1]));
                    uint4 o1 = make_uint4(pack_bf16(d[4 * j0 + 2], d[4 * j0 + 3]), pack_bf16(d[4 * j1 + 2], d[4 * j1 + 3]),
                                          pack_bf16(d[4 * j2 + 2], d[4 * j2 + 3]), pack_bf16(d[4 * j3 + 2], d[4 * j3 + 3]));
                    const int m = 4 * hf + mm;
                    if (r0 < N) outp[(size_t)r0 * 32 + 4 * m + q] = o0;
                    if (r0 + 8 < N) outp[(size_t)(r0 + 8) * 32 + 4 * m + q] = o1;
                }
            }
        }
        t_beg = t_stop;
        if (t_beg < t_end) asm volatile("bar.sync 2, %0;" :: "n"(K1_GW * 32) : "memory");
    }
    TSM(threadIdx.x == 0, 2);
}

__device__ __forceinline__ void edge_accum(const uint4 v, const float e, const float a[4], const float cc[4],
                                           float num[4], float den[4]) {
    float y0 = fmaf(bf_lo(v.x), -LOG2E, fmaf(e, cc[0], a[0]));
    float y1 = fmaf(bf_hi(v.x), -LOG2E, fmaf(e, cc[1], a[1]));
    float y2 = fmaf(bf_lo(v.y), -LOG2E, fmaf(e, cc[2], a[2]));
    float y3 = fmaf(bf_hi(v.y), -LOG2E, fmaf(e, cc[3], a[3]));
    float s0 = rcp_approx(1.f + ex2_approx(y0));
    float s1 = rcp_approx(1.f + ex2_approx(y1));
    float s2 = rcp_approx(1.f + ex2_approx(y2));
    float s3 = rcp_approx(1.f + ex2_approx(y3));
    den[0] += s0; den[1] += s1; den[2] += s2; den[3] += s3;
    num[0] = fmaf(s0, bf_lo(v.z), num[0]);
    num[1] = fmaf(s1, bf_hi(v.z), num[1]);
    num[2] = fmaf(s2, bf_lo(v.w), num[2]);
    num[3] = fmaf(s3, bf_hi(v.w), num[3]);
}

#define K2_THREADS 1024
#define K2_D 2
#define K2_GS 2
#define K2_RPT ((BINCAP + K2_THREADS - 1) / K2_THREADS)
#define K2_NW (K2_THREADS / 32)
#define SORT_WORDS (BINCAP + 4 * MAXNB)
#define K2_OFF_AU 0
#define K2_OFF_X (K2_OFF_AU + MAXNB * 512)
#define K2_OFF_PART (K2_OFF_X + MAXNB * 256)
#define K2_OFF_SORT (K2_OFF_PART + K2_NW * 1024)
#define K2_OFF_HIST (K2_OFF_SORT + SORT_WORDS * 4)
#define K2_OFF_OFF (K2_OFF_HIST + MAXNB * 4)
#define K2_DYN_SMEM (K2_OFF_OFF + (MAXNB + 4) * 4)

struct Grp { uint4 v[K2_GS]; };

__device__ __forceinline__ const uint4* row_ptr(const char* Tl, uint32_t rec) {
    return reinterpret_cast<const uint4*>(Tl + (size_t)((rec & 0xffffu) * 512u));
}
__device__ __forceinline__ void grp_load(Grp& g, const uint32_t* sp, const char* Tl) {
    const uint2 t = *reinterpret_cast<const uint2*>(sp);
    g.v[0] = __ldg(row_ptr(Tl, t.x));
    g.v[1] = __ldg(row_ptr(Tl, t.y));
}
__device__ __forceinline__ void grp_consume(const Grp& g, const uint32_t* sp, const float a[4], const float cc[4],
                                            float num[4], float den[4]) {
    const uint2 t = *reinterpret_cast<const uint2*>(sp);
    edge_accum(g.v[0], bf_hi(t.x), a, cc, num, den);
    edge_accum(g.v[1], bf_hi(t.y), a, cc, num, den);
}

__device__ __forceinline__ void load_a(const uint8_t* smem, int ln, int lane, float a[4]) {
    const uint2 av = *reinterpret_cast<const uint2*>(smem + K2_OFF_AU + ln * 512 + lane * 16);
    a[0] = -LOG2E * bf_lo(av.x); a[1] = -LOG2E * bf_hi(av.x); a[2] = -LOG2E * bf_lo(av.y); a[3] = -LOG2E * bf_hi(av.y);
}
__device__ __forceinline__ void write_node(const uint8_t* smem, __nv_bfloat16* out, int ln, int n,
                                           int lane, const float num[4], const float den[4]) {
    const uint2 uv = *reinterpret_cast<const uint2*>(smem + K2_OFF_AU + ln * 512 + lane * 16 + 8);
    const uint32_t* xr = reinterpret_cast<const uint32_t*>(smem + K2_OFF_X) + ln * 64 + (lane >> 2) * 8 + (lane & 3);
    const uint32_t x0 = xr[0], x1 = xr[4];
    const float u4[4] = { bf_lo(uv.x), bf_hi(uv.x), bf_lo(uv.y), bf_hi(uv.y) };
    const float x4[4] = { bf_lo(x0), bf_hi(x0), bf_lo(x1), bf_hi(x1) };
    float o[4];
    #pragma unroll
    for (int i = 0; i < 4; i++) {
        float agg = round_bf16(__fdividef(num[i], den[i] + 1e-6f));
        float z = round_bf16(u4[i] + agg);
        float rz = (z > 0.f) ? z : 0.f * z;
        o[i] = x4[i] + rz;
    }
    uint32_t* o32 = reinterpret_cast<uint32_t*>(out) + (size_t)n * 64 + (lane >> 2) * 8 + (lane & 3);
    o32[0] = pack_bf16(o[0], o[1]); o32[4] = pack_bf16(o[2], o[3]);
}

__device__ __noinline__ void slow_path(const uint8_t* smem, __nv_bfloat16* out, int node0, int nn, int ovf_n,
                                       float c0, float c1, float c2, float c3) {
    const uint32_t* s_sorted = reinterpret_cast<const uint32_t*>(smem + K2_OFF_SORT);
    const int* s_off = reinterpret_cast<const int*>(smem + K2_OFF_OFF);
    const int lane = threadIdx.x & 31, warp = threadIdx.x >> 5;
    const float cc[4] = { c0, c1, c2, c3 };
    const char* Tl = reinterpret_cast<const char*>(g_T) + lane * 16;
    for (int ln = warp; ln < nn; ln += K2_NW) {
        float a[4];
        load_a(smem, ln, lane, a);
        float num[4] = {0.f, 0.f, 0.f, 0.f}, den[4] = {0.f, 0.f, 0.f, 0.f};
        for (int i = s_off[ln]; i < s_off[ln + 1]; i++) {
            const uint32_t r = s_sorted[i];
            edge_accum(__ldg(row_ptr(Tl, r)), bf_hi(r), a, cc, num, den);
        }
        const int n = node0 + ln;
        for (int base = 0; base < ovf_n; base += 64) {
            int i2 = base + 2 * lane;
            int od = (i2 < ovf_n) ? g_ovf[i2] : -1;
            uint32_t orec = (i2 < ovf_n) ? (uint32_t)g_ovf[i2 + 1] : 0u;
            unsigned msk = __ballot_sync(0xffffffffu, od == n);
            while (msk) {
                int l = __ffs(msk) - 1; msk &= msk - 1;
                uint32_t r = __shfl_sync(0xffffffffu, orec, l);
                edge_accum(__ldg(row_ptr(Tl, r)), bf_hi(r), a, cc, num, den);
            }
        }
        write_node(smem, out, ln, n, lane, num, den);
    }
}

__global__ void __launch_bounds__(K2_THREADS, 1) k2_kernel(
    const __nv_bfloat16* __restrict__ x, const __nv_bfloat16* __restrict__ w_a, const __nv_bfloat16* __restrict__ w_u,
    const __nv_bfloat16* __restrict__ w_c, __nv_bfloat16* __restrict__ out, int N, int NB)
{
    extern __shared__ __align__(1024) uint8_t smem[];
    float4* s_part = reinterpret_cast<float4*>(smem + K2_OFF_PART);
    uint32_t* s_sorted = reinterpret_cast<uint32_t*>(smem + K2_OFF_SORT);
    int* s_hist = reinterpret_cast<int*>(smem + K2_OFF_HIST);
    int* s_off = reinterpret_cast<int*>(smem + K2_OFF_OFF);

    const int tid = threadIdx.x;
    const int lane = tid & 31, warp = tid >> 5;
    const int bin = blockIdx.x;
    const int node0 = bin * NB;
    const int nn = min(NB, N - node0);
    const uint32_t sb = (uint32_t)__cvta_generic_to_shared(smem);
    TSM(tid == 0, 5);

    const int fw = (lane >> 2) * 8 + (lane & 3);
    const uint2 wc = make_uint2(__ldg(reinterpret_cast<const uint32_t*>(w_c) + fw), __ldg(reinterpret_cast<const uint32_t*>(w_c) + fw + 4));
    s_part[warp * 64 + lane] = make_float4(0.f, 0.f, 0.f, 0.f);
    s_part[warp * 64 + 32 + lane] = make_float4(0.f, 0.f, 0.f, 0.f);
    for (int i = tid; i < nn * 16; i += K2_THREADS)
        cp_async16(sb + K2_OFF_X + i * 16, reinterpret_cast<const uint4*>(x) + (size_t)node0 * 16 + i);
    if (tid < MAXNB) s_hist[tid] = 0;
    for (int i = tid; i < SORT_WORDS; i += K2_THREADS) s_sorted[i] = (uint32_t)N;
    __syncthreads();
    asm volatile("griddepcontrol.wait;" ::: "memory");
    TSM(tid == 0, 8);
    {
        uint2 r[K2_RPT]; int rk[K2_RPT];
        const int cnt = min(g_bin_cnt[bin * CNT_STRIDE], BINCAP);
        if (tid == 64) s_off[MAXNB + 1] = g_ovf_cnt;
        #pragma unroll
        for (int i = 0; i < K2_RPT; i++) {
            int idx = i * K2_THREADS + tid;
            if (idx < cnt) r[i] = g_bins[bin * BINCAP + idx];
        }
        for (int i = tid; i < nn * 32; i += K2_THREADS)
            cp_async16(sb + K2_OFF_AU + i * 16, g_AU + (size_t)node0 * 32 + i);
        #pragma unroll
        for (int i = 0; i < K2_RPT; i++) {
            int idx = i * K2_THREADS + tid;
            if (idx < cnt) rk[i] = atomicAdd(&s_hist[r[i].y], 1);
        }
        __syncthreads();
        if (warp == 0) {
            int v[4]; int sum = 0;
            #pragma unroll
            for (int i = 0; i < 4; i++) { v[i] = (s_hist[lane * 4 + i] + K2_GS - 1) & ~(K2_GS - 1); sum += v[i]; }
            int inc = sum;
            #pragma unroll
            for (int o = 1; o < 32; o <<= 1) { int t = __shfl_up_sync(0xffffffffu, inc, o); if (lane >= o) inc += t; }
            int run = inc - sum;
            #pragma unroll
            for (int i = 0; i < 4; i++) { s_off[lane * 4 + i] = run; run += v[i]; }
            if (lane == 31) s_off[MAXNB] = run;
        }
        if (tid == 32) g_bin_cnt[bin * CNT_STRIDE] = 0;
        __syncthreads();
        #pragma unroll
        for (int i = 0; i < K2_RPT; i++) {
            int idx = i * K2_THREADS + tid;
            if (idx < cnt) s_sorted[s_off[r[i].y] + rk[i]] = r[i].x;
        }
        TSM(tid == 0, 9);
        asm volatile("cp.async.wait_all;" ::: "memory");
    }
    __syncthreads();
    TSM(tid == 0, 10);
    const float cc[4] = { -LOG2E * bf_lo(wc.x), -LOG2E * bf_hi(wc.x), -LOG2E * bf_lo(wc.y), -LOG2E * bf_hi(wc.y) };
    const int ovf_n = s_off[MAXNB + 1];

    if (ovf_n != 0) {
        slow_path(smem, out, node0, nn, ovf_n, cc[0], cc[1], cc[2], cc[3]);
        __syncthreads();
        if (tid == 0) {
            __threadfence();
            int t = atomicAdd(&g_done, 1);
            if (t == (int)gridDim.x - 1) { g_done = 0; __threadfence(); g_ovf_cnt = 0; }
        }
        return;
    }

    const char* Tl = reinterpret_cast<const char*>(g_T) + lane * 16;
    const int G = s_off[MAXNB] / K2_GS;
    int g = (G * warp) / K2_NW;
    const int g1 = (G * (warp + 1)) / K2_NW;
    int ln;
    {
        int c_lo = 0;
        #pragma unroll
        for (int i = 0; i < 4; i++) {
            int node = i * 32 + lane;
            int o = (node < nn) ? s_off[node] : 0x7fffffff;
            c_lo += __popc(__ballot_sync(0xffffffffu, o < g * K2_GS));
        }
        ln = c_lo;
    }
    bool head = ln > 0;
    if (head) ln--;
    float a[4], num[4] = {0.f, 0.f, 0.f, 0.f}, den[4] = {0.f, 0.f, 0.f, 0.f};
    int node_end;

    auto load_node = [&]() {
        load_a(smem, ln, lane, a);
        node_end = s_off[ln + 1] / K2_GS;
    };
    auto finish_node = [&]() { write_node(smem, out, ln, node0 + ln, lane, num, den); };
    auto close_node = [&]() {
        if (head) {
            s_part[warp * 64 + lane] = make_float4(num[0], num[1], num[2], num[3]);
            s_part[warp * 64 + 32 + lane] = make_float4(den[0], den[1], den[2], den[3]);
            head = false;
        } else {
            finish_node();
        }
        #pragma unroll
        for (int i = 0; i < 4; i++) { num[i] = 0.f; den[i] = 0.f; }
    };

    bool tail = false;
    if (g < g1 || warp == K2_NW - 1) {
        load_node();
        Grp b[K2_D];
        #pragma unroll
        for (int d = 0; d < K2_D; d++)
            if (g + d < g1) grp_load(b[d], s_sorted + K2_GS * (g + d), Tl);
        while (g < g1) {
            #pragma unroll
            for (int d = 0; d < K2_D; d++) {
                if (g < g1) {
                    while (g == node_end) { close_node(); ln++; load_node(); }
                    grp_consume(b[d], s_sorted + K2_GS * g, a, cc, num, den);
                    if (g + K2_D < g1) grp_load(b[d], s_sorted + K2_GS * (g + K2_D), Tl);
                    g++;
                }
            }
        }
        if (warp == K2_NW - 1) {
            while (true) { close_node(); ln++; if (ln >= nn) break; load_node(); }
        } else if (node_end == g1 || head) {
            close_node();
        } else {
            tail = true;
        }
    }
    TSM(tid == 0, 11);
    __syncthreads();
    TSM(tid == 0, 12);
    if (tail) {
        for (int w2 = warp + 1; w2 < K2_NW && (G * w2) / K2_NW < node_end; w2++) {
            const float4 pn = s_part[w2 * 64 + lane], pd = s_part[w2 * 64 + 32 + lane];
            num[0] += pn.x; num[1] += pn.y; num[2] += pn.z; num[3] += pn.w;
            den[0] += pd.x; den[1] += pd.y; den[2] += pd.z; den[3] += pd.w;
        }
        finish_node();
    }
}

extern "C" void kernel_launch(void* const* d_in, const int* in_sizes, int n_in,
                              void* d_out, int out_size) {
    const __nv_bfloat16* x      = (const __nv_bfloat16*)d_in[0];
    const __nv_bfloat16* e_attr = (const __nv_bfloat16*)d_in[1];
    const int* src = (const int*)d_in[2];
    const int* dst = (const int*)d_in[3];
    const __nv_bfloat16* w_a = (const __nv_bfloat16*)d_in[4];
    const __nv_bfloat16* w_b = (const __nv_bfloat16*)d_in[5];
    const __nv_bfloat16* w_c = (const __nv_bfloat16*)d_in[6];
    const __nv_bfloat16* w_u = (const __nv_bfloat16*)d_in[7];
    const __nv_bfloat16* w_v = (const __nv_bfloat16*)d_in[8];
    __nv_bfloat16* out = (__nv_bfloat16*)d_out;
    const int N = in_sizes[0] / D_FEAT;
    const int E = in_sizes[2];
    if (N > MAX_N || 2 * E > MAX_E || N <= 0) return;

    static int num_sms = 0;
    if (num_sms == 0) {
        int dev = 0;
        cudaGetDevice(&dev);
        cudaDeviceGetAttribute(&num_sms, cudaDevAttrMultiProcessorCount, dev);
        if (num_sms <= 0 || num_sms > MAXBINS) num_sms = 132;
        cudaFuncSetAttribute(k1_kernel, cudaFuncAttributeMaxDynamicSharedMemorySize, K1_SMEM);
        cudaFuncSetAttribute(k2_kernel, cudaFuncAttributeMaxDynamicSharedMemorySize, K2_DYN_SMEM);
    }
    cudaStream_t st = cudaStreamPerThread;
    int NB = (N + num_sms - 1) / num_sms;
    if (NB > MAXNB) NB = MAXNB;
    const int nbins = (N + NB - 1) / NB;
    const uint32_t magic = (uint32_t)(((1u << 24) + NB - 1) / NB);
    const int P = num_sms;
    int chunk = (E + P - 1) / P;
    if (chunk > P1_CHUNK) chunk = P1_CHUNK;
    if (chunk < 1) chunk = 1;
    k1_kernel<<<P, K1_THREADS, K1_SMEM, st>>>(x, e_attr, src, dst, w_b, w_v, w_a, w_u, N, E, chunk, NB, nbins, magic);

    cudaLaunchConfig_t cfg = {};
    cfg.gridDim = dim3(nbins);
    cfg.blockDim = dim3(K2_THREADS);
    cfg.dynamicSmemBytes = K2_DYN_SMEM;
    cfg.stream = st;
    cudaLaunchAttribute at[1];
    at[0].id = cudaLaunchAttributeProgrammaticStreamSerialization;
    at[0].val.programmaticStreamSerializationAllowed = 1;
    cfg.attrs = at; cfg.numAttrs = 1;
    cudaLaunchKernelEx(&cfg, k2_kernel, x, w_a, w_u, w_c, out, N, NB);
}
```

```cpp
#include <cuda_runtime.h>
#include <cuda.h>
#include <cuda_bf16.h>
#include <stdint.h>

#define D_FEAT 128
#define MAX_N 16384
#define MAX_E (1 << 20)
#define LOG2E 1.4426950408889634f

#define MAXBINS 256
#define MAXNB 128
#define BINCAP 3072
__device__ uint4 g_T[(MAX_N + 1) * 32];
#define CNT_STRIDE 1
__device__ int g_bin_cnt[MAXBINS * CNT_STRIDE];
__device__ uint2 g_bins[MAXBINS * BINCAP];
__device__ int g_ovf[MAX_E];
__device__ int g_ovf_cnt;
__device__ int g_done;

#define TSM(cond, i)
__device__ __forceinline__ float ex2_approx(float x) {
    float y; asm("ex2.approx.ftz.f32 %0, %1;" : "=f"(y) : "f"(x)); return y;
}
__device__ __forceinline__ float rcp_approx(float x) {
    float y; asm("rcp.approx.ftz.f32 %0, %1;" : "=f"(y) : "f"(x)); return y;
}
__device__ __forceinline__ uint32_t pack_bf16(float lo, float hi) {
    __nv_bfloat162 t = __floats2bfloat162_rn(lo, hi);
    return *reinterpret_cast<uint32_t*>(&t);
}
__device__ __forceinline__ float bf_lo(uint32_t v) { return __uint_as_float(v << 16); }
__device__ __forceinline__ float bf_hi(uint32_t v) { return __uint_as_float(v & 0xffff0000u); }
__device__ __forceinline__ float round_bf16(float x) { return __bfloat162float(__float2bfloat16_rn(x)); }

__device__ __forceinline__ void mma_bf16(float c[4], uint32_t a0, uint32_t a1, uint32_t a2, uint32_t a3,
                                         uint32_t b0, uint32_t b1) {
    asm volatile("mma.sync.aligned.m16n8k16.row.col.f32.bf16.bf16.f32 "
                 "{%0,%1,%2,%3}, {%4,%5,%6,%7}, {%8,%9}, {%0,%1,%2,%3};"
                 : "+f"(c[0]), "+f"(c[1]), "+f"(c[2]), "+f"(c[3])
                 : "r"(a0), "r"(a1), "r"(a2), "r"(a3), "r"(b0), "r"(b1));
}
__device__ __forceinline__ void ldmatrix_x4_trans(uint32_t& r0, uint32_t& r1, uint32_t& r2, uint32_t& r3, uint32_t addr) {
    asm volatile("ldmatrix.sync.aligned.m8n8.x4.trans.shared.b16 {%0,%1,%2,%3}, [%4];"
                 : "=r"(r0), "=r"(r1), "=r"(r2), "=r"(r3) : "r"(addr));
}

__device__ __forceinline__ void cp_async16(uint32_t saddr, const void* g) {
    asm volatile("cp.async.cg.shared.global [%0], [%1], 16;" :: "r"(saddr), "l"(g) : "memory");
}
__device__ __forceinline__ void cp_async16_zfill(uint32_t saddr, const void* g, int src_size) {
    asm volatile("cp.async.cg.shared.global [%0], [%1], 16, %2;" :: "r"(saddr), "l"(g), "r"(src_size) : "memory");
}
__device__ __forceinline__ void stage_weight(uint32_t sdst, const __nv_bfloat16* w, int mtx, int tid, int nthreads) {
    const uint4* W = reinterpret_cast<const uint4*>(w);
    for (int u = tid; u < 2048; u += nthreads) {
        int k = u >> 4, c16 = u & 15;
        int kg = k >> 3, rr = k & 7;
        int h = mtx * 2 + (c16 >> 3);
        cp_async16(sdst + kg * 4096 + h * 1024 + rr * 128 + (((c16 & 7) ^ rr) << 4), W + u);
    }
}
__device__ __forceinline__ void stage_x_tile(uint32_t sdst, const __nv_bfloat16* x, int row0, int N, int tid, int nthreads) {
    const uint4* X = reinterpret_cast<const uint4*>(x);
    for (int u = tid; u < 1024; u += nthreads) {
        int r = u >> 4, c16 = u & 15;
        int gr = row0 + r;
        bool ok = gr < N;
        cp_async16_zfill(sdst + (c16 >> 3) * 8192 + r * 128 + (((c16 & 7) ^ (r & 7)) << 4),
                         X + (size_t)(ok ? gr : 0) * 16 + c16, ok ? 16 : 0);
    }
}

__device__ __forceinline__ void mbar_init(uint32_t bar, int cnt) {
    asm volatile("mbarrier.init.shared::cta.b64 [%0], %1;" :: "r"(bar), "r"(cnt) : "memory");
    asm volatile("fence.mbarrier_init.release.cluster;" ::: "memory");
    asm volatile("fence.proxy.async.shared::cta;" ::: "memory");
}
__device__ __forceinline__ void mbar_expect_tx(uint32_t bar, uint32_t bytes) {
    asm volatile("mbarrier.arrive.expect_tx.shared::cta.b64 _, [%0], %1;" :: "r"(bar), "r"(bytes) : "memory");
}
__device__ __forceinline__ void mbar_wait(uint32_t bar, uint32_t parity) {
    asm volatile("{\n.reg .pred p;\nWAIT_LOOP:\n"
                 "mbarrier.try_wait.parity.shared::cta.b64 p, [%0], %1;\n"
                 "@p bra WAIT_DONE;\nbra WAIT_LOOP;\nWAIT_DONE:\n}" :: "r"(bar), "r"(parity) : "memory");
}
__device__ __forceinline__ void tma_2d(uint32_t sdst, const CUtensorMap* tm, int c0, int c1, uint32_t bar) {
    asm volatile("cp.async.bulk.tensor.2d.shared::cluster.global.mbarrier::complete_tx::bytes [%0], [%1, {%3, %4}], [%2];"
                 :: "r"(sdst), "l"(reinterpret_cast<uint64_t>(tm)), "r"(bar), "r"(c0), "r"(c1) : "memory");
}
__device__ __forceinline__ void tma_weights(uint32_t sdst, const CUtensorMap* m0, const CUtensorMap* m1, uint32_t bar) {
    tma_2d(sdst, m0, 0, 0, bar);
    tma_2d(sdst + 16384, m0, 64, 0, bar);
    tma_2d(sdst + 32768, m1, 0, 0, bar);
    tma_2d(sdst + 49152, m1, 64, 0, bar);
}
__device__ __forceinline__ void tma_x_tile(uint32_t sdst, const CUtensorMap* mx, int row0, uint32_t bar) {
    tma_2d(sdst, mx, 0, row0, bar);
    tma_2d(sdst + 8192, mx, 64, row0, bar);
}

__device__ __forceinline__ void wgmma_m64n128k16(float d[64], uint64_t desc_a, uint64_t desc_b, int scale_d) {
    asm volatile("{\n.reg .pred p;\nsetp.ne.b32 p, %66, 0;\n"
                 "wgmma.mma_async.sync.aligned.m64n128k16.f32.bf16.bf16 {%0,%1,%2,%3,%4,%5,%6,%7,%8,%9,%10,%11,%12,%13,%14,%15,%16,%17,%18,%19,%20,%21,%22,%23,%24,%25,%26,%27,%28,%29,%30,%31,%32,%33,%34,%35,%36,%37,%38,%39,%40,%41,%42,%43,%44,%45,%46,%47,%48,%49,%50,%51,%52,%53,%54,%55,%56,%57,%58,%59,%60,%61,%62,%63}, %64, %65, p, 1, 1, 0, 1;\n}"
                 : "+f"(d[0]),"+f"(d[1]),"+f"(d[2]),"+f"(d[3]),"+f"(d[4]),"+f"(d[5]),"+f"(d[6]),"+f"(d[7]),"+f"(d[8]),"+f"(d[9]),"+f"(d[10]),"+f"(d[11]),"+f"(d[12]),"+f"(d[13]),"+f"(d[14]),"+f"(d[15]),"+f"(d[16]),"+f"(d[17]),"+f"(d[18]),"+f"(d[19]),"+f"(d[20]),"+f"(d[21]),"+f"(d[22]),"+f"(d[23]),"+f"(d[24]),"+f"(d[25]),"+f"(d[26]),"+f"(d[27]),"+f"(d[28]),"+f"(d[29]),"+f"(d[30]),"+f"(d[31]),"+f"(d[32]),"+f"(d[33]),"+f"(d[34]),"+f"(d[35]),"+f"(d[36]),"+f"(d[37]),"+f"(d[38]),"+f"(d[39]),"+f"(d[40]),"+f"(d[41]),"+f"(d[42]),"+f"(d[43]),"+f"(d[44]),"+f"(d[45]),"+f"(d[46]),"+f"(d[47]),"+f"(d[48]),"+f"(d[49]),"+f"(d[50]),"+f"(d[51]),"+f"(d[52]),"+f"(d[53]),"+f"(d[54]),"+f"(d[55]),"+f"(d[56]),"+f"(d[57]),"+f"(d[58]),"+f"(d[59]),"+f"(d[60]),"+f"(d[61]),"+f"(d[62]),"+f"(d[63])
                 : "l"(desc_a), "l"(desc_b), "r"(scale_d));
}

__device__ __forceinline__ void wgmma_m64n64k16(float d[32], uint64_t desc_a, uint64_t desc_b, int scale_d) {
    asm volatile("{\n.reg .pred p;\nsetp.ne.b32 p, %34, 0;\n"
                 "wgmma.mma_async.sync.aligned.m64n64k16.f32.bf16.bf16 {%0,%1,%2,%3,%4,%5,%6,%7,%8,%9,%10,%11,%12,%13,%14,%15,%16,%17,%18,%19,%20,%21,%22,%23,%24,%25,%26,%27,%28,%29,%30,%31}, %32, %33, p, 1, 1, 0, 1;\n}"
                 : "+f"(d[0]),"+f"(d[1]),"+f"(d[2]),"+f"(d[3]),"+f"(d[4]),"+f"(d[5]),"+f"(d[6]),"+f"(d[7]),"+f"(d[8]),"+f"(d[9]),"+f"(d[10]),"+f"(d[11]),"+f"(d[12]),"+f"(d[13]),"+f"(d[14]),"+f"(d[15]),"+f"(d[16]),"+f"(d[17]),"+f"(d[18]),"+f"(d[19]),"+f"(d[20]),"+f"(d[21]),"+f"(d[22]),"+f"(d[23]),"+f"(d[24]),"+f"(d[25]),"+f"(d[26]),"+f"(d[27]),"+f"(d[28]),"+f"(d[29]),"+f"(d[30]),"+f"(d[31])
                 : "l"(desc_a), "l"(desc_b), "r"(scale_d));
}

#define K1_GW 12
#define K1_THREADS ((K1_GW + 8) * 32)
#define P1_EPT 10
#define P1_CHUNK (256 * P1_EPT)
#define K1_WBYTES (65536 + 2 * 16384)
#define K1_SMEM (K1_WBYTES + 3 * MAXBINS * 4 + P1_CHUNK * 8 + 16)

__device__ __forceinline__ void p1_bar() { asm volatile("bar.sync 1, 256;" ::: "memory"); }

__global__ void __launch_bounds__(K1_THREADS, 1) k1_kernel(
    const __grid_constant__ CUtensorMap tm_x, const __grid_constant__ CUtensorMap tm_wb, const __grid_constant__ CUtensorMap tm_wv,
    const __nv_bfloat16* __restrict__ x, const __nv_bfloat16* __restrict__ e_attr,
    const int* __restrict__ src, const int* __restrict__ dst,
    const __nv_bfloat16* __restrict__ w_b, const __nv_bfloat16* __restrict__ w_v,
    const __nv_bfloat16* __restrict__ w_a, const __nv_bfloat16* __restrict__ w_u,
    int N, int E, int chunk, int NB, int nbins, uint32_t magic)
{
    extern __shared__ __align__(1024) uint8_t smem[];
    asm volatile("griddepcontrol.launch_dependents;");
    TSM(threadIdx.x == 0, 0);

    const int warp = threadIdx.x >> 5, lane = threadIdx.x & 31;

    if (warp >= K1_GW) {
        const int tid = threadIdx.x - K1_GW * 32;
        if (blockIdx.x == 0 && tid < 32)
            g_T[(size_t)N * 32 + tid] = make_uint4(0xff80ff80u, 0xff80ff80u, 0u, 0u);
        int* hist = reinterpret_cast<int*>(smem + K1_WBYTES);
        int* loff = hist + MAXBINS;
        int* gbase = loff + MAXBINS;
        uint2* sorted = reinterpret_cast<uint2*>(smem + K1_WBYTES + 3 * MAXBINS * 4);
        for (int beg = blockIdx.x * chunk; beg < E; beg += gridDim.x * chunk) {
            const int end = min(E, beg + chunk);
            int d[P1_EPT]; uint32_t rec[P1_EPT]; int rk[P1_EPT]; int bn[P1_EPT];
            #pragma unroll
            for (int i = 0; i < P1_EPT; i++) {
                int e = beg + i * 256 + tid;
                d[i] = -1;
                if (e < end) {
                    d[i] = __ldg(dst + e);
                    uint32_t s = (uint32_t)__ldg(src + e);
                    uint32_t ev = (uint32_t)__ldg(reinterpret_cast<const unsigned short*>(e_attr) + e);
                    rec[i] = (ev << 16) | s;
                }
            }
            hist[tid] = 0;
            TSM(tid == 0 && d[P1_EPT - 2] != -5 && rec[P1_EPT - 2] != 0xfffffff5u, 14);
            p1_bar();
            #pragma unroll
            for (int i = 0; i < P1_EPT; i++) {
                if (d[i] >= 0) {
                    bn[i] = (int)(((uint64_t)(uint32_t)d[i] * magic) >> 24);
                    rk[i] = atomicAdd(&hist[bn[i]], 1);
                }
            }
            p1_bar();
            TSM(tid == 0, 3);
            {
                int h = hist[tid];
                if (tid < nbins && h > 0) gbase[tid] = atomicAdd(&g_bin_cnt[tid * CNT_STRIDE], h);
                if (tid < 32) {
                    int v[8]; int sum = 0;
                    #pragma unroll
                    for (int i = 0; i < 8; i++) { v[i] = hist[lane * 8 + i]; sum += v[i]; }
                    int inc = sum;
                    #pragma unroll
                    for (int o = 1; o < 32; o <<= 1) { int t = __shfl_up_sync(0xffffffffu, inc, o); if (lane >= o) inc += t; }
                    int run = inc - sum;
                    #pragma unroll
                    for (int i = 0; i < 8; i++) { loff[lane * 8 + i] = run; run += v[i]; }
                }
            }
            p1_bar();
            #pragma unroll
            for (int i = 0; i < P1_EPT; i++) {
                if (d[i] >= 0) sorted[loff[bn[i]] + rk[i]] = make_uint2(rec[i], (uint32_t)d[i]);
            }
            p1_bar();
            const int cnt = end - beg;
            for (int i = tid; i < cnt; i += 256) {
                uint2 r = sorted[i];
                int b = (int)(((uint64_t)r.y * magic) >> 24);
                int pos = gbase[b] + (i - loff[b]);
                if (pos < BINCAP) {
                    g_bins[b * BINCAP + pos] = make_uint2(r.x, r.y - (uint32_t)(b * NB));
                } else {
                    int p = atomicAdd(&g_ovf_cnt, 2);
                    g_ovf[p] = (int)r.y; g_ovf[p + 1] = (int)r.x;
                }
            }
            p1_bar();
        }
        TSM(tid == 0, 4);
        return;
    }

    if (blockIdx.x < 4 && threadIdx.x < 128) {
        const char* pw = reinterpret_cast<const char*>((blockIdx.x & 2) ? w_u : w_a) + (blockIdx.x & 1) * 16384 + threadIdx.x * 128;
        asm volatile("prefetch.global.L2 [%0];" :: "l"(pw));
    }
    const int q = lane & 3;
    const int wg = warp >> 2;
    const int n_tasks = ((N + 63) >> 6) * 2;
    const uint32_t sbase = (uint32_t)__cvta_generic_to_shared(smem);
    const uint32_t xbase = sbase + 65536;
    bool w_staged = false;
    const uint32_t mbar = sbase + K1_SMEM - 16;
    uint32_t phase = 0;
    if (threadIdx.x == 0) mbar_init(mbar, 1);
    int t_beg = (int)(((long long)n_tasks * blockIdx.x) / gridDim.x);
    const int t_end = (int)(((long long)n_tasks * (blockIdx.x + 1)) / gridDim.x);
    while (t_beg < t_end) {
        const int tile0 = t_beg >> 1;
        const int t_stop = min(t_end, (tile0 + 2) << 1);
        if (threadIdx.x == 0) {
            const bool two = ((t_stop - 1) >> 1) > tile0;
            mbar_expect_tx(mbar, (two ? 32768u : 16384u) + (w_staged ? 0u : 65536u));
            tma_x_tile(xbase, &tm_x, tile0 * 64, mbar);
            if (!w_staged) tma_weights(sbase, &tm_wb, &tm_wv, mbar);
            if (two) tma_x_tile(xbase + 16384, &tm_x, tile0 * 64 + 64, mbar);
        }
        if (!w_staged) asm volatile("bar.sync 2, %0;" :: "n"(K1_GW * 32) : "memory");
        w_staged = true;
        mbar_wait(mbar, phase);
        phase ^= 1;
        TSM(threadIdx.x == 0, 1);
        for (int task = t_beg + wg; task < t_stop; task += K1_GW / 4) {
            const int tile = task >> 1, hf = task & 1;
            const uint32_t baddr = sbase + hf * 16384;
            const uint64_t descb = (uint64_t)((baddr & 0x3FFFF) >> 4) | ((uint64_t)(32768 >> 4) << 16) |
                                   ((uint64_t)(1024 >> 4) << 32) | ((uint64_t)1 << 62);
            const uint32_t aaddr = xbase + (tile - tile0) * 16384;
            const uint64_t desca = (uint64_t)((aaddr & 0x3FFFF) >> 4) | ((uint64_t)1 << 16) |
                                   ((uint64_t)(1024 >> 4) << 32) | ((uint64_t)1 << 62);
            float d[64];
            asm volatile("wgmma.fence.sync.aligned;" ::: "memory");
            #pragma unroll
            for (int ks = 0; ks < 8; ks++) {
                wgmma_m64n128k16(d, desca + (uint64_t)(((ks >> 2) * 8192 + (ks & 3) * 32) >> 4),
                                 descb + (uint64_t)(ks * (2048 >> 4)), ks > 0 ? 1 : 0);
            }
            asm volatile("wgmma.commit_group.sync.aligned;" ::: "memory");
            asm volatile("wgmma.wait_group.sync.aligned 0;" ::: "memory");
            TSM(threadIdx.x == 0, 13);
            const int r0 = tile * 64 + (warp & 3) * 16 + (lane >> 2);
            #pragma unroll
            for (int mm = 0; mm < 4; mm++) {
                const int j0 = 2 * mm, j1 = 2 * mm + 1, j2 = 8 + 2 * mm, j3 = 9 + 2 * mm;
                uint4 o0 = make_uint4(pack_bf16(d[4 * j0], d[4 * j0 + 1]), pack_bf16(d[4 * j1], d[4 * j1 + 1]),
                                      pack_bf16(d[4 * j2], d[4 * j2 + 1]), pack_bf16(d[4 * j3], d[4 * j3 + 1]));
                uint4 o1 = make_uint4(pack_bf16(d[4 * j0 + 2], d[4 * j0 + 3]), pack_bf16(d[4 * j1 + 2], d[4 * j1 + 3]),
                                      pack_bf16(d[4 * j2 + 2], d[4 * j2 + 3]), pack_bf16(d[4 * j3 + 2], d[4 * j3 + 3]));
                const int m = 4 * hf + mm;
                if (r0 < N) g_T[(size_t)r0 * 32 + 4 * m + q] = o0;
                if (r0 + 8 < N) g_T[(size_t)(r0 + 8) * 32 + 4 * m + q] = o1;
            }
        }
        t_beg = t_stop;
        if (t_beg < t_end) asm volatile("bar.sync 2, %0;" :: "n"(K1_GW * 32) : "memory");
    }
    TSM(threadIdx.x == 0, 2);
}

__device__ __forceinline__ void edge_accum(const uint4 v, const float e, const float a[4], const float cc[4],
                                           float num[4], float den[4]) {
    float y0 = fmaf(bf_lo(v.x), -LOG2E, fmaf(e, cc[0], a[0]));
    float y1 = fmaf(bf_hi(v.x), -LOG2E, fmaf(e, cc[1], a[1]));
    float y2 = fmaf(bf_lo(v.y), -LOG2E, fmaf(e, cc[2], a[2]));
    float y3 = fmaf(bf_hi(v.y), -LOG2E, fmaf(e, cc[3], a[3]));
    float s0 = rcp_approx(1.f + ex2_approx(y0));
    float s1 = rcp_approx(1.f + ex2_approx(y1));
    float s2 = rcp_approx(1.f + ex2_approx(y2));
    float s3 = rcp_approx(1.f + ex2_approx(y3));
    den[0] += s0; den[1] += s1; den[2] += s2; den[3] += s3;
    num[0] = fmaf(s0, bf_lo(v.z), num[0]);
    num[1] = fmaf(s1, bf_hi(v.z), num[1]);
    num[2] = fmaf(s2, bf_lo(v.w), num[2]);
    num[3] = fmaf(s3, bf_hi(v.w), num[3]);
}

#define K2_THREADS 1024
#define K2_D 2
#define K2_GS 2
#define K2_RPT ((BINCAP + K2_THREADS - 1) / K2_THREADS)
#define K2_NW (K2_THREADS / 32)
#define SORT_WORDS (BINCAP + 4 * MAXNB)
#define K2_OFF_W 0
#define K2_OFF_X 65536
#define K2_OFF_A (K2_OFF_X + 32768)
#define K2_OFF_U (K2_OFF_A + MAXNB * 256)
#define K2_OFF_PART (K2_OFF_U + MAXNB * 256)
#define K2_OFF_SORT (K2_OFF_PART + K2_NW * 1024)
#define K2_OFF_HIST (K2_OFF_SORT + SORT_WORDS * 4)
#define K2_OFF_OFF (K2_OFF_HIST + MAXNB * 4)
#define K2_OFF_MBAR (K2_OFF_OFF + (MAXNB + 4) * 4)
#define K2_DYN_SMEM (K2_OFF_MBAR + 16)
#define K2_ST (K2_THREADS - 512)
#define K2_SRPT ((BINCAP + K2_ST - 1) / K2_ST)

struct Grp { uint4 v[K2_GS]; };

__device__ __forceinline__ const uint4* row_ptr(const char* Tl, uint32_t rec) {
    return reinterpret_cast<const uint4*>(Tl + (size_t)((rec & 0xffffu) * 512u));
}
__device__ __forceinline__ void grp_load(Grp& g, const uint32_t* sp, const char* Tl) {
    const uint2 t = *reinterpret_cast<const uint2*>(sp);
    g.v[0] = __ldg(row_ptr(Tl, t.x));
    g.v[1] = __ldg(row_ptr(Tl, t.y));
}
__device__ __forceinline__ void grp_consume(const Grp& g, const uint32_t* sp, const float a[4], const float cc[4],
                                            float num[4], float den[4]) {
    const uint2 t = *reinterpret_cast<const uint2*>(sp);
    edge_accum(g.v[0], bf_hi(t.x), a, cc, num, den);
    edge_accum(g.v[1], bf_hi(t.y), a, cc, num, den);
}

__device__ __forceinline__ void load_a(const uint8_t* smem, int ln, int lane, float a[4]) {
    const uint2 av = reinterpret_cast<const uint2*>(smem + K2_OFF_A)[ln * 32 + (lane ^ ((ln & 3) << 2))];
    a[0] = -LOG2E * bf_lo(av.x); a[1] = -LOG2E * bf_hi(av.x); a[2] = -LOG2E * bf_lo(av.y); a[3] = -LOG2E * bf_hi(av.y);
}
__device__ __forceinline__ void write_node(const uint8_t* smem, __nv_bfloat16* out, int ln, int n,
                                           int lane, const float num[4], const float den[4]) {
    const uint2 uv = reinterpret_cast<const uint2*>(smem + K2_OFF_U)[ln * 32 + (lane ^ ((ln & 3) << 2))];
    const int r = ln & 63, c16 = (lane >> 2) * 2;
    const uint8_t* xr = smem + K2_OFF_X + (ln >> 6) * 16384 + (c16 >> 3) * 8192 + r * 128 + (lane & 3) * 4;
    const uint32_t x0 = *reinterpret_cast<const uint32_t*>(xr + (((c16 & 7) ^ (r & 7)) << 4));
    const uint32_t x1 = *reinterpret_cast<const uint32_t*>(xr + ((((c16 + 1) & 7) ^ (r & 7)) << 4));
    const float u4[4] = { bf_lo(uv.x), bf_hi(uv.x), bf_lo(uv.y), bf_hi(uv.y) };
    const float x4[4] = { bf_lo(x0), bf_hi(x0), bf_lo(x1), bf_hi(x1) };
    float o[4];
    #pragma unroll
    for (int i = 0; i < 4; i++) {
        float agg = round_bf16(__fdividef(num[i], den[i] + 1e-6f));
        float z = round_bf16(u4[i] + agg);
        float rz = (z > 0.f) ? z : 0.f * z;
        o[i] = x4[i] + rz;
    }
    uint32_t* o32 = reinterpret_cast<uint32_t*>(out) + (size_t)n * 64 + (lane >> 2) * 8 + (lane & 3);
    o32[0] = pack_bf16(o[0], o[1]); o32[4] = pack_bf16(o[2], o[3]);
}

__device__ __noinline__ void slow_path(const uint8_t* smem, __nv_bfloat16* out, int node0, int nn, int ovf_n,
                                       float c0, float c1, float c2, float c3) {
    const uint32_t* s_sorted = reinterpret_cast<const uint32_t*>(smem + K2_OFF_SORT);
    const int* s_off = reinterpret_cast<const int*>(smem + K2_OFF_OFF);
    const int lane = threadIdx.x & 31, warp = threadIdx.x >> 5;
    const float cc[4] = { c0, c1, c2, c3 };
    const char* Tl = reinterpret_cast<const char*>(g_T) + lane * 16;
    for (int ln = warp; ln < nn; ln += K2_NW) {
        float a[4];
        load_a(smem, ln, lane, a);
        float num[4] = {0.f, 0.f, 0.f, 0.f}, den[4] = {0.f, 0.f, 0.f, 0.f};
        for (int i = s_off[ln]; i < s_off[ln + 1]; i++) {
            const uint32_t r = s_sorted[i];
            edge_accum(__ldg(row_ptr(Tl, r)), bf_hi(r), a, cc, num, den);
        }
        const int n = node0 + ln;
        for (int base = 0; base < ovf_n; base += 64) {
            int i2 = base + 2 * lane;
            int od = (i2 < ovf_n) ? g_ovf[i2] : -1;
            uint32_t orec = (i2 < ovf_n) ? (uint32_t)g_ovf[i2 + 1] : 0u;
            unsigned msk = __ballot_sync(0xffffffffu, od == n);
            while (msk) {
                int l = __ffs(msk) - 1; msk &= msk - 1;
                uint32_t r = __shfl_sync(0xffffffffu, orec, l);
                edge_accum(__ldg(row_ptr(Tl, r)), bf_hi(r), a, cc, num, den);
            }
        }
        write_node(smem, out, ln, n, lane, num, den);
    }
}

__global__ void __launch_bounds__(K2_THREADS, 1) k2_kernel(
    const __grid_constant__ CUtensorMap tm_x, const __grid_constant__ CUtensorMap tm_wa, const __grid_constant__ CUtensorMap tm_wu,
    const __nv_bfloat16* __restrict__ w_c, __nv_bfloat16* __restrict__ out, int N, int NB)
{
    extern __shared__ __align__(1024) uint8_t smem[];
    float4* s_part = reinterpret_cast<float4*>(smem + K2_OFF_PART);
    uint32_t* s_sorted = reinterpret_cast<uint32_t*>(smem + K2_OFF_SORT);
    int* s_hist = reinterpret_cast<int*>(smem + K2_OFF_HIST);
    int* s_off = reinterpret_cast<int*>(smem + K2_OFF_OFF);

    const int tid = threadIdx.x;
    const int lane = tid & 31, warp = tid >> 5;
    const int bin = blockIdx.x;
    const int node0 = bin * NB;
    const int nn = min(NB, N - node0);
    const uint32_t sb = (uint32_t)__cvta_generic_to_shared(smem);
    TSM(tid == 0, 5);

    const int fw = (lane >> 2) * 8 + (lane & 3);
    const uint2 wc = make_uint2(__ldg(reinterpret_cast<const uint32_t*>(w_c) + fw), __ldg(reinterpret_cast<const uint32_t*>(w_c) + fw + 4));
    s_part[warp * 64 + lane] = make_float4(0.f, 0.f, 0.f, 0.f);
    s_part[warp * 64 + 32 + lane] = make_float4(0.f, 0.f, 0.f, 0.f);
    if (warp < 16) {
        const uint32_t mbar = sb + K2_OFF_MBAR;
        if (tid == 0) {
            mbar_init(mbar, 1);
            mbar_expect_tx(mbar, (nn > 64 ? 32768u : 16384u) + 65536u);
            tma_x_tile(sb + K2_OFF_X, &tm_x, node0, mbar);
            tma_weights(sb + K2_OFF_W, &tm_wa, &tm_wu, mbar);
            if (nn > 64) tma_x_tile(sb + K2_OFF_X + 16384, &tm_x, node0 + 64, mbar);
        }
        asm volatile("bar.sync 2, 512;" ::: "memory");
        mbar_wait(mbar, 0);
        TSM(tid == 0, 6);
        const int wg = warp >> 2, tile = wg >> 1, mtx = wg & 1;
        if (tile * 64 < nn) {
            const uint32_t aaddr = sb + K2_OFF_X + tile * 16384;
            const uint64_t desca = (uint64_t)((aaddr & 0x3FFFF) >> 4) | ((uint64_t)1 << 16) |
                                   ((uint64_t)(1024 >> 4) << 32) | ((uint64_t)1 << 62);
            uint2* dst = reinterpret_cast<uint2*>(smem + (mtx ? K2_OFF_U : K2_OFF_A));
            const int r0 = tile * 64 + (warp & 3) * 16 + (lane >> 2);
            const int sw = (r0 & 3) << 2;
            #pragma unroll 1
            for (int hf = 0; hf < 2; hf++) {
                const uint32_t baddr = sb + K2_OFF_W + (mtx * 2 + hf) * 16384;
                const uint64_t descb = (uint64_t)((baddr & 0x3FFFF) >> 4) | ((uint64_t)(32768 >> 4) << 16) |
                                       ((uint64_t)(1024 >> 4) << 32) | ((uint64_t)1 << 62);
                float d[32];
                asm volatile("wgmma.fence.sync.aligned;" ::: "memory");
                #pragma unroll
                for (int ks = 0; ks < 8; ks++) {
                    wgmma_m64n64k16(d, desca + (uint64_t)(((ks >> 2) * 8192 + (ks & 3) * 32) >> 4),
                                    descb + (uint64_t)(ks * (2048 >> 4)), ks > 0 ? 1 : 0);
                }
                asm volatile("wgmma.commit_group.sync.aligned;" ::: "memory");
                asm volatile("wgmma.wait_group.sync.aligned 0;" ::: "memory");
                TSM(tid == 0 && hf == 0, 15);
                #pragma unroll
                for (int mm = 0; mm < 4; mm++) {
                    const int j0 = 2 * mm, j1 = 2 * mm + 1;
                    const int slot = (4 * (4 * hf + mm) + (lane & 3)) ^ sw;
                    dst[r0 * 32 + slot] = make_uint2(pack_bf16(d[4 * j0], d[4 * j0 + 1]), pack_bf16(d[4 * j1], d[4 * j1 + 1]));
                    dst[(r0 + 8) * 32 + slot] = make_uint2(pack_bf16(d[4 * j0 + 2], d[4 * j0 + 3]), pack_bf16(d[4 * j1 + 2], d[4 * j1 + 3]));
                }
            }
        }
        TSM(tid == 0, 7);
        asm volatile("griddepcontrol.wait;" ::: "memory");
    } else {
        const int st = tid - 512;
        if (st < MAXNB) s_hist[st] = 0;
        for (int i = st; i < SORT_WORDS; i += K2_ST) s_sorted[i] = (uint32_t)N;
        asm volatile("bar.sync 1, %0;" :: "n"(K2_ST) : "memory");
        asm volatile("griddepcontrol.wait;" ::: "memory");
        TSM(st == 0, 8);
        uint2 r[K2_SRPT]; int rk[K2_SRPT];
        const int cnt = min(g_bin_cnt[bin * CNT_STRIDE], BINCAP);
        if (st == 64) s_off[MAXNB + 1] = g_ovf_cnt;
        #pragma unroll
        for (int i = 0; i < K2_SRPT; i++) {
            int idx = i * K2_ST + st;
            if (idx < cnt) r[i] = g_bins[bin * BINCAP + idx];
        }
        #pragma unroll
        for (int i = 0; i < K2_SRPT; i++) {
            int idx = i * K2_ST + st;
            if (idx < cnt) rk[i] = atomicAdd(&s_hist[r[i].y], 1);
        }
        asm volatile("bar.sync 1, %0;" :: "n"(K2_ST) : "memory");
        if (warp == 16) {
            int v[4]; int sum = 0;
            #pragma unroll
            for (int i = 0; i < 4; i++) { v[i] = (s_hist[lane * 4 + i] + K2_GS - 1) & ~(K2_GS - 1); sum += v[i]; }
            int inc = sum;
            #pragma unroll
            for (int o = 1; o < 32; o <<= 1) { int t = __shfl_up_sync(0xffffffffu, inc, o); if (lane >= o) inc += t; }
            int run = inc - sum;
            #pragma unroll
            for (int i = 0; i < 4; i++) { s_off[lane * 4 + i] = run; run += v[i]; }
            if (lane == 31) s_off[MAXNB] = run;
        }
        if (st == 32) g_bin_cnt[bin * CNT_STRIDE] = 0;
        asm volatile("bar.sync 1, %0;" :: "n"(K2_ST) : "memory");
        #pragma unroll
        for (int i = 0; i < K2_SRPT; i++) {
            int idx = i * K2_ST + st;
            if (idx < cnt) s_sorted[s_off[r[i].y] + rk[i]] = r[i].x;
        }
        TSM(st == 0, 9);
    }
    __syncthreads();
    TSM(tid == 0, 10);
    const float cc[4] = { -LOG2E * bf_lo(wc.x), -LOG2E * bf_hi(wc.x), -LOG2E * bf_lo(wc.y), -LOG2E * bf_hi(wc.y) };
    const int ovf_n = s_off[MAXNB + 1];

    if (ovf_n != 0) {
        slow_path(smem, out, node0, nn, ovf_n, cc[0], cc[1], cc[2], cc[3]);
        __syncthreads();
        if (tid == 0) {
            __threadfence();
            int t = atomicAdd(&g_done, 1);
            if (t == (int)gridDim.x - 1) { g_done = 0; __threadfence(); g_ovf_cnt = 0; }
        }
        return;
    }

    const char* Tl = reinterpret_cast<const char*>(g_T) + lane * 16;
    const int G = s_off[MAXNB] / K2_GS;
    int g = (G * warp) / K2_NW;
    const int g1 = (G * (warp + 1)) / K2_NW;
    int ln;
    {
        int c_lo = 0;
        #pragma unroll
        for (int i = 0; i < 4; i++) {
            int node = i * 32 + lane;
            int o = (node < nn) ? s_off[node] : 0x7fffffff;
            c_lo += __popc(__ballot_sync(0xffffffffu, o < g * K2_GS));
        }
        ln = c_lo;
    }
    bool head = ln > 0;
    if (head) ln--;
    float a[4], num[4] = {0.f, 0.f, 0.f, 0.f}, den[4] = {0.f, 0.f, 0.f, 0.f};
    int node_end;

    auto load_node = [&]() {
        load_a(smem, ln, lane, a);
        node_end = s_off[ln + 1] / K2_GS;
    };
    auto finish_node = [&]() { write_node(smem, out, ln, node0 + ln, lane, num, den); };
    auto close_node = [&]() {
        if (head) {
            s_part[warp * 64 + lane] = make_float4(num[0], num[1], num[2], num[3]);
            s_part[warp * 64 + 32 + lane] = make_float4(den[0], den[1], den[2], den[3]);
            head = false;
        } else {
            finish_node();
        }
        #pragma unroll
        for (int i = 0; i < 4; i++) { num[i] = 0.f; den[i] = 0.f; }
    };

    bool tail = false;
    if (g < g1 || warp == K2_NW - 1) {
        load_node();
        Grp b[K2_D];
        #pragma unroll
        for (int d = 0; d < K2_D; d++)
            if (g + d < g1) grp_load(b[d], s_sorted + K2_GS * (g + d), Tl);
        while (g < g1) {
            #pragma unroll
            for (int d = 0; d < K2_D; d++) {
                if (g < g1) {
                    while (g == node_end) { close_node(); ln++; load_node(); }
                    grp_consume(b[d], s_sorted + K2_GS * g, a, cc, num, den);
                    if (g + K2_D < g1) grp_load(b[d], s_sorted + K2_GS * (g + K2_D), Tl);
                    g++;
                }
            }
        }
        if (warp == K2_NW - 1) {
            while (true) { close_node(); ln++; if (ln >= nn) break; load_node(); }
        } else if (node_end == g1 || head) {
            close_node();
        } else {
            tail = true;
        }
    }
    TSM(tid == 0, 11);
    __syncthreads();
    TSM(tid == 0, 12);
    if (tail) {
        for (int w2 = warp + 1; w2 < K2_NW && (G * w2) / K2_NW < node_end; w2++) {
            const float4 pn = s_part[w2 * 64 + lane], pd = s_part[w2 * 64 + 32 + lane];
            num[0] += pn.x; num[1] += pn.y; num[2] += pn.z; num[3] += pn.w;
            den[0] += pd.x; den[1] += pd.y; den[2] += pd.z; den[3] += pd.w;
        }
        finish_node();
    }
}

extern "C" void kernel_launch(void* const* d_in, const int* in_sizes, int n_in,
                              void* d_out, int out_size) {
    const __nv_bfloat16* x      = (const __nv_bfloat16*)d_in[0];
    const __nv_bfloat16* e_attr = (const __nv_bfloat16*)d_in[1];
    const int* src = (const int*)d_in[2];
    const int* dst = (const int*)d_in[3];
    const __nv_bfloat16* w_a = (const __nv_bfloat16*)d_in[4];
    const __nv_bfloat16* w_b = (const __nv_bfloat16*)d_in[5];
    const __nv_bfloat16* w_c = (const __nv_bfloat16*)d_in[6];
    const __nv_bfloat16* w_u = (const __nv_bfloat16*)d_in[7];
    const __nv_bfloat16* w_v = (const __nv_bfloat16*)d_in[8];
    __nv_bfloat16* out = (__nv_bfloat16*)d_out;
    const int N = in_sizes[0] / D_FEAT;
    const int E = in_sizes[2];
    if (N > MAX_N || 2 * E > MAX_E || N <= 0) return;

    static int num_sms = 0;
    if (num_sms == 0) {
        int dev = 0;
        cudaGetDevice(&dev);
        cudaDeviceGetAttribute(&num_sms, cudaDevAttrMultiProcessorCount, dev);
        if (num_sms <= 0 || num_sms > MAXBINS) num_sms = 132;
        cudaFuncSetAttribute(k1_kernel, cudaFuncAttributeMaxDynamicSharedMemorySize, K1_SMEM);
        cudaFuncSetAttribute(k2_kernel, cudaFuncAttributeMaxDynamicSharedMemorySize, K2_DYN_SMEM);
    }
    typedef CUresult (*EncodeFn)(CUtensorMap*, CUtensorMapDataType, cuuint32_t, void*, const cuuint64_t*, const cuuint64_t*,
                                 const cuuint32_t*, const cuuint32_t*, CUtensorMapInterleave, CUtensorMapSwizzle,
                                 CUtensorMapL2promotion, CUtensorMapFloatOOBfill);
    static EncodeFn encode = nullptr;
    if (!encode) {
        void* fn = nullptr;
        cudaDriverEntryPointQueryResult qres;
        if (cudaGetDriverEntryPoint("cuTensorMapEncodeTiled", &fn, cudaEnableDefault, &qres) != cudaSuccess || !fn) return;
        encode = (EncodeFn)fn;
    }
    auto make_map = [&](CUtensorMap* m, const void* base, int rows, int box_rows) {
        cuuint64_t dims[2] = { D_FEAT, (cuuint64_t)rows };
        cuuint64_t strides[1] = { D_FEAT * 2 };
        cuuint32_t box[2] = { 64, (cuuint32_t)box_rows };
        cuuint32_t es[2] = { 1, 1 };
        return encode(m, CU_TENSOR_MAP_DATA_TYPE_BFLOAT16, 2, const_cast<void*>(base), dims, strides, box, es,
                      CU_TENSOR_MAP_INTERLEAVE_NONE, CU_TENSOR_MAP_SWIZZLE_128B, CU_TENSOR_MAP_L2_PROMOTION_L2_128B,
                      CU_TENSOR_MAP_FLOAT_OOB_FILL_NONE);
    };
    CUtensorMap tm_x, tm_wa, tm_wb, tm_wu, tm_wv;
    if (make_map(&tm_x, x, N, 64) != CUDA_SUCCESS || make_map(&tm_wa, w_a, D_FEAT, 128) != CUDA_SUCCESS ||
        make_map(&tm_wb, w_b, D_FEAT, 128) != CUDA_SUCCESS || make_map(&tm_wu, w_u, D_FEAT, 128) != CUDA_SUCCESS ||
        make_map(&tm_wv, w_v, D_FEAT, 128) != CUDA_SUCCESS) return;
    cudaStream_t st = cudaStreamPerThread;
    int NB = (N + num_sms - 1) / num_sms;
    if (NB > MAXNB) NB = MAXNB;
    const int nbins = (N + NB - 1) / NB;
    const uint32_t magic = (uint32_t)(((1u << 24) + NB - 1) / NB);
    const int P = num_sms;
    int chunk = (E + P - 1) / P;
    if (chunk > P1_CHUNK) chunk = P1_CHUNK;
    if (chunk < 1) chunk = 1;
    k1_kernel<<<P, K1_THREADS, K1_SMEM, st>>>(tm_x, tm_wb, tm_wv, x, e_attr, src, dst, w_b, w_v, w_a, w_u, N, E, chunk, NB, nbins, magic);

    cudaLaunchConfig_t cfg = {};
    cfg.gridDim = dim3(nbins);
    cfg.blockDim = dim3(K2_THREADS);
    cfg.dynamicSmemBytes = K2_DYN_SMEM;
    cfg.stream = st;
    cudaLaunchAttribute at[1];
    at[0].id = cudaLaunchAttributeProgrammaticStreamSerialization;
    at[0].val.programmaticStreamSerializationAllowed = 1;
    cfg.attrs = at; cfg.numAttrs = 1;
    cudaLaunchKernelEx(&cfg, k2_kernel, tm_x, tm_wa, tm_wu, w_c, out, N, NB);
}
```

```cpp
#include <cuda_runtime.h>
#include <cuda.h>
#include <cuda_bf16.h>
#include <stdint.h>

#define D_FEAT 128
#define MAX_N 16384
#define MAX_E (1 << 20)
#define LOG2E 1.4426950408889634f

#define MAXBINS 256
#define MAXNB 128
#define BINCAP 3072
__device__ uint4 g_T[(MAX_N + 1) * 32];
#define CNT_STRIDE 1
__device__ int g_bin_cnt[MAXBINS * CNT_STRIDE];
__device__ uint2 g_bins[MAXBINS * BINCAP];
__device__ int g_ovf[MAX_E];
__device__ int g_ovf_cnt;
__device__ int g_done;

#define TSM(cond, i)
__device__ __forceinline__ float ex2_approx(float x) {
    float y; asm("ex2.approx.ftz.f32 %0, %1;" : "=f"(y) : "f"(x)); return y;
}
__device__ __forceinline__ float rcp_approx(float x) {
    float y; asm("rcp.approx.ftz.f32 %0, %1;" : "=f"(y) : "f"(x)); return y;
}
__device__ __forceinline__ uint32_t pack_bf16(float lo, float hi) {
    __nv_bfloat162 t = __floats2bfloat162_rn(lo, hi);
    return *reinterpret_cast<uint32_t*>(&t);
}
__device__ __forceinline__ float bf_lo(uint32_t v) { return __uint_as_float(v << 16); }
__device__ __forceinline__ float bf_hi(uint32_t v) { return __uint_as_float(v & 0xffff0000u); }
__device__ __forceinline__ float round_bf16(float x) { return __bfloat162float(__float2bfloat16_rn(x)); }

__device__ __forceinline__ void mma_bf16(float c[4], uint32_t a0, uint32_t a1, uint32_t a2, uint32_t a3,
                                         uint32_t b0, uint32_t b1) {
    asm volatile("mma.sync.aligned.m16n8k16.row.col.f32.bf16.bf16.f32 "
                 "{%0,%1,%2,%3}, {%4,%5,%6,%7}, {%8,%9}, {%0,%1,%2,%3};"
                 : "+f"(c[0]), "+f"(c[1]), "+f"(c[2]), "+f"(c[3])
                 : "r"(a0), "r"(a1), "r"(a2), "r"(a3), "r"(b0), "r"(b1));
}
__device__ __forceinline__ void ldmatrix_x4_trans(uint32_t& r0, uint32_t& r1, uint32_t& r2, uint32_t& r3, uint32_t addr) {
    asm volatile("ldmatrix.sync.aligned.m8n8.x4.trans.shared.b16 {%0,%1,%2,%3}, [%4];"
                 : "=r"(r0), "=r"(r1), "=r"(r2), "=r"(r3) : "r"(addr));
}

__device__ __forceinline__ void cp_async16(uint32_t saddr, const void* g) {
    asm volatile("cp.async.cg.shared.global [%0], [%1], 16;" :: "r"(saddr), "l"(g) : "memory");
}
__device__ __forceinline__ void cp_async16_zfill(uint32_t saddr, const void* g, int src_size) {
    asm volatile("cp.async.cg.shared.global [%0], [%1], 16, %2;" :: "r"(saddr), "l"(g), "r"(src_size) : "memory");
}
__device__ __forceinline__ void stage_weight(uint32_t sdst, const __nv_bfloat16* w, int mtx, int tid, int nthreads) {
    const uint4* W = reinterpret_cast<const uint4*>(w);
    for (int u = tid; u < 2048; u += nthreads) {
        int k = u >> 4, c16 = u & 15;
        int kg = k >> 3, rr = k & 7;
        int h = mtx * 2 + (c16 >> 3);
        cp_async16(sdst + kg * 4096 + h * 1024 + rr * 128 + (((c16 & 7) ^ rr) << 4), W + u);
    }
}
__device__ __forceinline__ void stage_x_tile(uint32_t sdst, const __nv_bfloat16* x, int row0, int N, int tid, int nthreads) {
    const uint4* X = reinterpret_cast<const uint4*>(x);
    for (int u = tid; u < 1024; u += nthreads) {
        int r = u >> 4, c16 = u & 15;
        int gr = row0 + r;
        bool ok = gr < N;
        cp_async16_zfill(sdst + (c16 >> 3) * 8192 + r * 128 + (((c16 & 7) ^ (r & 7)) << 4),
                         X + (size_t)(ok ? gr : 0) * 16 + c16, ok ? 16 : 0);
    }
}

__device__ __forceinline__ void mbar_init(uint32_t bar, int cnt) {
    asm volatile("mbarrier.init.shared::cta.b64 [%0], %1;" :: "r"(bar), "r"(cnt) : "memory");
    asm volatile("fence.mbarrier_init.release.cluster;" ::: "memory");
    asm volatile("fence.proxy.async.shared::cta;" ::: "memory");
}
__device__ __forceinline__ void mbar_expect_tx(uint32_t bar, uint32_t bytes) {
    asm volatile("mbarrier.arrive.expect_tx.shared::cta.b64 _, [%0], %1;" :: "r"(bar), "r"(bytes) : "memory");
}
__device__ __forceinline__ void mbar_wait(uint32_t bar, uint32_t parity) {
    asm volatile("{\n.reg .pred p;\nWAIT_LOOP:\n"
                 "mbarrier.try_wait.parity.shared::cta.b64 p, [%0], %1;\n"
                 "@p bra WAIT_DONE;\nbra WAIT_LOOP;\nWAIT_DONE:\n}" :: "r"(bar), "r"(parity) : "memory");
}
__device__ __forceinline__ void tma_2d(uint32_t sdst, const CUtensorMap* tm, int c0, int c1, uint32_t bar) {
    asm volatile("cp.async.bulk.tensor.2d.shared::cluster.global.mbarrier::complete_tx::bytes [%0], [%1, {%3, %4}], [%2];"
                 :: "r"(sdst), "l"(reinterpret_cast<uint64_t>(tm)), "r"(bar), "r"(c0), "r"(c1) : "memory");
}
__device__ __forceinline__ void tma_weights(uint32_t sdst, const CUtensorMap* m0, const CUtensorMap* m1, uint32_t bar) {
    tma_2d(sdst, m0, 0, 0, bar);
    tma_2d(sdst + 16384, m0, 64, 0, bar);
    tma_2d(sdst + 32768, m1, 0, 0, bar);
    tma_2d(sdst + 49152, m1, 64, 0, bar);
}
__device__ __forceinline__ void tma_x_tile(uint32_t sdst, const CUtensorMap* mx, int row0, uint32_t bar) {
    tma_2d(sdst, mx, 0, row0, bar);
    tma_2d(sdst + 8192, mx, 64, row0, bar);
}

__device__ __forceinline__ void wgmma_m64n128k16(float d[64], uint64_t desc_a, uint64_t desc_b, int scale_d) {
    asm volatile("{\n.reg .pred p;\nsetp.ne.b32 p, %66, 0;\n"
                 "wgmma.mma_async.sync.aligned.m64n128k16.f32.bf16.bf16 {%0,%1,%2,%3,%4,%5,%6,%7,%8,%9,%10,%11,%12,%13,%14,%15,%16,%17,%18,%19,%20,%21,%22,%23,%24,%25,%26,%27,%28,%29,%30,%31,%32,%33,%34,%35,%36,%37,%38,%39,%40,%41,%42,%43,%44,%45,%46,%47,%48,%49,%50,%51,%52,%53,%54,%55,%56,%57,%58,%59,%60,%61,%62,%63}, %64, %65, p, 1, 1, 0, 1;\n}"
                 : "+f"(d[0]),"+f"(d[1]),"+f"(d[2]),"+f"(d[3]),"+f"(d[4]),"+f"(d[5]),"+f"(d[6]),"+f"(d[7]),"+f"(d[8]),"+f"(d[9]),"+f"(d[10]),"+f"(d[11]),"+f"(d[12]),"+f"(d[13]),"+f"(d[14]),"+f"(d[15]),"+f"(d[16]),"+f"(d[17]),"+f"(d[18]),"+f"(d[19]),"+f"(d[20]),"+f"(d[21]),"+f"(d[22]),"+f"(d[23]),"+f"(d[24]),"+f"(d[25]),"+f"(d[26]),"+f"(d[27]),"+f"(d[28]),"+f"(d[29]),"+f"(d[30]),"+f"(d[31]),"+f"(d[32]),"+f"(d[33]),"+f"(d[34]),"+f"(d[35]),"+f"(d[36]),"+f"(d[37]),"+f"(d[38]),"+f"(d[39]),"+f"(d[40]),"+f"(d[41]),"+f"(d[42]),"+f"(d[43]),"+f"(d[44]),"+f"(d[45]),"+f"(d[46]),"+f"(d[47]),"+f"(d[48]),"+f"(d[49]),"+f"(d[50]),"+f"(d[51]),"+f"(d[52]),"+f"(d[53]),"+f"(d[54]),"+f"(d[55]),"+f"(d[56]),"+f"(d[57]),"+f"(d[58]),"+f"(d[59]),"+f"(d[60]),"+f"(d[61]),"+f"(d[62]),"+f"(d[63])
                 : "l"(desc_a), "l"(desc_b), "r"(scale_d));
}

__device__ __forceinline__ void wgmma_m64n64k16(float d[32], uint64_t desc_a, uint64_t desc_b, int scale_d) {
    asm volatile("{\n.reg .pred p;\nsetp.ne.b32 p, %34, 0;\n"
                 "wgmma.mma_async.sync.aligned.m64n64k16.f32.bf16.bf16 {%0,%1,%2,%3,%4,%5,%6,%7,%8,%9,%10,%11,%12,%13,%14,%15,%16,%17,%18,%19,%20,%21,%22,%23,%24,%25,%26,%27,%28,%29,%30,%31}, %32, %33, p, 1, 1, 0, 1;\n}"
                 : "+f"(d[0]),"+f"(d[1]),"+f"(d[2]),"+f"(d[3]),"+f"(d[4]),"+f"(d[5]),"+f"(d[6]),"+f"(d[7]),"+f"(d[8]),"+f"(d[9]),"+f"(d[10]),"+f"(d[11]),"+f"(d[12]),"+f"(d[13]),"+f"(d[14]),"+f"(d[15]),"+f"(d[16]),"+f"(d[17]),"+f"(d[18]),"+f"(d[19]),"+f"(d[20]),"+f"(d[21]),"+f"(d[22]),"+f"(d[23]),"+f"(d[24]),"+f"(d[25]),"+f"(d[26]),"+f"(d[27]),"+f"(d[28]),"+f"(d[29]),"+f"(d[30]),"+f"(d[31])
                 : "l"(desc_a), "l"(desc_b), "r"(scale_d));
}

#define K1_GW 12
#define P1_T 256
#define K1_THREADS (K1_GW * 32 + P1_T)
#define P1_EPT ((2560 + P1_T - 1) / P1_T)
#define P1_CHUNK (P1_T * P1_EPT)
#define K1_WBYTES (65536 + 2 * 16384)
#define K1_SMEM (K1_WBYTES + 3 * MAXBINS * 4 + P1_CHUNK * 8 + 16)

__device__ __forceinline__ void p1_bar() { asm volatile("bar.sync 1, %0;" :: "n"(P1_T) : "memory"); }

__global__ void __launch_bounds__(K1_THREADS, 1) k1_kernel(
    const __grid_constant__ CUtensorMap tm_x, const __grid_constant__ CUtensorMap tm_wb, const __grid_constant__ CUtensorMap tm_wv,
    const __nv_bfloat16* __restrict__ x, const __nv_bfloat16* __restrict__ e_attr,
    const int* __restrict__ src, const int* __restrict__ dst,
    const __nv_bfloat16* __restrict__ w_b, const __nv_bfloat16* __restrict__ w_v,
    const __nv_bfloat16* __restrict__ w_a, const __nv_bfloat16* __restrict__ w_u,
    int N, int E, int chunk, int NB, int nbins, uint32_t magic)
{
    extern __shared__ __align__(1024) uint8_t smem[];
    asm volatile("griddepcontrol.launch_dependents;");
    TSM(threadIdx.x == 0, 0);

    const int warp = threadIdx.x >> 5, lane = threadIdx.x & 31;

    if (warp >= K1_GW) {
        const int tid = threadIdx.x - K1_GW * 32;
        if (blockIdx.x == 0 && tid < 32)
            g_T[(size_t)N * 32 + tid] = make_uint4(0xff80ff80u, 0xff80ff80u, 0u, 0u);
        int* hist = reinterpret_cast<int*>(smem + K1_WBYTES);
        int* loff = hist + MAXBINS;
        int* gbase = loff + MAXBINS;
        uint2* sorted = reinterpret_cast<uint2*>(smem + K1_WBYTES + 3 * MAXBINS * 4);
        for (int beg = blockIdx.x * chunk; beg < E; beg += gridDim.x * chunk) {
            const int end = min(E, beg + chunk);
            int d[P1_EPT]; uint32_t rec[P1_EPT]; int rk[P1_EPT]; int bn[P1_EPT];
            #pragma unroll
            for (int i = 0; i < P1_EPT; i++) {
                int e = beg + i * P1_T + tid;
                d[i] = -1;
                if (e < end) {
                    d[i] = __ldg(dst + e);
                    uint32_t s = (uint32_t)__ldg(src + e);
                    uint32_t ev = (uint32_t)__ldg(reinterpret_cast<const unsigned short*>(e_attr) + e);
                    rec[i] = (ev << 16) | s;
                }
            }
            if (tid < MAXBINS) hist[tid] = 0;
            TSM(tid == 0 && d[P1_EPT - 2] != -5 && rec[P1_EPT - 2] != 0xfffffff5u, 14);
            p1_bar();
            #pragma unroll
            for (int i = 0; i < P1_EPT; i++) {
                if (d[i] >= 0) {
                    bn[i] = (int)(((uint64_t)(uint32_t)d[i] * magic) >> 24);
                    rk[i] = atomicAdd(&hist[bn[i]], 1);
                }
            }
            p1_bar();
            TSM(tid == 0, 3);
            {
                int h = (tid < MAXBINS) ? hist[tid] : 0;
                if (tid < nbins && h > 0) gbase[tid] = atomicAdd(&g_bin_cnt[tid * CNT_STRIDE], h);
                if (tid < 32) {
                    int v[8]; int sum = 0;
                    #pragma unroll
                    for (int i = 0; i < 8; i++) { v[i] = hist[lane * 8 + i]; sum += v[i]; }
                    int inc = sum;
                    #pragma unroll
                    for (int o = 1; o < 32; o <<= 1) { int t = __shfl_up_sync(0xffffffffu, inc, o); if (lane >= o) inc += t; }
                    int run = inc - sum;
                    #pragma unroll
                    for (int i = 0; i < 8; i++) { loff[lane * 8 + i] = run; run += v[i]; }
                }
            }
            p1_bar();
            #pragma unroll
            for (int i = 0; i < P1_EPT; i++) {
                if (d[i] >= 0) sorted[loff[bn[i]] + rk[i]] = make_uint2(rec[i], (uint32_t)d[i]);
            }
            p1_bar();
            const int cnt = end - beg;
            for (int i = tid; i < cnt; i += P1_T) {
                uint2 r = sorted[i];
                int b = (int)(((uint64_t)r.y * magic) >> 24);
                int pos = gbase[b] + (i - loff[b]);
                if (pos < BINCAP) {
                    g_bins[b * BINCAP + pos] = make_uint2(r.x, r.y - (uint32_t)(b * NB));
                } else {
                    int p = atomicAdd(&g_ovf_cnt, 2);
                    g_ovf[p] = (int)r.y; g_ovf[p + 1] = (int)r.x;
                }
            }
            p1_bar();
        }
        TSM(tid == 0, 4);
        return;
    }

    if (blockIdx.x < 4 && threadIdx.x < 128) {
        const char* pw = reinterpret_cast<const char*>((blockIdx.x & 2) ? w_u : w_a) + (blockIdx.x & 1) * 16384 + threadIdx.x * 128;
        asm volatile("prefetch.global.L2 [%0];" :: "l"(pw));
    }
    const int q = lane & 3;
    const int wg = warp >> 2;
    const int n_tasks = ((N + 63) >> 6) * 2;
    const uint32_t sbase = (uint32_t)__cvta_generic_to_shared(smem);
    const uint32_t xbase = sbase + 65536;
    bool w_staged = false;
    const uint32_t mbar = sbase + K1_SMEM - 16;
    uint32_t phase = 0;
    if (threadIdx.x == 0) mbar_init(mbar, 1);
    int t_beg = (int)(((long long)n_tasks * blockIdx.x) / gridDim.x);
    const int t_end = (int)(((long long)n_tasks * (blockIdx.x + 1)) / gridDim.x);
    while (t_beg < t_end) {
        const int tile0 = t_beg >> 1;
        const int t_stop = min(t_end, (tile0 + 2) << 1);
        if (threadIdx.x == 0) {
            const bool two = ((t_stop - 1) >> 1) > tile0;
            mbar_expect_tx(mbar, (two ? 32768u : 16384u) + (w_staged ? 0u : 65536u));
            tma_x_tile(xbase, &tm_x, tile0 * 64, mbar);
            if (!w_staged) tma_weights(sbase, &tm_wb, &tm_wv, mbar);
            if (two) tma_x_tile(xbase + 16384, &tm_x, tile0 * 64 + 64, mbar);
        }
        if (!w_staged) asm volatile("bar.sync 2, %0;" :: "n"(K1_GW * 32) : "memory");
        w_staged = true;
        mbar_wait(mbar, phase);
        phase ^= 1;
        TSM(threadIdx.x == 0, 1);
        for (int task = t_beg + wg; task < t_stop; task += K1_GW / 4) {
            const int tile = task >> 1, hf = task & 1;
            const uint32_t baddr = sbase + hf * 16384;
            const uint64_t descb = (uint64_t)((baddr & 0x3FFFF) >> 4) | ((uint64_t)(32768 >> 4) << 16) |
                                   ((uint64_t)(1024 >> 4) << 32) | ((uint64_t)1 << 62);
            const uint32_t aaddr = xbase + (tile - tile0) * 16384;
            const uint64_t desca = (uint64_t)((aaddr & 0x3FFFF) >> 4) | ((uint64_t)1 << 16) |
                                   ((uint64_t)(1024 >> 4) << 32) | ((uint64_t)1 << 62);
            float d[64];
            asm volatile("wgmma.fence.sync.aligned;" ::: "memory");
            #pragma unroll
            for (int ks = 0; ks < 8; ks++) {
                wgmma_m64n128k16(d, desca + (uint64_t)(((ks >> 2) * 8192 + (ks & 3) * 32) >> 4),
                                 descb + (uint64_t)(ks * (2048 >> 4)), ks > 0 ? 1 : 0);
            }
            asm volatile("wgmma.commit_group.sync.aligned;" ::: "memory");
            asm volatile("wgmma.wait_group.sync.aligned 0;" ::: "memory");
            TSM(threadIdx.x == 0, 13);
            const int r0 = tile * 64 + (warp & 3) * 16 + (lane >> 2);
            #pragma unroll
            for (int mm = 0; mm < 4; mm++) {
                const int j0 = 2 * mm, j1 = 2 * mm + 1, j2 = 8 + 2 * mm, j3 = 9 + 2 * mm;
                uint4 o0 = make_uint4(pack_bf16(d[4 * j0], d[4 * j0 + 1]), pack_bf16(d[4 * j1], d[4 * j1 + 1]),
                                      pack_bf16(d[4 * j2], d[4 * j2 + 1]), pack_bf16(d[4 * j3], d[4 * j3 + 1]));
                uint4 o1 = make_uint4(pack_bf16(d[4 * j0 + 2], d[4 * j0 + 3]), pack_bf16(d[4 * j1 + 2], d[4 * j1 + 3]),
                                      pack_bf16(d[4 * j2 + 2], d[4 * j2 + 3]), pack_bf16(d[4 * j3 + 2], d[4 * j3 + 3]));
                const int m = 4 * hf + mm;
                if (r0 < N) g_T[(size_t)r0 * 32 + 4 * m + q] = o0;
                if (r0 + 8 < N) g_T[(size_t)(r0 + 8) * 32 + 4 * m + q] = o1;
            }
        }
        t_beg = t_stop;
        if (t_beg < t_end) asm volatile("bar.sync 2, %0;" :: "n"(K1_GW * 32) : "memory");
    }
    TSM(threadIdx.x == 0, 2);
}

__device__ __forceinline__ void edge_accum(const uint4 v, const float e, const float a[4], const float cc[4],
                                           float num[4], float den[4]) {
    float y0 = fmaf(bf_lo(v.x), -LOG2E, fmaf(e, cc[0], a[0]));
    float y1 = fmaf(bf_hi(v.x), -LOG2E, fmaf(e, cc[1], a[1]));
    float y2 = fmaf(bf_lo(v.y), -LOG2E, fmaf(e, cc[2], a[2]));
    float y3 = fmaf(bf_hi(v.y), -LOG2E, fmaf(e, cc[3], a[3]));
    float s0 = rcp_approx(1.f + ex2_approx(y0));
    float s1 = rcp_approx(1.f + ex2_approx(y1));
    float s2 = rcp_approx(1.f + ex2_approx(y2));
    float s3 = rcp_approx(1.f + ex2_approx(y3));
    den[0] += s0; den[1] += s1; den[2] += s2; den[3] += s3;
    num[0] = fmaf(s0, bf_lo(v.z), num[0]);
    num[1] = fmaf(s1, bf_hi(v.z), num[1]);
    num[2] = fmaf(s2, bf_lo(v.w), num[2]);
    num[3] = fmaf(s3, bf_hi(v.w), num[3]);
}

#define K2_THREADS 1024
#define K2_D 2
#define K2_GS 2
#define K2_RPT ((BINCAP + K2_THREADS - 1) / K2_THREADS)
#define K2_NW (K2_THREADS / 32)
#define SORT_WORDS (BINCAP + 4 * MAXNB)
#define K2_OFF_W 0
#define K2_OFF_X 65536
#define K2_OFF_A (K2_OFF_X + 32768)
#define K2_OFF_U (K2_OFF_A + MAXNB * 256)
#define K2_OFF_PART (K2_OFF_U + MAXNB * 256)
#define K2_OFF_SORT (K2_OFF_PART + K2_NW * 1024)
#define K2_OFF_HIST (K2_OFF_SORT + SORT_WORDS * 4)
#define K2_OFF_OFF (K2_OFF_HIST + MAXNB * 4)
#define K2_OFF_MBAR (K2_OFF_OFF + (MAXNB + 4) * 4)
#define K2_DYN_SMEM (K2_OFF_MBAR + 16)
#define K2_ST (K2_THREADS - 512)
#define K2_SRPT ((BINCAP + K2_ST - 1) / K2_ST)

struct Grp { uint4 v[K2_GS]; };

__device__ __forceinline__ const uint4* row_ptr(const char* Tl, uint32_t rec) {
    return reinterpret_cast<const uint4*>(Tl + (size_t)((rec & 0xffffu) * 512u));
}
__device__ __forceinline__ void grp_load(Grp& g, const uint32_t* sp, const char* Tl) {
    const uint2 t = *reinterpret_cast<const uint2*>(sp);
    g.v[0] = __ldg(row_ptr(Tl, t.x));
    g.v[1] = __ldg(row_ptr(Tl, t.y));
}
__device__ __forceinline__ void grp_consume(const Grp& g, const uint32_t* sp, const float a[4], const float cc[4],
                                            float num[4], float den[4]) {
    const uint2 t = *reinterpret_cast<const uint2*>(sp);
    edge_accum(g.v[0], bf_hi(t.x), a, cc, num, den);
    edge_accum(g.v[1], bf_hi(t.y), a, cc, num, den);
}

__device__ __forceinline__ void load_a(const uint8_t* smem, int ln, int lane, float a[4]) {
    const uint2 av = reinterpret_cast<const uint2*>(smem + K2_OFF_A)[ln * 32 + (lane ^ ((ln & 3) << 2))];
    a[0] = -LOG2E * bf_lo(av.x); a[1] = -LOG2E * bf_hi(av.x); a[2] = -LOG2E * bf_lo(av.y); a[3] = -LOG2E * bf_hi(av.y);
}
__device__ __forceinline__ void write_node(const uint8_t* smem, __nv_bfloat16* out, int ln, int n,
                                           int lane, const float num[4], const float den[4]) {
    const uint2 uv = reinterpret_cast<const uint2*>(smem + K2_OFF_U)[ln * 32 + (lane ^ ((ln & 3) << 2))];
    const int r = ln & 63, c16 = (lane >> 2) * 2;
    const uint8_t* xr = smem + K2_OFF_X + (ln >> 6) * 16384 + (c16 >> 3) * 8192 + r * 128 + (lane & 3) * 4;
    const uint32_t x0 = *reinterpret_cast<const uint32_t*>(xr + (((c16 & 7) ^ (r & 7)) << 4));
    const uint32_t x1 = *reinterpret_cast<const uint32_t*>(xr + ((((c16 + 1) & 7) ^ (r & 7)) << 4));
    const float u4[4] = { bf_lo(uv.x), bf_hi(uv.x), bf_lo(uv.y), bf_hi(uv.y) };
    const float x4[4] = { bf_lo(x0), bf_hi(x0), bf_lo(x1), bf_hi(x1) };
    float o[4];
    #pragma unroll
    for (int i = 0; i < 4; i++) {
        float agg = round_bf16(__fdividef(num[i], den[i] + 1e-6f));
        float z = round_bf16(u4[i] + agg);
        float rz = (z > 0.f) ? z : 0.f * z;
        o[i] = x4[i] + rz;
    }
    uint32_t* o32 = reinterpret_cast<uint32_t*>(out) + (size_t)n * 64 + (lane >> 2) * 8 + (lane & 3);
    o32[0] = pack_bf16(o[0], o[1]); o32[4] = pack_bf16(o[2], o[3]);
}

__device__ __noinline__ void slow_path(const uint8_t* smem, __nv_bfloat16* out, int node0, int nn, int ovf_n,
                                       float c0, float c1, float c2, float c3) {
    const uint32_t* s_sorted = reinterpret_cast<const uint32_t*>(smem + K2_OFF_SORT);
    const int* s_off = reinterpret_cast<const int*>(smem + K2_OFF_OFF);
    const int lane = threadIdx.x & 31, warp = threadIdx.x >> 5;
    const float cc[4] = { c0, c1, c2, c3 };
    const char* Tl = reinterpret_cast<const char*>(g_T) + lane * 16;
    for (int ln = warp; ln < nn; ln += K2_NW) {
        float a[4];
        load_a(smem, ln, lane, a);
        float num[4] = {0.f, 0.f, 0.f, 0.f}, den[4] = {0.f, 0.f, 0.f, 0.f};
        for (int i = s_off[ln]; i < s_off[ln + 1]; i++) {
            const uint32_t r = s_sorted[i];
            edge_accum(__ldg(row_ptr(Tl, r)), bf_hi(r), a, cc, num, den);
        }
        const int n = node0 + ln;
        for (int base = 0; base < ovf_n; base += 64) {
            int i2 = base + 2 * lane;
            int od = (i2 < ovf_n) ? g_ovf[i2] : -1;
            uint32_t orec = (i2 < ovf_n) ? (uint32_t)g_ovf[i2 + 1] : 0u;
            unsigned msk = __ballot_sync(0xffffffffu, od == n);
            while (msk) {
                int l = __ffs(msk) - 1; msk &= msk - 1;
                uint32_t r = __shfl_sync(0xffffffffu, orec, l);
                edge_accum(__ldg(row_ptr(Tl, r)), bf_hi(r), a, cc, num, den);
            }
        }
        write_node(smem, out, ln, n, lane, num, den);
    }
}

__global__ void __launch_bounds__(K2_THREADS, 1) k2_kernel(
    const __grid_constant__ CUtensorMap tm_x, const __grid_constant__ CUtensorMap tm_wa, const __grid_constant__ CUtensorMap tm_wu,
    const __nv_bfloat16* __restrict__ w_c, __nv_bfloat16* __restrict__ out, int N, int NB)
{
    extern __shared__ __align__(1024) uint8_t smem[];
    float4* s_part = reinterpret_cast<float4*>(smem + K2_OFF_PART);
    uint32_t* s_sorted = reinterpret_cast<uint32_t*>(smem + K2_OFF_SORT);
    int* s_hist = reinterpret_cast<int*>(smem + K2_OFF_HIST);
    int* s_off = reinterpret_cast<int*>(smem + K2_OFF_OFF);

    const int tid = threadIdx.x;
    const int lane = tid & 31, warp = tid >> 5;
    const int bin = blockIdx.x;
    const int node0 = bin * NB;
    const int nn = min(NB, N - node0);
    const uint32_t sb = (uint32_t)__cvta_generic_to_shared(smem);
    TSM(tid == 0, 5);

    const int fw = (lane >> 2) * 8 + (lane & 3);
    const uint2 wc = make_uint2(__ldg(reinterpret_cast<const uint32_t*>(w_c) + fw), __ldg(reinterpret_cast<const uint32_t*>(w_c) + fw + 4));
    s_part[warp * 64 + lane] = make_float4(0.f, 0.f, 0.f, 0.f);
    s_part[warp * 64 + 32 + lane] = make_float4(0.f, 0.f, 0.f, 0.f);
    if (warp < 16) {
        const uint32_t mbar = sb + K2_OFF_MBAR;
        if (tid == 0) {
            mbar_init(mbar, 1);
            mbar_expect_tx(mbar, (nn > 64 ? 32768u : 16384u) + 65536u);
            tma_x_tile(sb + K2_OFF_X, &tm_x, node0, mbar);
            tma_weights(sb + K2_OFF_W, &tm_wa, &tm_wu, mbar);
            if (nn > 64) tma_x_tile(sb + K2_OFF_X + 16384, &tm_x, node0 + 64, mbar);
        }
        asm volatile("bar.sync 2, 512;" ::: "memory");
        mbar_wait(mbar, 0);
        TSM(tid == 0, 6);
        const int wg = warp >> 2, tile = wg >> 1, mtx = wg & 1;
        if (tile * 64 < nn) {
            const uint32_t aaddr = sb + K2_OFF_X + tile * 16384;
            const uint64_t desca = (uint64_t)((aaddr & 0x3FFFF) >> 4) | ((uint64_t)1 << 16) |
                                   ((uint64_t)(1024 >> 4) << 32) | ((uint64_t)1 << 62);
            uint2* dst = reinterpret_cast<uint2*>(smem + (mtx ? K2_OFF_U : K2_OFF_A));
            const int r0 = tile * 64 + (warp & 3) * 16 + (lane >> 2);
            const int sw = (r0 & 3) << 2;
            #pragma unroll 1
            for (int hf = 0; hf < 2; hf++) {
                const uint32_t baddr = sb + K2_OFF_W + (mtx * 2 + hf) * 16384;
                const uint64_t descb = (uint64_t)((baddr & 0x3FFFF) >> 4) | ((uint64_t)(32768 >> 4) << 16) |
                                       ((uint64_t)(1024 >> 4) << 32) | ((uint64_t)1 << 62);
                float d[32];
                asm volatile("wgmma.fence.sync.aligned;" ::: "memory");
                #pragma unroll
                for (int ks = 0; ks < 8; ks++) {
                    wgmma_m64n64k16(d, desca + (uint64_t)(((ks >> 2) * 8192 + (ks & 3) * 32) >> 4),
                                    descb + (uint64_t)(ks * (2048 >> 4)), ks > 0 ? 1 : 0);
                }
                asm volatile("wgmma.commit_group.sync.aligned;" ::: "memory");
                asm volatile("wgmma.wait_group.sync.aligned 0;" ::: "memory");
                TSM(tid == 0 && hf == 0, 15);
                #pragma unroll
                for (int mm = 0; mm < 4; mm++) {
                    const int j0 = 2 * mm, j1 = 2 * mm + 1;
                    const int slot = (4 * (4 * hf + mm) + (lane & 3)) ^ sw;
                    dst[r0 * 32 + slot] = make_uint2(pack_bf16(d[4 * j0], d[4 * j0 + 1]), pack_bf16(d[4 * j1], d[4 * j1 + 1]));
                    dst[(r0 + 8) * 32 + slot] = make_uint2(pack_bf16(d[4 * j0 + 2], d[4 * j0 + 3]), pack_bf16(d[4 * j1 + 2], d[4 * j1 + 3]));
                }
            }
        }
        TSM(tid == 0, 7);
        asm volatile("griddepcontrol.wait;" ::: "memory");
    } else {
        const int st = tid - 512;
        if (st < MAXNB) s_hist[st] = 0;
        for (int i = st; i < SORT_WORDS; i += K2_ST) s_sorted[i] = (uint32_t)N;
        asm volatile("bar.sync 1, %0;" :: "n"(K2_ST) : "memory");
        asm volatile("griddepcontrol.wait;" ::: "memory");
        TSM(st == 0, 8);
        uint2 r[K2_SRPT]; int rk[K2_SRPT];
        const int cnt = min(g_bin_cnt[bin * CNT_STRIDE], BINCAP);
        if (st == 64) s_off[MAXNB + 1] = g_ovf_cnt;
        #pragma unroll
        for (int i = 0; i < K2_SRPT; i++) {
            int idx = i * K2_ST + st;
            if (idx < cnt) r[i] = g_bins[bin * BINCAP + idx];
        }
        #pragma unroll
        for (int i = 0; i < K2_SRPT; i++) {
            int idx = i * K2_ST + st;
            if (idx < cnt) rk[i] = atomicAdd(&s_hist[r[i].y], 1);
        }
        asm volatile("bar.sync 1, %0;" :: "n"(K2_ST) : "memory");
        if (warp == 16) {
            int v[4]; int sum = 0;
            #pragma unroll
            for (int i = 0; i < 4; i++) { v[i] = (s_hist[lane * 4 + i] + K2_GS - 1) & ~(K2_GS - 1); sum += v[i]; }
            int inc = sum;
            #pragma unroll
            for (int o = 1; o < 32; o <<= 1) { int t = __shfl_up_sync(0xffffffffu, inc, o); if (lane >= o) inc += t; }
            int run = inc - sum;
            #pragma unroll
            for (int i = 0; i < 4; i++) { s_off[lane * 4 + i] = run; run += v[i]; }
            if (lane == 31) s_off[MAXNB] = run;
        }
        if (st == 32) g_bin_cnt[bin * CNT_STRIDE] = 0;
        asm volatile("bar.sync 1, %0;" :: "n"(K2_ST) : "memory");
        #pragma unroll
        for (int i = 0; i < K2_SRPT; i++) {
            int idx = i * K2_ST + st;
            if (idx < cnt) s_sorted[s_off[r[i].y] + rk[i]] = r[i].x;
        }
        TSM(st == 0, 9);
    }
    __syncthreads();
    TSM(tid == 0, 10);
    const float cc[4] = { -LOG2E * bf_lo(wc.x), -LOG2E * bf_hi(wc.x), -LOG2E * bf_lo(wc.y), -LOG2E * bf_hi(wc.y) };
    const int ovf_n = s_off[MAXNB + 1];

    if (ovf_n != 0) {
        slow_path(smem, out, node0, nn, ovf_n, cc[0], cc[1], cc[2], cc[3]);
        __syncthreads();
        if (tid == 0) {
            __threadfence();
            int t = atomicAdd(&g_done, 1);
            if (t == (int)gridDim.x - 1) { g_done = 0; __threadfence(); g_ovf_cnt = 0; }
        }
        return;
    }

    const char* Tl = reinterpret_cast<const char*>(g_T) + lane * 16;
    const int G = s_off[MAXNB] / K2_GS;
    int g = (G * warp) / K2_NW;
    const int g1 = (G * (warp + 1)) / K2_NW;
    int ln;
    {
        int c_lo = 0;
        #pragma unroll
        for (int i = 0; i < 4; i++) {
            int node = i * 32 + lane;
            int o = (node < nn) ? s_off[node] : 0x7fffffff;
            c_lo += __popc(__ballot_sync(0xffffffffu, o < g * K2_GS));
        }
        ln = c_lo;
    }
    bool head = ln > 0;
    if (head) ln--;
    float a[4], num[4] = {0.f, 0.f, 0.f, 0.f}, den[4] = {0.f, 0.f, 0.f, 0.f};
    int node_end;

    auto load_node = [&]() {
        load_a(smem, ln, lane, a);
        node_end = s_off[ln + 1] / K2_GS;
    };
    auto finish_node = [&]() { write_node(smem, out, ln, node0 + ln, lane, num, den); };
    auto close_node = [&]() {
        if (head) {
            s_part[warp * 64 + lane] = make_float4(num[0], num[1], num[2], num[3]);
            s_part[warp * 64 + 32 + lane] = make_float4(den[0], den[1], den[2], den[3]);
            head = false;
        } else {
            finish_node();
        }
        #pragma unroll
        for (int i = 0; i < 4; i++) { num[i] = 0.f; den[i] = 0.f; }
    };

    bool tail = false;
    if (g < g1 || warp == K2_NW - 1) {
        load_node();
        Grp b[K2_D];
        #pragma unroll
        for (int d = 0; d < K2_D; d++)
            if (g + d < g1) grp_load(b[d], s_sorted + K2_GS * (g + d), Tl);
        while (g < g1) {
            #pragma unroll
            for (int d = 0; d < K2_D; d++) {
                if (g < g1) {
                    while (g == node_end) { close_node(); ln++; load_node(); }
                    grp_consume(b[d], s_sorted + K2_GS * g, a, cc, num, den);
                    if (g + K2_D < g1) grp_load(b[d], s_sorted + K2_GS * (g + K2_D), Tl);
                    g++;
                }
            }
        }
        if (warp == K2_NW - 1) {
            while (true) { close_node(); ln++; if (ln >= nn) break; load_node(); }
        } else if (node_end == g1 || head) {
            close_node();
        } else {
            tail = true;
        }
    }
    TSM(tid == 0, 11);
    __syncthreads();
    TSM(tid == 0, 12);
    if (tail) {
        for (int w2 = warp + 1; w2 < K2_NW && (G * w2) / K2_NW < node_end; w2++) {
            const float4 pn = s_part[w2 * 64 + lane], pd = s_part[w2 * 64 + 32 + lane];
            num[0] += pn.x; num[1] += pn.y; num[2] += pn.z; num[3] += pn.w;
            den[0] += pd.x; den[1] += pd.y; den[2] += pd.z; den[3] += pd.w;
        }
        finish_node();
    }
}

extern "C" void kernel_launch(void* const* d_in, const int* in_sizes, int n_in,
                              void* d_out, int out_size) {
    const __nv_bfloat16* x      = (const __nv_bfloat16*)d_in[0];
    const __nv_bfloat16* e_attr = (const __nv_bfloat16*)d_in[1];
    const int* src = (const int*)d_in[2];
    const int* dst = (const int*)d_in[3];
    const __nv_bfloat16* w_a = (const __nv_bfloat16*)d_in[4];
    const __nv_bfloat16* w_b = (const __nv_bfloat16*)d_in[5];
    const __nv_bfloat16* w_c = (const __nv_bfloat16*)d_in[6];
    const __nv_bfloat16* w_u = (const __nv_bfloat16*)d_in[7];
    const __nv_bfloat16* w_v = (const __nv_bfloat16*)d_in[8];
    __nv_bfloat16* out = (__nv_bfloat16*)d_out;
    const int N = in_sizes[0] / D_FEAT;
    const int E = in_sizes[2];
    if (N > MAX_N || 2 * E > MAX_E || N <= 0) return;

    static int num_sms = 0;
    if (num_sms == 0) {
        int dev = 0;
        cudaGetDevice(&dev);
        cudaDeviceGetAttribute(&num_sms, cudaDevAttrMultiProcessorCount, dev);
        if (num_sms <= 0 || num_sms > MAXBINS) num_sms = 132;
        cudaFuncSetAttribute(k1_kernel, cudaFuncAttributeMaxDynamicSharedMemorySize, K1_SMEM);
        cudaFuncSetAttribute(k2_kernel, cudaFuncAttributeMaxDynamicSharedMemorySize, K2_DYN_SMEM);
    }
    typedef CUresult (*EncodeFn)(CUtensorMap*, CUtensorMapDataType, cuuint32_t, void*, const cuuint64_t*, const cuuint64_t*,
                                 const cuuint32_t*, const cuuint32_t*, CUtensorMapInterleave, CUtensorMapSwizzle,
                                 CUtensorMapL2promotion, CUtensorMapFloatOOBfill);
    static EncodeFn encode = nullptr;
    if (!encode) {
        void* fn = nullptr;
        cudaDriverEntryPointQueryResult qres;
        if (cudaGetDriverEntryPoint("cuTensorMapEncodeTiled", &fn, cudaEnableDefault, &qres) != cudaSuccess || !fn) return;
        encode = (EncodeFn)fn;
    }
    auto make_map = [&](CUtensorMap* m, const void* base, int rows, int box_rows) {
        cuuint64_t dims[2] = { D_FEAT, (cuuint64_t)rows };
        cuuint64_t strides[1] = { D_FEAT * 2 };
        cuuint32_t box[2] = { 64, (cuuint32_t)box_rows };
        cuuint32_t es[2] = { 1, 1 };
        return encode(m, CU_TENSOR_MAP_DATA_TYPE_BFLOAT16, 2, const_cast<void*>(base), dims, strides, box, es,
                      CU_TENSOR_MAP_INTERLEAVE_NONE, CU_TENSOR_MAP_SWIZZLE_128B, CU_TENSOR_MAP_L2_PROMOTION_L2_128B,
                      CU_TENSOR_MAP_FLOAT_OOB_FILL_NONE);
    };
    CUtensorMap tm_x, tm_wa, tm_wb, tm_wu, tm_wv;
    if (make_map(&tm_x, x, N, 64) != CUDA_SUCCESS || make_map(&tm_wa, w_a, D_FEAT, 128) != CUDA_SUCCESS ||
        make_map(&tm_wb, w_b, D_FEAT, 128) != CUDA_SUCCESS || make_map(&tm_wu, w_u, D_FEAT, 128) != CUDA_SUCCESS ||
        make_map(&tm_wv, w_v, D_FEAT, 128) != CUDA_SUCCESS) return;
    cudaStream_t st = cudaStreamPerThread;
    int NB = (N + num_sms - 1) / num_sms;
    if (NB > MAXNB) NB = MAXNB;
    const int nbins = (N + NB - 1) / NB;
    const uint32_t magic = (uint32_t)(((1u << 24) + NB - 1) / NB);
    const int P = num_sms;
    int chunk = (E + P - 1) / P;
    if (chunk > P1_CHUNK) chunk = P1_CHUNK;
    if (chunk < 1) chunk = 1;
    k1_kernel<<<P, K1_THREADS, K1_SMEM, st>>>(tm_x, tm_wb, tm_wv, x, e_attr, src, dst, w_b, w_v, w_a, w_u, N, E, chunk, NB, nbins, magic);

    cudaLaunchConfig_t cfg = {};
    cfg.gridDim = dim3(nbins);
    cfg.blockDim = dim3(K2_THREADS);
    cfg.dynamicSmemBytes = K2_DYN_SMEM;
    cfg.stream = st;
    cudaLaunchAttribute at[1];
    at[0].id = cudaLaunchAttributeProgrammaticStreamSerialization;
    at[0].val.programmaticStreamSerializationAllowed = 1;
    cfg.attrs = at; cfg.numAttrs = 1;
    cudaLaunchKernelEx(&cfg, k2_kernel, tm_x, tm_wa, tm_wu, w_c, out, N, NB);
}
```

```cpp
#include <cuda_runtime.h>
#include <cuda.h>
#include <cuda_bf16.h>
#include <stdint.h>

#define D_FEAT 128
#define MAX_N 16384
#define MAX_E (1 << 20)
#define LOG2E 1.4426950408889634f

#define MAXBINS 256
#define MAXNB 128
#define BINCAP 3072
__device__ uint4 g_T[(MAX_N + 1) * 32];
#define CNT_STRIDE 1
__device__ int g_bin_cnt[MAXBINS * CNT_STRIDE];
__device__ uint2 g_bins[MAXBINS * BINCAP];
__device__ int g_ovf[MAX_E];
__device__ int g_ovf_cnt;
__device__ int g_done;

#define TSM(cond, i)
__device__ __forceinline__ float ex2_approx(float x) {
    float y; asm("ex2.approx.ftz.f32 %0, %1;" : "=f"(y) : "f"(x)); return y;
}
__device__ __forceinline__ float rcp_approx(float x) {
    float y; asm("rcp.approx.ftz.f32 %0, %1;" : "=f"(y) : "f"(x)); return y;
}
__device__ __forceinline__ uint32_t pack_bf16(float lo, float hi) {
    __nv_bfloat162 t = __floats2bfloat162_rn(lo, hi);
    return *reinterpret_cast<uint32_t*>(&t);
}
__device__ __forceinline__ float bf_lo(uint32_t v) { return __uint_as_float(v << 16); }
__device__ __forceinline__ float bf_hi(uint32_t v) { return __uint_as_float(v & 0xffff0000u); }
__device__ __forceinline__ float round_bf16(float x) { return __bfloat162float(__float2bfloat16_rn(x)); }

__device__ __forceinline__ void mma_bf16(float c[4], uint32_t a0, uint32_t a1, uint32_t a2, uint32_t a3,
                                         uint32_t b0, uint32_t b1) {
    asm volatile("mma.sync.aligned.m16n8k16.row.col.f32.bf16.bf16.f32 "
                 "{%0,%1,%2,%3}, {%4,%5,%6,%7}, {%8,%9}, {%0,%1,%2,%3};"
                 : "+f"(c[0]), "+f"(c[1]), "+f"(c[2]), "+f"(c[3])
                 : "r"(a0), "r"(a1), "r"(a2), "r"(a3), "r"(b0), "r"(b1));
}
__device__ __forceinline__ void ldmatrix_x4_trans(uint32_t& r0, uint32_t& r1, uint32_t& r2, uint32_t& r3, uint32_t addr) {
    asm volatile("ldmatrix.sync.aligned.m8n8.x4.trans.shared.b16 {%0,%1,%2,%3}, [%4];"
                 : "=r"(r0), "=r"(r1), "=r"(r2), "=r"(r3) : "r"(addr));
}

__device__ __forceinline__ void cp_async16(uint32_t saddr, const void* g) {
    asm volatile("cp.async.cg.shared.global [%0], [%1], 16;" :: "r"(saddr), "l"(g) : "memory");
}
__device__ __forceinline__ void cp_async16_zfill(uint32_t saddr, const void* g, int src_size) {
    asm volatile("cp.async.cg.shared.global [%0], [%1], 16, %2;" :: "r"(saddr), "l"(g), "r"(src_size) : "memory");
}
__device__ __forceinline__ void stage_weight(uint32_t sdst, const __nv_bfloat16* w, int mtx, int tid, int nthreads) {
    const uint4* W = reinterpret_cast<const uint4*>(w);
    for (int u = tid; u < 2048; u += nthreads) {
        int k = u >> 4, c16 = u & 15;
        int kg = k >> 3, rr = k & 7;
        int h = mtx * 2 + (c16 >> 3);
        cp_async16(sdst + kg * 4096 + h * 1024 + rr * 128 + (((c16 & 7) ^ rr) << 4), W + u);
    }
}
__device__ __forceinline__ void stage_x_tile(uint32_t sdst, const __nv_bfloat16* x, int row0, int N, int tid, int nthreads) {
    const uint4* X = reinterpret_cast<const uint4*>(x);
    for (int u = tid; u < 1024; u += nthreads) {
        int r = u >> 4, c16 = u & 15;
        int gr = row0 + r;
        bool ok = gr < N;
        cp_async16_zfill(sdst + (c16 >> 3) * 8192 + r * 128 + (((c16 & 7) ^ (r & 7)) << 4),
                         X + (size_t)(ok ? gr : 0) * 16 + c16, ok ? 16 : 0);
    }
}

__device__ __forceinline__ void mbar_init(uint32_t bar, int cnt) {
    asm volatile("mbarrier.init.shared::cta.b64 [%0], %1;" :: "r"(bar), "r"(cnt) : "memory");
    asm volatile("fence.mbarrier_init.release.cluster;" ::: "memory");
    asm volatile("fence.proxy.async.shared::cta;" ::: "memory");
}
__device__ __forceinline__ void mbar_expect_tx(uint32_t bar, uint32_t bytes) {
    asm volatile("mbarrier.arrive.expect_tx.shared::cta.b64 _, [%0], %1;" :: "r"(bar), "r"(bytes) : "memory");
}
__device__ __forceinline__ void mbar_wait(uint32_t bar, uint32_t parity) {
    asm volatile("{\n.reg .pred p;\nWAIT_LOOP:\n"
                 "mbarrier.try_wait.parity.shared::cta.b64 p, [%0], %1;\n"
                 "@p bra WAIT_DONE;\nbra WAIT_LOOP;\nWAIT_DONE:\n}" :: "r"(bar), "r"(parity) : "memory");
}
__device__ __forceinline__ void tma_2d(uint32_t sdst, const CUtensorMap* tm, int c0, int c1, uint32_t bar) {
    asm volatile("cp.async.bulk.tensor.2d.shared::cluster.global.mbarrier::complete_tx::bytes [%0], [%1, {%3, %4}], [%2];"
                 :: "r"(sdst), "l"(reinterpret_cast<uint64_t>(tm)), "r"(bar), "r"(c0), "r"(c1) : "memory");
}
__device__ __forceinline__ void tma_weights(uint32_t sdst, const CUtensorMap* m0, const CUtensorMap* m1, uint32_t bar) {
    tma_2d(sdst, m0, 0, 0, bar);
    tma_2d(sdst + 16384, m0, 64, 0, bar);
    tma_2d(sdst + 32768, m1, 0, 0, bar);
    tma_2d(sdst + 49152, m1, 64, 0, bar);
}
__device__ __forceinline__ void tma_x_tile(uint32_t sdst, const CUtensorMap* mx, int row0, uint32_t bar) {
    tma_2d(sdst, mx, 0, row0, bar);
    tma_2d(sdst + 8192, mx, 64, row0, bar);
}

__device__ __forceinline__ void wgmma_m64n128k16(float d[64], uint64_t desc_a, uint64_t desc_b, int scale_d) {
    asm volatile("{\n.reg .pred p;\nsetp.ne.b32 p, %66, 0;\n"
                 "wgmma.mma_async.sync.aligned.m64n128k16.f32.bf16.bf16 {%0,%1,%2,%3,%4,%5,%6,%7,%8,%9,%10,%11,%12,%13,%14,%15,%16,%17,%18,%19,%20,%21,%22,%23,%24,%25,%26,%27,%28,%29,%30,%31,%32,%33,%34,%35,%36,%37,%38,%39,%40,%41,%42,%43,%44,%45,%46,%47,%48,%49,%50,%51,%52,%53,%54,%55,%56,%57,%58,%59,%60,%61,%62,%63}, %64, %65, p, 1, 1, 0, 1;\n}"
                 : "+f"(d[0]),"+f"(d[1]),"+f"(d[2]),"+f"(d[3]),"+f"(d[4]),"+f"(d[5]),"+f"(d[6]),"+f"(d[7]),"+f"(d[8]),"+f"(d[9]),"+f"(d[10]),"+f"(d[11]),"+f"(d[12]),"+f"(d[13]),"+f"(d[14]),"+f"(d[15]),"+f"(d[16]),"+f"(d[17]),"+f"(d[18]),"+f"(d[19]),"+f"(d[20]),"+f"(d[21]),"+f"(d[22]),"+f"(d[23]),"+f"(d[24]),"+f"(d[25]),"+f"(d[26]),"+f"(d[27]),"+f"(d[28]),"+f"(d[29]),"+f"(d[30]),"+f"(d[31]),"+f"(d[32]),"+f"(d[33]),"+f"(d[34]),"+f"(d[35]),"+f"(d[36]),"+f"(d[37]),"+f"(d[38]),"+f"(d[39]),"+f"(d[40]),"+f"(d[41]),"+f"(d[42]),"+f"(d[43]),"+f"(d[44]),"+f"(d[45]),"+f"(d[46]),"+f"(d[47]),"+f"(d[48]),"+f"(d[49]),"+f"(d[50]),"+f"(d[51]),"+f"(d[52]),"+f"(d[53]),"+f"(d[54]),"+f"(d[55]),"+f"(d[56]),"+f"(d[57]),"+f"(d[58]),"+f"(d[59]),"+f"(d[60]),"+f"(d[61]),"+f"(d[62]),"+f"(d[63])
                 : "l"(desc_a), "l"(desc_b), "r"(scale_d));
}

__device__ __forceinline__ void wgmma_m64n64k16(float d[32], uint64_t desc_a, uint64_t desc_b, int scale_d) {
    asm volatile("{\n.reg .pred p;\nsetp.ne.b32 p, %34, 0;\n"
                 "wgmma.mma_async.sync.aligned.m64n64k16.f32.bf16.bf16 {%0,%1,%2,%3,%4,%5,%6,%7,%8,%9,%10,%11,%12,%13,%14,%15,%16,%17,%18,%19,%20,%21,%22,%23,%24,%25,%26,%27,%28,%29,%30,%31}, %32, %33, p, 1, 1, 0, 1;\n}"
                 : "+f"(d[0]),"+f"(d[1]),"+f"(d[2]),"+f"(d[3]),"+f"(d[4]),"+f"(d[5]),"+f"(d[6]),"+f"(d[7]),"+f"(d[8]),"+f"(d[9]),"+f"(d[10]),"+f"(d[11]),"+f"(d[12]),"+f"(d[13]),"+f"(d[14]),"+f"(d[15]),"+f"(d[16]),"+f"(d[17]),"+f"(d[18]),"+f"(d[19]),"+f"(d[20]),"+f"(d[21]),"+f"(d[22]),"+f"(d[23]),"+f"(d[24]),"+f"(d[25]),"+f"(d[26]),"+f"(d[27]),"+f"(d[28]),"+f"(d[29]),"+f"(d[30]),"+f"(d[31])
                 : "l"(desc_a), "l"(desc_b), "r"(scale_d));
}

#define K1_GW 12
#define P1_T 256
#define K1_THREADS (K1_GW * 32 + P1_T)
#define P1_EPT ((2560 + P1_T - 1) / P1_T)
#define P1_CHUNK (P1_T * P1_EPT)
#define K1_WBYTES (65536 + 2 * 16384)
#define K1_SMEM (K1_WBYTES + 3 * MAXBINS * 4 + P1_CHUNK * 8 + 16)

__device__ __forceinline__ void p1_bar() { asm volatile("bar.sync 1, %0;" :: "n"(P1_T) : "memory"); }

__global__ void __launch_bounds__(K1_THREADS, 1) k1_kernel(
    const __grid_constant__ CUtensorMap tm_x, const __grid_constant__ CUtensorMap tm_wb, const __grid_constant__ CUtensorMap tm_wv,
    const __nv_bfloat16* __restrict__ x, const __nv_bfloat16* __restrict__ e_attr,
    const int* __restrict__ src, const int* __restrict__ dst,
    const __nv_bfloat16* __restrict__ w_b, const __nv_bfloat16* __restrict__ w_v,
    const __nv_bfloat16* __restrict__ w_a, const __nv_bfloat16* __restrict__ w_u,
    int N, int E, int chunk, int NB, int nbins, uint32_t magic)
{
    extern __shared__ __align__(1024) uint8_t smem[];
    asm volatile("griddepcontrol.launch_dependents;");
    TSM(threadIdx.x == 0, 0);

    const int warp = threadIdx.x >> 5, lane = threadIdx.x & 31;

    if (warp >= K1_GW) {
        const int tid = threadIdx.x - K1_GW * 32;
        if (blockIdx.x == 0 && tid < 32)
            g_T[(size_t)N * 32 + tid] = make_uint4(0xff80ff80u, 0xff80ff80u, 0u, 0u);
        int* hist = reinterpret_cast<int*>(smem + K1_WBYTES);
        int* loff = hist + MAXBINS;
        int* gbase = loff + MAXBINS;
        uint2* sorted = reinterpret_cast<uint2*>(smem + K1_WBYTES + 3 * MAXBINS * 4);
        for (int beg = blockIdx.x * chunk; beg < E; beg += gridDim.x * chunk) {
            const int end = min(E, beg + chunk);
            int d[P1_EPT]; uint32_t rec[P1_EPT]; int rk[P1_EPT]; int bn[P1_EPT];
            #pragma unroll
            for (int i = 0; i < P1_EPT; i++) {
                int e = beg + i * P1_T + tid;
                d[i] = -1;
                if (e < end) {
                    d[i] = __ldg(dst + e);
                    uint32_t s = (uint32_t)__ldg(src + e);
                    uint32_t ev = (uint32_t)__ldg(reinterpret_cast<const unsigned short*>(e_attr) + e);
                    rec[i] = (ev << 16) | s;
                }
            }
            if (tid < MAXBINS) hist[tid] = 0;
            TSM(tid == 0 && d[P1_EPT - 2] != -5 && rec[P1_EPT - 2] != 0xfffffff5u, 14);
            p1_bar();
            #pragma unroll
            for (int i = 0; i < P1_EPT; i++) {
                if (d[i] >= 0) {
                    bn[i] = (int)(((uint64_t)(uint32_t)d[i] * magic) >> 24);
                    rk[i] = atomicAdd(&hist[bn[i]], 1);
                }
            }
            p1_bar();
            TSM(tid == 0, 3);
            {
                int h = (tid < MAXBINS) ? hist[tid] : 0;
                if (tid < nbins && h > 0) gbase[tid] = atomicAdd(&g_bin_cnt[tid * CNT_STRIDE], h);
                if (tid < 32) {
                    int v[8]; int sum = 0;
                    #pragma unroll
                    for (int i = 0; i < 8; i++) { v[i] = hist[lane * 8 + i]; sum += v[i]; }
                    int inc = sum;
                    #pragma unroll
                    for (int o = 1; o < 32; o <<= 1) { int t = __shfl_up_sync(0xffffffffu, inc, o); if (lane >= o) inc += t; }
                    int run = inc - sum;
                    #pragma unroll
                    for (int i = 0; i < 8; i++) { loff[lane * 8 + i] = run; run += v[i]; }
                }
            }
            p1_bar();
            TSM(tid == 0, 6);
            #pragma unroll
            for (int i = 0; i < P1_EPT; i++) {
                if (d[i] >= 0) sorted[loff[bn[i]] + rk[i]] = make_uint2(rec[i], (uint32_t)d[i]);
            }
            p1_bar();
            TSM(tid == 0, 7);
            const int cnt = end - beg;
            {
                uint2 r[P1_EPT]; int b[P1_EPT], pos[P1_EPT];
                #pragma unroll
                for (int k = 0; k < P1_EPT; k++) {
                    const int i = k * P1_T + tid;
                    r[k] = sorted[min(i, P1_CHUNK - 1)];
                }
                #pragma unroll
                for (int k = 0; k < P1_EPT; k++) {
                    const int i = k * P1_T + tid;
                    b[k] = (i < cnt) ? (int)(((uint64_t)r[k].y * magic) >> 24) : 0;
                    pos[k] = gbase[b[k]] + (i - loff[b[k]]);
                }
                #pragma unroll
                for (int k = 0; k < P1_EPT; k++) {
                    const int i = k * P1_T + tid;
                    if (i < cnt) {
                        if (pos[k] < BINCAP) {
                            g_bins[b[k] * BINCAP + pos[k]] = make_uint2(r[k].x, r[k].y - (uint32_t)(b[k] * NB));
                        } else {
                            int p = atomicAdd(&g_ovf_cnt, 2);
                            g_ovf[p] = (int)r[k].y; g_ovf[p + 1] = (int)r[k].x;
                        }
                    }
                }
            }
            p1_bar();
        }
        TSM(tid == 0, 4);
        return;
    }

    if (blockIdx.x < 4 && threadIdx.x < 128) {
        const char* pw = reinterpret_cast<const char*>((blockIdx.x & 2) ? w_u : w_a) + (blockIdx.x & 1) * 16384 + threadIdx.x * 128;
        asm volatile("prefetch.global.L2 [%0];" :: "l"(pw));
    }
    const int q = lane & 3;
    const int wg = warp >> 2;
    const int n_tasks = ((N + 63) >> 6) * 2;
    const uint32_t sbase = (uint32_t)__cvta_generic_to_shared(smem);
    const uint32_t xbase = sbase + 65536;
    bool w_staged = false;
    const uint32_t mbar = sbase + K1_SMEM - 16;
    uint32_t phase = 0;
    if (threadIdx.x == 0) mbar_init(mbar, 1);
    int t_beg = (int)(((long long)n_tasks * blockIdx.x) / gridDim.x);
    const int t_end = (int)(((long long)n_tasks * (blockIdx.x + 1)) / gridDim.x);
    while (t_beg < t_end) {
        const int tile0 = t_beg >> 1;
        const int t_stop = min(t_end, (tile0 + 2) << 1);
        if (threadIdx.x == 0) {
            const bool two = ((t_stop - 1) >> 1) > tile0;
            mbar_expect_tx(mbar, (two ? 32768u : 16384u) + (w_staged ? 0u : 65536u));
            tma_x_tile(xbase, &tm_x, tile0 * 64, mbar);
            if (!w_staged) tma_weights(sbase, &tm_wb, &tm_wv, mbar);
            if (two) tma_x_tile(xbase + 16384, &tm_x, tile0 * 64 + 64, mbar);
        }
        if (!w_staged) asm volatile("bar.sync 2, %0;" :: "n"(K1_GW * 32) : "memory");
        w_staged = true;
        mbar_wait(mbar, phase);
        phase ^= 1;
        TSM(threadIdx.x == 0, 1);
        for (int task = t_beg + wg; task < t_stop; task += K1_GW / 4) {
            const int tile = task >> 1, hf = task & 1;
            const uint32_t baddr = sbase + hf * 16384;
            const uint64_t descb = (uint64_t)((baddr & 0x3FFFF) >> 4) | ((uint64_t)(32768 >> 4) << 16) |
                                   ((uint64_t)(1024 >> 4) << 32) | ((uint64_t)1 << 62);
            const uint32_t aaddr = xbase + (tile - tile0) * 16384;
            const uint64_t desca = (uint64_t)((aaddr & 0x3FFFF) >> 4) | ((uint64_t)1 << 16) |
                                   ((uint64_t)(1024 >> 4) << 32) | ((uint64_t)1 << 62);
            float d[64];
            asm volatile("wgmma.fence.sync.aligned;" ::: "memory");
            #pragma unroll
            for (int ks = 0; ks < 8; ks++) {
                wgmma_m64n128k16(d, desca + (uint64_t)(((ks >> 2) * 8192 + (ks & 3) * 32) >> 4),
                                 descb + (uint64_t)(ks * (2048 >> 4)), ks > 0 ? 1 : 0);
            }
            asm volatile("wgmma.commit_group.sync.aligned;" ::: "memory");
            asm volatile("wgmma.wait_group.sync.aligned 0;" ::: "memory");
            TSM(threadIdx.x == 0, 13);
            const int r0 = tile * 64 + (warp & 3) * 16 + (lane >> 2);
            #pragma unroll
            for (int mm = 0; mm < 4; mm++) {
                const int j0 = 2 * mm, j1 = 2 * mm + 1, j2 = 8 + 2 * mm, j3 = 9 + 2 * mm;
                uint4 o0 = make_uint4(pack_bf16(d[4 * j0], d[4 * j0 + 1]), pack_bf16(d[4 * j1], d[4 * j1 + 1]),
                                      pack_bf16(d[4 * j2], d[4 * j2 + 1]), pack_bf16(d[4 * j3], d[4 * j3 + 1]));
                uint4 o1 = make_uint4(pack_bf16(d[4 * j0 + 2], d[4 * j0 + 3]), pack_bf16(d[4 * j1 + 2], d[4 * j1 + 3]),
                                      pack_bf16(d[4 * j2 + 2], d[4 * j2 + 3]), pack_bf16(d[4 * j3 + 2], d[4 * j3 + 3]));
                const int m = 4 * hf + mm;
                if (r0 < N) g_T[(size_t)r0 * 32 + 4 * m + q] = o0;
                if (r0 + 8 < N) g_T[(size_t)(r0 + 8) * 32 + 4 * m + q] = o1;
            }
        }
        t_beg = t_stop;
        if (t_beg < t_end) asm volatile("bar.sync 2, %0;" :: "n"(K1_GW * 32) : "memory");
    }
    TSM(threadIdx.x == 0, 2);
}

__device__ __forceinline__ void edge_accum(const uint4 v, const float e, const float a[4], const float cc[4],
                                           float num[4], float den[4]) {
    float y0 = fmaf(bf_lo(v.x), -LOG2E, fmaf(e, cc[0], a[0]));
    float y1 = fmaf(bf_hi(v.x), -LOG2E, fmaf(e, cc[1], a[1]));
    float y2 = fmaf(bf_lo(v.y), -LOG2E, fmaf(e, cc[2], a[2]));
    float y3 = fmaf(bf_hi(v.y), -LOG2E, fmaf(e, cc[3], a[3]));
    float s0 = rcp_approx(1.f + ex2_approx(y0));
    float s1 = rcp_approx(1.f + ex2_approx(y1));
    float s2 = rcp_approx(1.f + ex2_approx(y2));
    float s3 = rcp_approx(1.f + ex2_approx(y3));
    den[0] += s0; den[1] += s1; den[2] += s2; den[3] += s3;
    num[0] = fmaf(s0, bf_lo(v.z), num[0]);
    num[1] = fmaf(s1, bf_hi(v.z), num[1]);
    num[2] = fmaf(s2, bf_lo(v.w), num[2]);
    num[3] = fmaf(s3, bf_hi(v.w), num[3]);
}

#define K2_THREADS 1024
#define K2_D 2
#define K2_GS 2
#define K2_RPT ((BINCAP + K2_THREADS - 1) / K2_THREADS)
#define K2_NW (K2_THREADS / 32)
#define SORT_WORDS (BINCAP + 4 * MAXNB)
#define K2_OFF_W 0
#define K2_OFF_X 65536
#define K2_OFF_A (K2_OFF_X + 32768)
#define K2_OFF_U (K2_OFF_A + MAXNB * 256)
#define K2_OFF_PART (K2_OFF_U + MAXNB * 256)
#define K2_OFF_SORT (K2_OFF_PART + K2_NW * 1024)
#define K2_OFF_HIST (K2_OFF_SORT + SORT_WORDS * 4)
#define K2_OFF_OFF (K2_OFF_HIST + MAXNB * 4)
#define K2_OFF_MBAR (K2_OFF_OFF + (MAXNB + 4) * 4)
#define K2_DYN_SMEM (K2_OFF_MBAR + 16)
#define K2_ST (K2_THREADS - 512)
#define K2_SRPT ((BINCAP + K2_ST - 1) / K2_ST)

struct Grp { uint4 v[K2_GS]; };

__device__ __forceinline__ const uint4* row_ptr(const char* Tl, uint32_t rec) {
    return reinterpret_cast<const uint4*>(Tl + (size_t)((rec & 0xffffu) * 512u));
}
__device__ __forceinline__ void grp_load(Grp& g, const uint32_t* sp, const char* Tl) {
    const uint2 t = *reinterpret_cast<const uint2*>(sp);
    g.v[0] = __ldg(row_ptr(Tl, t.x));
    g.v[1] = __ldg(row_ptr(Tl, t.y));
}
__device__ __forceinline__ void grp_consume(const Grp& g, const uint32_t* sp, const float a[4], const float cc[4],
                                            float num[4], float den[4]) {
    const uint2 t = *reinterpret_cast<const uint2*>(sp);
    edge_accum(g.v[0], bf_hi(t.x), a, cc, num, den);
    edge_accum(g.v[1], bf_hi(t.y), a, cc, num, den);
}

__device__ __forceinline__ void load_a(const uint8_t* smem, int ln, int lane, float a[4]) {
    const uint2 av = reinterpret_cast<const uint2*>(smem + K2_OFF_A)[ln * 32 + (lane ^ ((ln & 3) << 2))];
    a[0] = -LOG2E * bf_lo(av.x); a[1] = -LOG2E * bf_hi(av.x); a[2] = -LOG2E * bf_lo(av.y); a[3] = -LOG2E * bf_hi(av.y);
}
__device__ __forceinline__ void write_node(const uint8_t* smem, __nv_bfloat16* out, int ln, int n,
                                           int lane, const float num[4], const float den[4]) {
    const uint2 uv = reinterpret_cast<const uint2*>(smem + K2_OFF_U)[ln * 32 + (lane ^ ((ln & 3) << 2))];
    const int r = ln & 63, c16 = (lane >> 2) * 2;
    const uint8_t* xr = smem + K2_OFF_X + (ln >> 6) * 16384 + (c16 >> 3) * 8192 + r * 128 + (lane & 3) * 4;
    const uint32_t x0 = *reinterpret_cast<const uint32_t*>(xr + (((c16 & 7) ^ (r & 7)) << 4));
    const uint32_t x1 = *reinterpret_cast<const uint32_t*>(xr + ((((c16 + 1) & 7) ^ (r & 7)) << 4));
    const float u4[4] = { bf_lo(uv.x), bf_hi(uv.x), bf_lo(uv.y), bf_hi(uv.y) };
    const float x4[4] = { bf_lo(x0), bf_hi(x0), bf_lo(x1), bf_hi(x1) };
    float o[4];
    #pragma unroll
    for (int i = 0; i < 4; i++) {
        float agg = round_bf16(__fdividef(num[i], den[i] + 1e-6f));
        float z = round_bf16(u4[i] + agg);
        float rz = (z > 0.f) ? z : 0.f * z;
        o[i] = x4[i] + rz;
    }
    uint32_t* o32 = reinterpret_cast<uint32_t*>(out) + (size_t)n * 64 + (lane >> 2) * 8 + (lane & 3);
    o32[0] = pack_bf16(o[0], o[1]); o32[4] = pack_bf16(o[2], o[3]);
}

__device__ __noinline__ void slow_path(const uint8_t* smem, __nv_bfloat16* out, int node0, int nn, int ovf_n,
                                       float c0, float c1, float c2, float c3) {
    const uint32_t* s_sorted = reinterpret_cast<const uint32_t*>(smem + K2_OFF_SORT);
    const int* s_off = reinterpret_cast<const int*>(smem + K2_OFF_OFF);
    const int lane = threadIdx.x & 31, warp = threadIdx.x >> 5;
    const float cc[4] = { c0, c1, c2, c3 };
    const char* Tl = reinterpret_cast<const char*>(g_T) + lane * 16;
    for (int ln = warp; ln < nn; ln += K2_NW) {
        float a[4];
        load_a(smem, ln, lane, a);
        float num[4] = {0.f, 0.f, 0.f, 0.f}, den[4] = {0.f, 0.f, 0.f, 0.f};
        for (int i = s_off[ln]; i < s_off[ln + 1]; i++) {
            const uint32_t r = s_sorted[i];
            edge_accum(__ldg(row_ptr(Tl, r)), bf_hi(r), a, cc, num, den);
        }
        const int n = node0 + ln;
        for (int base = 0; base < ovf_n; base += 64) {
            int i2 = base + 2 * lane;
            int od = (i2 < ovf_n) ? g_ovf[i2] : -1;
            uint32_t orec = (i2 < ovf_n) ? (uint32_t)g_ovf[i2 + 1] : 0u;
            unsigned msk = __ballot_sync(0xffffffffu, od == n);
            while (msk) {
                int l = __ffs(msk) - 1; msk &= msk - 1;
                uint32_t r = __shfl_sync(0xffffffffu, orec, l);
                edge_accum(__ldg(row_ptr(Tl, r)), bf_hi(r), a, cc, num, den);
            }
        }
        write_node(smem, out, ln, n, lane, num, den);
    }
}

__global__ void __launch_bounds__(K2_THREADS, 1) k2_kernel(
    const __grid_constant__ CUtensorMap tm_x, const __grid_constant__ CUtensorMap tm_wa, const __grid_constant__ CUtensorMap tm_wu,
    const __nv_bfloat16* __restrict__ w_c, __nv_bfloat16* __restrict__ out, int N, int NB)
{
    extern __shared__ __align__(1024) uint8_t smem[];
    float4* s_part = reinterpret_cast<float4*>(smem + K2_OFF_PART);
    uint32_t* s_sorted = reinterpret_cast<uint32_t*>(smem + K2_OFF_SORT);
    int* s_hist = reinterpret_cast<int*>(smem + K2_OFF_HIST);
    int* s_off = reinterpret_cast<int*>(smem + K2_OFF_OFF);

    const int tid = threadIdx.x;
    const int lane = tid & 31, warp = tid >> 5;
    const int bin = blockIdx.x;
    const int node0 = bin * NB;
    const int nn = min(NB, N - node0);
    const uint32_t sb = (uint32_t)__cvta_generic_to_shared(smem);
    TSM(tid == 0, 5);

    const int fw = (lane >> 2) * 8 + (lane & 3);
    const uint2 wc = make_uint2(__ldg(reinterpret_cast<const uint32_t*>(w_c) + fw), __ldg(reinterpret_cast<const uint32_t*>(w_c) + fw + 4));
    s_part[warp * 64 + lane] = make_float4(0.f, 0.f, 0.f, 0.f);
    s_part[warp * 64 + 32 + lane] = make_float4(0.f, 0.f, 0.f, 0.f);
    if (warp < 16) {
        const uint32_t mbar = sb + K2_OFF_MBAR;
        if (tid == 0) {
            mbar_init(mbar, 1);
            mbar_expect_tx(mbar, (nn > 64 ? 32768u : 16384u) + 65536u);
            tma_x_tile(sb + K2_OFF_X, &tm_x, node0, mbar);
            tma_weights(sb + K2_OFF_W, &tm_wa, &tm_wu, mbar);
            if (nn > 64) tma_x_tile(sb + K2_OFF_X + 16384, &tm_x, node0 + 64, mbar);
        }
        asm volatile("bar.sync 2, 512;" ::: "memory");
        mbar_wait(mbar, 0);
        const int wg = warp >> 2, tile = wg >> 1, mtx = wg & 1;
        if (tile * 64 < nn) {
            const uint32_t aaddr = sb + K2_OFF_X + tile * 16384;
            const uint64_t desca = (uint64_t)((aaddr & 0x3FFFF) >> 4) | ((uint64_t)1 << 16) |
                                   ((uint64_t)(1024 >> 4) << 32) | ((uint64_t)1 << 62);
            uint2* dst = reinterpret_cast<uint2*>(smem + (mtx ? K2_OFF_U : K2_OFF_A));
            const int r0 = tile * 64 + (warp & 3) * 16 + (lane >> 2);
            const int sw = (r0 & 3) << 2;
            #pragma unroll 1
            for (int hf = 0; hf < 2; hf++) {
                const uint32_t baddr = sb + K2_OFF_W + (mtx * 2 + hf) * 16384;
                const uint64_t descb = (uint64_t)((baddr & 0x3FFFF) >> 4) | ((uint64_t)(32768 >> 4) << 16) |
                                       ((uint64_t)(1024 >> 4) << 32) | ((uint64_t)1 << 62);
                float d[32];
                asm volatile("wgmma.fence.sync.aligned;" ::: "memory");
                #pragma unroll
                for (int ks = 0; ks < 8; ks++) {
                    wgmma_m64n64k16(d, desca + (uint64_t)(((ks >> 2) * 8192 + (ks & 3) * 32) >> 4),
                                    descb + (uint64_t)(ks * (2048 >> 4)), ks > 0 ? 1 : 0);
                }
                asm volatile("wgmma.commit_group.sync.aligned;" ::: "memory");
                asm volatile("wgmma.wait_group.sync.aligned 0;" ::: "memory");
                TSM(tid == 0 && hf == 0, 15);
                #pragma unroll
                for (int mm = 0; mm < 4; mm++) {
                    const int j0 = 2 * mm, j1 = 2 * mm + 1;
                    const int slot = (4 * (4 * hf + mm) + (lane & 3)) ^ sw;
                    dst[r0 * 32 + slot] = make_uint2(pack_bf16(d[4 * j0], d[4 * j0 + 1]), pack_bf16(d[4 * j1], d[4 * j1 + 1]));
                    dst[(r0 + 8) * 32 + slot] = make_uint2(pack_bf16(d[4 * j0 + 2], d[4 * j0 + 3]), pack_bf16(d[4 * j1 + 2], d[4 * j1 + 3]));
                }
            }
        }
        asm volatile("griddepcontrol.wait;" ::: "memory");
    } else {
        const int st = tid - 512;
        if (st < MAXNB) s_hist[st] = 0;
        for (int i = st; i < SORT_WORDS; i += K2_ST) s_sorted[i] = (uint32_t)N;
        asm volatile("bar.sync 1, %0;" :: "n"(K2_ST) : "memory");
        asm volatile("griddepcontrol.wait;" ::: "memory");
        TSM(st == 0, 8);
        uint2 r[K2_SRPT]; int rk[K2_SRPT];
        const int cnt = min(g_bin_cnt[bin * CNT_STRIDE], BINCAP);
        if (st == 64) s_off[MAXNB + 1] = g_ovf_cnt;
        #pragma unroll
        for (int i = 0; i < K2_SRPT; i++) {
            int idx = i * K2_ST + st;
            if (idx < cnt) r[i] = g_bins[bin * BINCAP + idx];
        }
        #pragma unroll
        for (int i = 0; i < K2_SRPT; i++) {
            int idx = i * K2_ST + st;
            if (idx < cnt) rk[i] = atomicAdd(&s_hist[r[i].y], 1);
        }
        asm volatile("bar.sync 1, %0;" :: "n"(K2_ST) : "memory");
        if (warp == 16) {
            int v[4]; int sum = 0;
            #pragma unroll
            for (int i = 0; i < 4; i++) { v[i] = (s_hist[lane * 4 + i] + K2_GS - 1) & ~(K2_GS - 1); sum += v[i]; }
            int inc = sum;
            #pragma unroll
            for (int o = 1; o < 32; o <<= 1) { int t = __shfl_up_sync(0xffffffffu, inc, o); if (lane >= o) inc += t; }
            int run = inc - sum;
            #pragma unroll
            for (int i = 0; i < 4; i++) { s_off[lane * 4 + i] = run; run += v[i]; }
            if (lane == 31) s_off[MAXNB] = run;
        }
        if (st == 32) g_bin_cnt[bin * CNT_STRIDE] = 0;
        asm volatile("bar.sync 1, %0;" :: "n"(K2_ST) : "memory");
        #pragma unroll
        for (int i = 0; i < K2_SRPT; i++) {
            int idx = i * K2_ST + st;
            if (idx < cnt) s_sorted[s_off[r[i].y] + rk[i]] = r[i].x;
        }
        TSM(st == 0, 9);
    }
    __syncthreads();
    TSM(tid == 0, 10);
    const float cc[4] = { -LOG2E * bf_lo(wc.x), -LOG2E * bf_hi(wc.x), -LOG2E * bf_lo(wc.y), -LOG2E * bf_hi(wc.y) };
    const int ovf_n = s_off[MAXNB + 1];

    if (ovf_n != 0) {
        slow_path(smem, out, node0, nn, ovf_n, cc[0], cc[1], cc[2], cc[3]);
        __syncthreads();
        if (tid == 0) {
            __threadfence();
            int t = atomicAdd(&g_done, 1);
            if (t == (int)gridDim.x - 1) { g_done = 0; __threadfence(); g_ovf_cnt = 0; }
        }
        return;
    }

    const char* Tl = reinterpret_cast<const char*>(g_T) + lane * 16;
    const int G = s_off[MAXNB] / K2_GS;
    int g = (G * warp) / K2_NW;
    const int g1 = (G * (warp + 1)) / K2_NW;
    int ln;
    {
        int c_lo = 0;
        #pragma unroll
        for (int i = 0; i < 4; i++) {
            int node = i * 32 + lane;
            int o = (node < nn) ? s_off[node] : 0x7fffffff;
            c_lo += __popc(__ballot_sync(0xffffffffu, o < g * K2_GS));
        }
        ln = c_lo;
    }
    bool head = ln > 0;
    if (head) ln--;
    float a[4], num[4] = {0.f, 0.f, 0.f, 0.f}, den[4] = {0.f, 0.f, 0.f, 0.f};
    int node_end;

    auto load_node = [&]() {
        load_a(smem, ln, lane, a);
        node_end = s_off[ln + 1] / K2_GS;
    };
    auto finish_node = [&]() { write_node(smem, out, ln, node0 + ln, lane, num, den); };
    auto close_node = [&]() {
        if (head) {
            s_part[warp * 64 + lane] = make_float4(num[0], num[1], num[2], num[3]);
            s_part[warp * 64 + 32 + lane] = make_float4(den[0], den[1], den[2], den[3]);
            head = false;
        } else {
            finish_node();
        }
        #pragma unroll
        for (int i = 0; i < 4; i++) { num[i] = 0.f; den[i] = 0.f; }
    };

    bool tail = false;
    if (g < g1 || warp == K2_NW - 1) {
        load_node();
        Grp b[K2_D];
        #pragma unroll
        for (int d = 0; d < K2_D; d++)
            if (g + d < g1) grp_load(b[d], s_sorted + K2_GS * (g + d), Tl);
        while (g < g1) {
            #pragma unroll
            for (int d = 0; d < K2_D; d++) {
                if (g < g1) {
                    while (g == node_end) { close_node(); ln++; load_node(); }
                    grp_consume(b[d], s_sorted + K2_GS * g, a, cc, num, den);
                    if (g + K2_D < g1) grp_load(b[d], s_sorted + K2_GS * (g + K2_D), Tl);
                    g++;
                }
            }
        }
        if (warp == K2_NW - 1) {
            while (true) { close_node(); ln++; if (ln >= nn) break; load_node(); }
        } else if (node_end == g1 || head) {
            close_node();
        } else {
            tail = true;
        }
    }
    TSM(tid == 0, 11);
    __syncthreads();
    TSM(tid == 0, 12);
    if (tail) {
        for (int w2 = warp + 1; w2 < K2_NW && (G * w2) / K2_NW < node_end; w2++) {
            const float4 pn = s_part[w2 * 64 + lane], pd = s_part[w2 * 64 + 32 + lane];
            num[0] += pn.x; num[1] += pn.y; num[2] += pn.z; num[3] += pn.w;
            den[0] += pd.x; den[1] += pd.y; den[2] += pd.z; den[3] += pd.w;
        }
        finish_node();
    }
}

extern "C" void kernel_launch(void* const* d_in, const int* in_sizes, int n_in,
                              void* d_out, int out_size) {
    const __nv_bfloat16* x      = (const __nv_bfloat16*)d_in[0];
    const __nv_bfloat16* e_attr = (const __nv_bfloat16*)d_in[1];
    const int* src = (const int*)d_in[2];
    const int* dst = (const int*)d_in[3];
    const __nv_bfloat16* w_a = (const __nv_bfloat16*)d_in[4];
    const __nv_bfloat16* w_b = (const __nv_bfloat16*)d_in[5];
    const __nv_bfloat16* w_c = (const __nv_bfloat16*)d_in[6];
    const __nv_bfloat16* w_u = (const __nv_bfloat16*)d_in[7];
    const __nv_bfloat16* w_v = (const __nv_bfloat16*)d_in[8];
    __nv_bfloat16* out = (__nv_bfloat16*)d_out;
    const int N = in_sizes[0] / D_FEAT;
    const int E = in_sizes[2];
    if (N > MAX_N || 2 * E > MAX_E || N <= 0) return;

    static int num_sms = 0;
    if (num_sms == 0) {
        int dev = 0;
        cudaGetDevice(&dev);
        cudaDeviceGetAttribute(&num_sms, cudaDevAttrMultiProcessorCount, dev);
        if (num_sms <= 0 || num_sms > MAXBINS) num_sms = 132;
        cudaFuncSetAttribute(k1_kernel, cudaFuncAttributeMaxDynamicSharedMemorySize, K1_SMEM);
        cudaFuncSetAttribute(k2_kernel, cudaFuncAttributeMaxDynamicSharedMemorySize, K2_DYN_SMEM);
    }
    typedef CUresult (*EncodeFn)(CUtensorMap*, CUtensorMapDataType, cuuint32_t, void*, const cuuint64_t*, const cuuint64_t*,
                                 const cuuint32_t*, const cuuint32_t*, CUtensorMapInterleave, CUtensorMapSwizzle,
                                 CUtensorMapL2promotion, CUtensorMapFloatOOBfill);
    static EncodeFn encode = nullptr;
    if (!encode) {
        void* fn = nullptr;
        cudaDriverEntryPointQueryResult qres;
        if (cudaGetDriverEntryPoint("cuTensorMapEncodeTiled", &fn, cudaEnableDefault, &qres) != cudaSuccess || !fn) return;
        encode = (EncodeFn)fn;
    }
    auto make_map = [&](CUtensorMap* m, const void* base, int rows, int box_rows) {
        cuuint64_t dims[2] = { D_FEAT, (cuuint64_t)rows };
        cuuint64_t strides[1] = { D_FEAT * 2 };
        cuuint32_t box[2] = { 64, (cuuint32_t)box_rows };
        cuuint32_t es[2] = { 1, 1 };
        return encode(m, CU_TENSOR_MAP_DATA_TYPE_BFLOAT16, 2, const_cast<void*>(base), dims, strides, box, es,
                      CU_TENSOR_MAP_INTERLEAVE_NONE, CU_TENSOR_MAP_SWIZZLE_128B, CU_TENSOR_MAP_L2_PROMOTION_L2_128B,
                      CU_TENSOR_MAP_FLOAT_OOB_FILL_NONE);
    };
    CUtensorMap tm_x, tm_wa, tm_wb, tm_wu, tm_wv;
    if (make_map(&tm_x, x, N, 64) != CUDA_SUCCESS || make_map(&tm_wa, w_a, D_FEAT, 128) != CUDA_SUCCESS ||
        make_map(&tm_wb, w_b, D_FEAT, 128) != CUDA_SUCCESS || make_map(&tm_wu, w_u, D_FEAT, 128) != CUDA_SUCCESS ||
        make_map(&tm_wv, w_v, D_FEAT, 128) != CUDA_SUCCESS) return;
    cudaStream_t st = cudaStreamPerThread;
    int NB = (N + num_sms - 1) / num_sms;
    if (NB > MAXNB) NB = MAXNB;
    const int nbins = (N + NB - 1) / NB;
    const uint32_t magic = (uint32_t)(((1u << 24) + NB - 1) / NB);
    const int P = num_sms;
    int chunk = (E + P - 1) / P;
    if (chunk > P1_CHUNK) chunk = P1_CHUNK;
    if (chunk < 1) chunk = 1;
    k1_kernel<<<P, K1_THREADS, K1_SMEM, st>>>(tm_x, tm_wb, tm_wv, x, e_attr, src, dst, w_b, w_v, w_a, w_u, N, E, chunk, NB, nbins, magic);

    cudaLaunchConfig_t cfg = {};
    cfg.gridDim = dim3(nbins);
    cfg.blockDim = dim3(K2_THREADS);
    cfg.dynamicSmemBytes = K2_DYN_SMEM;
    cfg.stream = st;
    cudaLaunchAttribute at[1];
    at[0].id = cudaLaunchAttributeProgrammaticStreamSerialization;
    at[0].val.programmaticStreamSerializationAllowed = 1;
    cfg.attrs = at; cfg.numAttrs = 1;
    cudaLaunchKernelEx(&cfg, k2_kernel, tm_x, tm_wa, tm_wu, w_c, out, N, NB);
}
```

```cpp
#include <cuda_runtime.h>
#include <cuda.h>
#include <cuda_bf16.h>
#include <stdint.h>

#define D_FEAT 128
#define MAX_N 16384
#define MAX_E (1 << 20)
#define LOG2E 1.4426950408889634f

#define MAXBINS 256
#define MAXNB 128
#define BINCAP 3072
__device__ uint4 g_T[(MAX_N + 1) * 32];
#define CNT_STRIDE 1
__device__ int g_bin_cnt[MAXBINS * CNT_STRIDE];
__device__ uint2 g_bins[MAXBINS * BINCAP];
__device__ int g_ovf[MAX_E];
__device__ int g_ovf_cnt;
__device__ int g_done;

#define TSM(cond, i)
__device__ __forceinline__ float ex2_approx(float x) {
    float y; asm("ex2.approx.ftz.f32 %0, %1;" : "=f"(y) : "f"(x)); return y;
}
__device__ __forceinline__ float rcp_approx(float x) {
    float y; asm("rcp.approx.ftz.f32 %0, %1;" : "=f"(y) : "f"(x)); return y;
}
__device__ __forceinline__ uint32_t pack_bf16(float lo, float hi) {
    __nv_bfloat162 t = __floats2bfloat162_rn(lo, hi);
    return *reinterpret_cast<uint32_t*>(&t);
}
__device__ __forceinline__ float bf_lo(uint32_t v) { return __uint_as_float(v << 16); }
__device__ __forceinline__ float bf_hi(uint32_t v) { return __uint_as_float(v & 0xffff0000u); }
__device__ __forceinline__ float round_bf16(float x) { return __bfloat162float(__float2bfloat16_rn(x)); }

__device__ __forceinline__ void mma_bf16(float c[4], uint32_t a0, uint32_t a1, uint32_t a2, uint32_t a3,
                                         uint32_t b0, uint32_t b1) {
    asm volatile("mma.sync.aligned.m16n8k16.row.col.f32.bf16.bf16.f32 "
                 "{%0,%1,%2,%3}, {%4,%5,%6,%7}, {%8,%9}, {%0,%1,%2,%3};"
                 : "+f"(c[0]), "+f"(c[1]), "+f"(c[2]), "+f"(c[3])
                 : "r"(a0), "r"(a1), "r"(a2), "r"(a3), "r"(b0), "r"(b1));
}
__device__ __forceinline__ void ldmatrix_x4_trans(uint32_t& r0, uint32_t& r1, uint32_t& r2, uint32_t& r3, uint32_t addr) {
    asm volatile("ldmatrix.sync.aligned.m8n8.x4.trans.shared.b16 {%0,%1,%2,%3}, [%4];"
                 : "=r"(r0), "=r"(r1), "=r"(r2), "=r"(r3) : "r"(addr));
}

__device__ __forceinline__ void cp_async16(uint32_t saddr, const void* g) {
    asm volatile("cp.async.cg.shared.global [%0], [%1], 16;" :: "r"(saddr), "l"(g) : "memory");
}
__device__ __forceinline__ void cp_async16_zfill(uint32_t saddr, const void* g, int src_size) {
    asm volatile("cp.async.cg.shared.global [%0], [%1], 16, %2;" :: "r"(saddr), "l"(g), "r"(src_size) : "memory");
}
__device__ __forceinline__ void stage_weight(uint32_t sdst, const __nv_bfloat16* w, int mtx, int tid, int nthreads) {
    const uint4* W = reinterpret_cast<const uint4*>(w);
    for (int u = tid; u < 2048; u += nthreads) {
        int k = u >> 4, c16 = u & 15;
        int kg = k >> 3, rr = k & 7;
        int h = mtx * 2 + (c16 >> 3);
        cp_async16(sdst + kg * 4096 + h * 1024 + rr * 128 + (((c16 & 7) ^ rr) << 4), W + u);
    }
}
__device__ __forceinline__ void stage_x_tile(uint32_t sdst, const __nv_bfloat16* x, int row0, int N, int tid, int nthreads) {
    const uint4* X = reinterpret_cast<const uint4*>(x);
    for (int u = tid; u < 1024; u += nthreads) {
        int r = u >> 4, c16 = u & 15;
        int gr = row0 + r;
        bool ok = gr < N;
        cp_async16_zfill(sdst + (c16 >> 3) * 8192 + r * 128 + (((c16 & 7) ^ (r & 7)) << 4),
                         X + (size_t)(ok ? gr : 0) * 16 + c16, ok ? 16 : 0);
    }
}

__device__ __forceinline__ void mbar_init(uint32_t bar, int cnt) {
    asm volatile("mbarrier.init.shared::cta.b64 [%0], %1;" :: "r"(bar), "r"(cnt) : "memory");
    asm volatile("fence.mbarrier_init.release.cluster;" ::: "memory");
    asm volatile("fence.proxy.async.shared::cta;" ::: "memory");
}
__device__ __forceinline__ void mbar_expect_tx(uint32_t bar, uint32_t bytes) {
    asm volatile("mbarrier.arrive.expect_tx.shared::cta.b64 _, [%0], %1;" :: "r"(bar), "r"(bytes) : "memory");
}
__device__ __forceinline__ void mbar_wait(uint32_t bar, uint32_t parity) {
    asm volatile("{\n.reg .pred p;\nWAIT_LOOP:\n"
                 "mbarrier.try_wait.parity.shared::cta.b64 p, [%0], %1;\n"
                 "@p bra WAIT_DONE;\nbra WAIT_LOOP;\nWAIT_DONE:\n}" :: "r"(bar), "r"(parity) : "memory");
}
__device__ __forceinline__ void tma_2d(uint32_t sdst, const CUtensorMap* tm, int c0, int c1, uint32_t bar) {
    asm volatile("cp.async.bulk.tensor.2d.shared::cluster.global.mbarrier::complete_tx::bytes [%0], [%1, {%3, %4}], [%2];"
                 :: "r"(sdst), "l"(reinterpret_cast<uint64_t>(tm)), "r"(bar), "r"(c0), "r"(c1) : "memory");
}
__device__ __forceinline__ void tma_weights(uint32_t sdst, const CUtensorMap* m0, const CUtensorMap* m1, uint32_t bar) {
    tma_2d(sdst, m0, 0, 0, bar);
    tma_2d(sdst + 16384, m0, 64, 0, bar);
    tma_2d(sdst + 32768, m1, 0, 0, bar);
    tma_2d(sdst + 49152, m1, 64, 0, bar);
}
__device__ __forceinline__ void tma_x_tile(uint32_t sdst, const CUtensorMap* mx, int row0, uint32_t bar) {
    tma_2d(sdst, mx, 0, row0, bar);
    tma_2d(sdst + 8192, mx, 64, row0, bar);
}

__device__ __forceinline__ void wgmma_m64n128k16(float d[64], uint64_t desc_a, uint64_t desc_b, int scale_d) {
    asm volatile("{\n.reg .pred p;\nsetp.ne.b32 p, %66, 0;\n"
                 "wgmma.mma_async.sync.aligned.m64n128k16.f32.bf16.bf16 {%0,%1,%2,%3,%4,%5,%6,%7,%8,%9,%10,%11,%12,%13,%14,%15,%16,%17,%18,%19,%20,%21,%22,%23,%24,%25,%26,%27,%28,%29,%30,%31,%32,%33,%34,%35,%36,%37,%38,%39,%40,%41,%42,%43,%44,%45,%46,%47,%48,%49,%50,%51,%52,%53,%54,%55,%56,%57,%58,%59,%60,%61,%62,%63}, %64, %65, p, 1, 1, 0, 1;\n}"
                 : "+f"(d[0]),"+f"(d[1]),"+f"(d[2]),"+f"(d[3]),"+f"(d[4]),"+f"(d[5]),"+f"(d[6]),"+f"(d[7]),"+f"(d[8]),"+f"(d[9]),"+f"(d[10]),"+f"(d[11]),"+f"(d[12]),"+f"(d[13]),"+f"(d[14]),"+f"(d[15]),"+f"(d[16]),"+f"(d[17]),"+f"(d[18]),"+f"(d[19]),"+f"(d[20]),"+f"(d[21]),"+f"(d[22]),"+f"(d[23]),"+f"(d[24]),"+f"(d[25]),"+f"(d[26]),"+f"(d[27]),"+f"(d[28]),"+f"(d[29]),"+f"(d[30]),"+f"(d[31]),"+f"(d[32]),"+f"(d[33]),"+f"(d[34]),"+f"(d[35]),"+f"(d[36]),"+f"(d[37]),"+f"(d[38]),"+f"(d[39]),"+f"(d[40]),"+f"(d[41]),"+f"(d[42]),"+f"(d[43]),"+f"(d[44]),"+f"(d[45]),"+f"(d[46]),"+f"(d[47]),"+f"(d[48]),"+f"(d[49]),"+f"(d[50]),"+f"(d[51]),"+f"(d[52]),"+f"(d[53]),"+f"(d[54]),"+f"(d[55]),"+f"(d[56]),"+f"(d[57]),"+f"(d[58]),"+f"(d[59]),"+f"(d[60]),"+f"(d[61]),"+f"(d[62]),"+f"(d[63])
                 : "l"(desc_a), "l"(desc_b), "r"(scale_d));
}

__device__ __forceinline__ void wgmma_m64n64k16(float d[32], uint64_t desc_a, uint64_t desc_b, int scale_d) {
    asm volatile("{\n.reg .pred p;\nsetp.ne.b32 p, %34, 0;\n"
                 "wgmma.mma_async.sync.aligned.m64n64k16.f32.bf16.bf16 {%0,%1,%2,%3,%4,%5,%6,%7,%8,%9,%10,%11,%12,%13,%14,%15,%16,%17,%18,%19,%20,%21,%22,%23,%24,%25,%26,%27,%28,%29,%30,%31}, %32, %33, p, 1, 1, 0, 1;\n}"
                 : "+f"(d[0]),"+f"(d[1]),"+f"(d[2]),"+f"(d[3]),"+f"(d[4]),"+f"(d[5]),"+f"(d[6]),"+f"(d[7]),"+f"(d[8]),"+f"(d[9]),"+f"(d[10]),"+f"(d[11]),"+f"(d[12]),"+f"(d[13]),"+f"(d[14]),"+f"(d[15]),"+f"(d[16]),"+f"(d[17]),"+f"(d[18]),"+f"(d[19]),"+f"(d[20]),"+f"(d[21]),"+f"(d[22]),"+f"(d[23]),"+f"(d[24]),"+f"(d[25]),"+f"(d[26]),"+f"(d[27]),"+f"(d[28]),"+f"(d[29]),"+f"(d[30]),"+f"(d[31])
                 : "l"(desc_a), "l"(desc_b), "r"(scale_d));
}

#define K1_GW 12
#define P1_FIRST
#define P1_T 256
#define K1_THREADS (K1_GW * 32 + P1_T)
#define P1_EPT ((2560 + P1_T - 1) / P1_T)
#define P1_CHUNK (P1_T * P1_EPT)
#define K1_WBYTES (65536 + 2 * 16384)
#define K1_SMEM (K1_WBYTES + 3 * MAXBINS * 4 + P1_CHUNK * 8 + 16)

__device__ __forceinline__ void p1_bar() { asm volatile("bar.sync 1, %0;" :: "n"(P1_T) : "memory"); }

__global__ void __launch_bounds__(K1_THREADS, 1) k1_kernel(
    const __grid_constant__ CUtensorMap tm_x, const __grid_constant__ CUtensorMap tm_wb, const __grid_constant__ CUtensorMap tm_wv,
    const __nv_bfloat16* __restrict__ x, const __nv_bfloat16* __restrict__ e_attr,
    const int* __restrict__ src, const int* __restrict__ dst,
    const __nv_bfloat16* __restrict__ w_b, const __nv_bfloat16* __restrict__ w_v,
    const __nv_bfloat16* __restrict__ w_a, const __nv_bfloat16* __restrict__ w_u,
    int N, int E, int chunk, int NB, int nbins, uint32_t magic)
{
    extern __shared__ __align__(1024) uint8_t smem[];
    asm volatile("griddepcontrol.launch_dependents;");
    TSM(threadIdx.x == 0, 0);

    const int warp = threadIdx.x >> 5, lane = threadIdx.x & 31;

    if (warp >= K1_GW) {
        const int tid = threadIdx.x - K1_GW * 32;
        if (blockIdx.x == 0 && tid < 32)
            g_T[(size_t)N * 32 + tid] = make_uint4(0xff80ff80u, 0xff80ff80u, 0u, 0u);
        int* hist = reinterpret_cast<int*>(smem + K1_WBYTES);
        int* loff = hist + MAXBINS;
        int* gbase = loff + MAXBINS;
        uint2* sorted = reinterpret_cast<uint2*>(smem + K1_WBYTES + 3 * MAXBINS * 4);
        for (int beg = blockIdx.x * chunk; beg < E; beg += gridDim.x * chunk) {
            const int end = min(E, beg + chunk);
            int d[P1_EPT]; uint32_t rec[P1_EPT]; int rk[P1_EPT]; int bn[P1_EPT];
            #pragma unroll
            for (int i = 0; i < P1_EPT; i++) {
                int e = beg + i * P1_T + tid;
                d[i] = -1;
                if (e < end) {
                    d[i] = __ldg(dst + e);
                    uint32_t s = (uint32_t)__ldg(src + e);
                    uint32_t ev = (uint32_t)__ldg(reinterpret_cast<const unsigned short*>(e_attr) + e);
                    rec[i] = (ev << 16) | s;
                }
            }
            if (beg == (int)blockIdx.x * chunk) asm volatile("bar.arrive 3, %0;" :: "n"(K1_THREADS) : "memory");
            if (tid < MAXBINS) hist[tid] = 0;
            TSM(tid == 0 && d[P1_EPT - 2] != -5 && rec[P1_EPT - 2] != 0xfffffff5u, 14);
            p1_bar();
            #pragma unroll
            for (int i = 0; i < P1_EPT; i++) {
                if (d[i] >= 0) {
                    bn[i] = (int)(((uint64_t)(uint32_t)d[i] * magic) >> 24);
                    rk[i] = atomicAdd(&hist[bn[i]], 1);
                }
            }
            p1_bar();
            TSM(tid == 0, 3);
            {
                int h = (tid < MAXBINS) ? hist[tid] : 0;
                if (tid < nbins && h > 0) gbase[tid] = atomicAdd(&g_bin_cnt[tid * CNT_STRIDE], h);
                if (tid < 32) {
                    int v[8]; int sum = 0;
                    #pragma unroll
                    for (int i = 0; i < 8; i++) { v[i] = hist[lane * 8 + i]; sum += v[i]; }
                    int inc = sum;
                    #pragma unroll
                    for (int o = 1; o < 32; o <<= 1) { int t = __shfl_up_sync(0xffffffffu, inc, o); if (lane >= o) inc += t; }
                    int run = inc - sum;
                    #pragma unroll
                    for (int i = 0; i < 8; i++) { loff[lane * 8 + i] = run; run += v[i]; }
                }
            }
            p1_bar();
            TSM(tid == 0, 6);
            #pragma unroll
            for (int i = 0; i < P1_EPT; i++) {
                if (d[i] >= 0) sorted[loff[bn[i]] + rk[i]] = make_uint2(rec[i], (uint32_t)d[i]);
            }
            p1_bar();
            TSM(tid == 0, 7);
            const int cnt = end - beg;
            {
                uint2 r[P1_EPT]; int b[P1_EPT], pos[P1_EPT];
                #pragma unroll
                for (int k = 0; k < P1_EPT; k++) {
                    const int i = k * P1_T + tid;
                    r[k] = sorted[min(i, P1_CHUNK - 1)];
                }
                #pragma unroll
                for (int k = 0; k < P1_EPT; k++) {
                    const int i = k * P1_T + tid;
                    b[k] = (i < cnt) ? (int)(((uint64_t)r[k].y * magic) >> 24) : 0;
                    pos[k] = gbase[b[k]] + (i - loff[b[k]]);
                }
                #pragma unroll
                for (int k = 0; k < P1_EPT; k++) {
                    const int i = k * P1_T + tid;
                    if (i < cnt) {
                        if (pos[k] < BINCAP) {
                            g_bins[b[k] * BINCAP + pos[k]] = make_uint2(r[k].x, r[k].y - (uint32_t)(b[k] * NB));
                        } else {
                            int p = atomicAdd(&g_ovf_cnt, 2);
                            g_ovf[p] = (int)r[k].y; g_ovf[p + 1] = (int)r[k].x;
                        }
                    }
                }
            }
            p1_bar();
        }
        TSM(tid == 0, 4);
        return;
    }

    if ((int)blockIdx.x * chunk < E) asm volatile("bar.sync 3, %0;" :: "n"(K1_THREADS) : "memory");
    if (blockIdx.x < 4 && threadIdx.x < 128) {
        const char* pw = reinterpret_cast<const char*>((blockIdx.x & 2) ? w_u : w_a) + (blockIdx.x & 1) * 16384 + threadIdx.x * 128;
        asm volatile("prefetch.global.L2 [%0];" :: "l"(pw));
    }
    const int q = lane & 3;
    const int wg = warp >> 2;
    const int n_tasks = ((N + 63) >> 6) * 2;
    const uint32_t sbase = (uint32_t)__cvta_generic_to_shared(smem);
    const uint32_t xbase = sbase + 65536;
    bool w_staged = false;
    const uint32_t mbar = sbase + K1_SMEM - 16;
    uint32_t phase = 0;
    if (threadIdx.x == 0) mbar_init(mbar, 1);
    int t_beg = (int)(((long long)n_tasks * blockIdx.x) / gridDim.x);
    const int t_end = (int)(((long long)n_tasks * (blockIdx.x + 1)) / gridDim.x);
    while (t_beg < t_end) {
        const int tile0 = t_beg >> 1;
        const int t_stop = min(t_end, (tile0 + 2) << 1);
        if (threadIdx.x == 0) {
            const bool two = ((t_stop - 1) >> 1) > tile0;
            mbar_expect_tx(mbar, (two ? 32768u : 16384u) + (w_staged ? 0u : 65536u));
            tma_x_tile(xbase, &tm_x, tile0 * 64, mbar);
            if (!w_staged) tma_weights(sbase, &tm_wb, &tm_wv, mbar);
            if (two) tma_x_tile(xbase + 16384, &tm_x, tile0 * 64 + 64, mbar);
        }
        if (!w_staged) asm volatile("bar.sync 2, %0;" :: "n"(K1_GW * 32) : "memory");
        w_staged = true;
        mbar_wait(mbar, phase);
        phase ^= 1;
        TSM(threadIdx.x == 0, 1);
        for (int task = t_beg + wg; task < t_stop; task += K1_GW / 4) {
            const int tile = task >> 1, hf = task & 1;
            const uint32_t baddr = sbase + hf * 16384;
            const uint64_t descb = (uint64_t)((baddr & 0x3FFFF) >> 4) | ((uint64_t)(32768 >> 4) << 16) |
                                   ((uint64_t)(1024 >> 4) << 32) | ((uint64_t)1 << 62);
            const uint32_t aaddr = xbase + (tile - tile0) * 16384;
            const uint64_t desca = (uint64_t)((aaddr & 0x3FFFF) >> 4) | ((uint64_t)1 << 16) |
                                   ((uint64_t)(1024 >> 4) << 32) | ((uint64_t)1 << 62);
            float d[64];
            asm volatile("wgmma.fence.sync.aligned;" ::: "memory");
            #pragma unroll
            for (int ks = 0; ks < 8; ks++) {
                wgmma_m64n128k16(d, desca + (uint64_t)(((ks >> 2) * 8192 + (ks & 3) * 32) >> 4),
                                 descb + (uint64_t)(ks * (2048 >> 4)), ks > 0 ? 1 : 0);
            }
            asm volatile("wgmma.commit_group.sync.aligned;" ::: "memory");
            asm volatile("wgmma.wait_group.sync.aligned 0;" ::: "memory");
            TSM(threadIdx.x == 0, 13);
            const int r0 = tile * 64 + (warp & 3) * 16 + (lane >> 2);
            #pragma unroll
            for (int mm = 0; mm < 4; mm++) {
                const int j0 = 2 * mm, j1 = 2 * mm + 1, j2 = 8 + 2 * mm, j3 = 9 + 2 * mm;
                uint4 o0 = make_uint4(pack_bf16(d[4 * j0], d[4 * j0 + 1]), pack_bf16(d[4 * j1], d[4 * j1 + 1]),
                                      pack_bf16(d[4 * j2], d[4 * j2 + 1]), pack_bf16(d[4 * j3], d[4 * j3 + 1]));
                uint4 o1 = make_uint4(pack_bf16(d[4 * j0 + 2], d[4 * j0 + 3]), pack_bf16(d[4 * j1 + 2], d[4 * j1 + 3]),
                                      pack_bf16(d[4 * j2 + 2], d[4 * j2 + 3]), pack_bf16(d[4 * j3 + 2], d[4 * j3 + 3]));
                const int m = 4 * hf + mm;
                if (r0 < N) g_T[(size_t)r0 * 32 + 4 * m + q] = o0;
                if (r0 + 8 < N) g_T[(size_t)(r0 + 8) * 32 + 4 * m + q] = o1;
            }
        }
        t_beg = t_stop;
        if (t_beg < t_end) asm volatile("bar.sync 2, %0;" :: "n"(K1_GW * 32) : "memory");
    }
    TSM(threadIdx.x == 0, 2);
}

__device__ __forceinline__ void edge_accum(const uint4 v, const float e, const float a[4], const float cc[4],
                                           float num[4], float den[4]) {
    float y0 = fmaf(bf_lo(v.x), -LOG2E, fmaf(e, cc[0], a[0]));
    float y1 = fmaf(bf_hi(v.x), -LOG2E, fmaf(e, cc[1], a[1]));
    float y2 = fmaf(bf_lo(v.y), -LOG2E, fmaf(e, cc[2], a[2]));
    float y3 = fmaf(bf_hi(v.y), -LOG2E, fmaf(e, cc[3], a[3]));
    float s0 = rcp_approx(1.f + ex2_approx(y0));
    float s1 = rcp_approx(1.f + ex2_approx(y1));
    float s2 = rcp_approx(1.f + ex2_approx(y2));
    float s3 = rcp_approx(1.f + ex2_approx(y3));
    den[0] += s0; den[1] += s1; den[2] += s2; den[3] += s3;
    num[0] = fmaf(s0, bf_lo(v.z), num[0]);
    num[1] = fmaf(s1, bf_hi(v.z), num[1]);
    num[2] = fmaf(s2, bf_lo(v.w), num[2]);
    num[3] = fmaf(s3, bf_hi(v.w), num[3]);
}

#define K2_THREADS 1024
#define K2_D 2
#define K2_GS 2
#define K2_RPT ((BINCAP + K2_THREADS - 1) / K2_THREADS)
#define K2_NW (K2_THREADS / 32)
#define SORT_WORDS (BINCAP + 4 * MAXNB)
#define K2_OFF_W 0
#define K2_OFF_X 65536
#define K2_OFF_A (K2_OFF_X + 32768)
#define K2_OFF_U (K2_OFF_A + MAXNB * 256)
#define K2_OFF_PART (K2_OFF_U + MAXNB * 256)
#define K2_OFF_SORT (K2_OFF_PART + K2_NW * 1024)
#define K2_OFF_HIST (K2_OFF_SORT + SORT_WORDS * 4)
#define K2_OFF_OFF (K2_OFF_HIST + MAXNB * 4)
#define K2_OFF_MBAR (K2_OFF_OFF + (MAXNB + 4) * 4)
#define K2_DYN_SMEM (K2_OFF_MBAR + 16)
#define K2_ST (K2_THREADS - 512)
#define K2_SRPT ((BINCAP + K2_ST - 1) / K2_ST)

struct Grp { uint4 v[K2_GS]; };

__device__ __forceinline__ const uint4* row_ptr(const char* Tl, uint32_t rec) {
    return reinterpret_cast<const uint4*>(Tl + (size_t)((rec & 0xffffu) * 512u));
}
__device__ __forceinline__ void grp_load(Grp& g, const uint32_t* sp, const char* Tl) {
    const uint2 t = *reinterpret_cast<const uint2*>(sp);
    g.v[0] = __ldg(row_ptr(Tl, t.x));
    g.v[1] = __ldg(row_ptr(Tl, t.y));
}
__device__ __forceinline__ void grp_consume(const Grp& g, const uint32_t* sp, const float a[4], const float cc[4],
                                            float num[4], float den[4]) {
    const uint2 t = *reinterpret_cast<const uint2*>(sp);
    edge_accum(g.v[0], bf_hi(t.x), a, cc, num, den);
    edge_accum(g.v[1], bf_hi(t.y), a, cc, num, den);
}

__device__ __forceinline__ void load_a(const uint8_t* smem, int ln, int lane, float a[4]) {
    const uint2 av = reinterpret_cast<const uint2*>(smem + K2_OFF_A)[ln * 32 + (lane ^ ((ln & 3) << 2))];
    a[0] = -LOG2E * bf_lo(av.x); a[1] = -LOG2E * bf_hi(av.x); a[2] = -LOG2E * bf_lo(av.y); a[3] = -LOG2E * bf_hi(av.y);
}
__device__ __forceinline__ void write_node(const uint8_t* smem, __nv_bfloat16* out, int ln, int n,
                                           int lane, const float num[4], const float den[4]) {
    const uint2 uv = reinterpret_cast<const uint2*>(smem + K2_OFF_U)[ln * 32 + (lane ^ ((ln & 3) << 2))];
    const int r = ln & 63, c16 = (lane >> 2) * 2;
    const uint8_t* xr = smem + K2_OFF_X + (ln >> 6) * 16384 + (c16 >> 3) * 8192 + r * 128 + (lane & 3) * 4;
    const uint32_t x0 = *reinterpret_cast<const uint32_t*>(xr + (((c16 & 7) ^ (r & 7)) << 4));
    const uint32_t x1 = *reinterpret_cast<const uint32_t*>(xr + ((((c16 + 1) & 7) ^ (r & 7)) << 4));
    const float u4[4] = { bf_lo(uv.x), bf_hi(uv.x), bf_lo(uv.y), bf_hi(uv.y) };
    const float x4[4] = { bf_lo(x0), bf_hi(x0), bf_lo(x1), bf_hi(x1) };
    float o[4];
    #pragma unroll
    for (int i = 0; i < 4; i++) {
        float agg = round_bf16(__fdividef(num[i], den[i] + 1e-6f));
        float z = round_bf16(u4[i] + agg);
        float rz = (z > 0.f) ? z : 0.f * z;
        o[i] = x4[i] + rz;
    }
    uint32_t* o32 = reinterpret_cast<uint32_t*>(out) + (size_t)n * 64 + (lane >> 2) * 8 + (lane & 3);
    o32[0] = pack_bf16(o[0], o[1]); o32[4] = pack_bf16(o[2], o[3]);
}

__device__ __noinline__ void slow_path(const uint8_t* smem, __nv_bfloat16* out, int node0, int nn, int ovf_n,
                                       float c0, float c1, float c2, float c3) {
    const uint32_t* s_sorted = reinterpret_cast<const uint32_t*>(smem + K2_OFF_SORT);
    const int* s_off = reinterpret_cast<const int*>(smem + K2_OFF_OFF);
    const int lane = threadIdx.x & 31, warp = threadIdx.x >> 5;
    const float cc[4] = { c0, c1, c2, c3 };
    const char* Tl = reinterpret_cast<const char*>(g_T) + lane * 16;
    for (int ln = warp; ln < nn; ln += K2_NW) {
        float a[4];
        load_a(smem, ln, lane, a);
        float num[4] = {0.f, 0.f, 0.f, 0.f}, den[4] = {0.f, 0.f, 0.f, 0.f};
        for (int i = s_off[ln]; i < s_off[ln + 1]; i++) {
            const uint32_t r = s_sorted[i];
            edge_accum(__ldg(row_ptr(Tl, r)), bf_hi(r), a, cc, num, den);
        }
        const int n = node0 + ln;
        for (int base = 0; base < ovf_n; base += 64) {
            int i2 = base + 2 * lane;
            int od = (i2 < ovf_n) ? g_ovf[i2] : -1;
            uint32_t orec = (i2 < ovf_n) ? (uint32_t)g_ovf[i2 + 1] : 0u;
            unsigned msk = __ballot_sync(0xffffffffu, od == n);
            while (msk) {
                int l = __ffs(msk) - 1; msk &= msk - 1;
                uint32_t r = __shfl_sync(0xffffffffu, orec, l);
                edge_accum(__ldg(row_ptr(Tl, r)), bf_hi(r), a, cc, num, den);
            }
        }
        write_node(smem, out, ln, n, lane, num, den);
    }
}

__global__ void __launch_bounds__(K2_THREADS, 1) k2_kernel(
    const __grid_constant__ CUtensorMap tm_x, const __grid_constant__ CUtensorMap tm_wa, const __grid_constant__ CUtensorMap tm_wu,
    const __nv_bfloat16* __restrict__ w_c, __nv_bfloat16* __restrict__ out, int N, int NB)
{
    extern __shared__ __align__(1024) uint8_t smem[];
    float4* s_part = reinterpret_cast<float4*>(smem + K2_OFF_PART);
    uint32_t* s_sorted = reinterpret_cast<uint32_t*>(smem + K2_OFF_SORT);
    int* s_hist = reinterpret_cast<int*>(smem + K2_OFF_HIST);
    int* s_off = reinterpret_cast<int*>(smem + K2_OFF_OFF);

    const int tid = threadIdx.x;
    const int lane = tid & 31, warp = tid >> 5;
    const int bin = blockIdx.x;
    const int node0 = bin * NB;
    const int nn = min(NB, N - node0);
    const uint32_t sb = (uint32_t)__cvta_generic_to_shared(smem);
    TSM(tid == 0, 5);

    const int fw = (lane >> 2) * 8 + (lane & 3);
    const uint2 wc = make_uint2(__ldg(reinterpret_cast<const uint32_t*>(w_c) + fw), __ldg(reinterpret_cast<const uint32_t*>(w_c) + fw + 4));
    s_part[warp * 64 + lane] = make_float4(0.f, 0.f, 0.f, 0.f);
    s_part[warp * 64 + 32 + lane] = make_float4(0.f, 0.f, 0.f, 0.f);
    const uint32_t mbar = sb + K2_OFF_MBAR;
    if (tid == 0) {
        mbar_init(mbar, 1);
        mbar_expect_tx(mbar, (nn > 64 ? 32768u : 16384u) + 65536u);
        tma_x_tile(sb + K2_OFF_X, &tm_x, node0, mbar);
        tma_weights(sb + K2_OFF_W, &tm_wa, &tm_wu, mbar);
        if (nn > 64) tma_x_tile(sb + K2_OFF_X + 16384, &tm_x, node0 + 64, mbar);
    }
    if (tid < MAXNB) s_hist[tid] = 0;
    for (int i = tid; i < SORT_WORDS; i += K2_THREADS) s_sorted[i] = (uint32_t)N;
    __syncthreads();
    asm volatile("griddepcontrol.wait;" ::: "memory");
    TSM(tid == 0, 8);
    {
        uint2 r[K2_RPT]; int rk[K2_RPT];
        const int cnt = min(g_bin_cnt[bin * CNT_STRIDE], BINCAP);
        if (tid == 64) s_off[MAXNB + 1] = g_ovf_cnt;
        #pragma unroll
        for (int i = 0; i < K2_RPT; i++) {
            int idx = i * K2_THREADS + tid;
            if (idx < cnt) r[i] = g_bins[bin * BINCAP + idx];
        }
        const int wg = warp >> 2, tile = wg >> 2, h = wg & 3;
        const bool do_mma = tile * 64 < nn;
        float d[32];
        if (do_mma) {
            const uint32_t aaddr = sb + K2_OFF_X + tile * 16384;
            const uint64_t desca = (uint64_t)((aaddr & 0x3FFFF) >> 4) | ((uint64_t)1 << 16) |
                                   ((uint64_t)(1024 >> 4) << 32) | ((uint64_t)1 << 62);
            const uint32_t baddr = sb + K2_OFF_W + h * 16384;
            const uint64_t descb = (uint64_t)((baddr & 0x3FFFF) >> 4) | ((uint64_t)(32768 >> 4) << 16) |
                                   ((uint64_t)(1024 >> 4) << 32) | ((uint64_t)1 << 62);
            mbar_wait(mbar, 0);
            asm volatile("wgmma.fence.sync.aligned;" ::: "memory");
            #pragma unroll
            for (int ks = 0; ks < 8; ks++) {
                wgmma_m64n64k16(d, desca + (uint64_t)(((ks >> 2) * 8192 + (ks & 3) * 32) >> 4),
                                descb + (uint64_t)(ks * (2048 >> 4)), ks > 0 ? 1 : 0);
            }
            asm volatile("wgmma.commit_group.sync.aligned;" ::: "memory");
        }
        #pragma unroll
        for (int i = 0; i < K2_RPT; i++) {
            int idx = i * K2_THREADS + tid;
            if (idx < cnt) rk[i] = atomicAdd(&s_hist[r[i].y], 1);
        }
        __syncthreads();
        if (warp == 0) {
            int v[4]; int sum = 0;
            #pragma unroll
            for (int i = 0; i < 4; i++) { v[i] = (s_hist[lane * 4 + i] + K2_GS - 1) & ~(K2_GS - 1); sum += v[i]; }
            int inc = sum;
            #pragma unroll
            for (int o = 1; o < 32; o <<= 1) { int t = __shfl_up_sync(0xffffffffu, inc, o); if (lane >= o) inc += t; }
            int run = inc - sum;
            #pragma unroll
            for (int i = 0; i < 4; i++) { s_off[lane * 4 + i] = run; run += v[i]; }
            if (lane == 31) s_off[MAXNB] = run;
        }
        if (tid == 32) g_bin_cnt[bin * CNT_STRIDE] = 0;
        __syncthreads();
        #pragma unroll
        for (int i = 0; i < K2_RPT; i++) {
            int idx = i * K2_THREADS + tid;
            if (idx < cnt) s_sorted[s_off[r[i].y] + rk[i]] = r[i].x;
        }
        TSM(tid == 0, 9);
        if (do_mma) {
            asm volatile("wgmma.wait_group.sync.aligned 0;" ::: "memory");
            #pragma unroll
            for (int i = 0; i < 32; i++) asm volatile("" : "+f"(d[i]) :: "memory");
            uint2* dst = reinterpret_cast<uint2*>(smem + ((h >> 1) ? K2_OFF_U : K2_OFF_A));
            const int r0 = tile * 64 + (warp & 3) * 16 + (lane >> 2);
            const int sw = (r0 & 3) << 2;
            #pragma unroll
            for (int mm = 0; mm < 4; mm++) {
                const int j0 = 2 * mm, j1 = 2 * mm + 1;
                const int slot = (4 * (4 * (h & 1) + mm) + (lane & 3)) ^ sw;
                dst[r0 * 32 + slot] = make_uint2(pack_bf16(d[4 * j0], d[4 * j0 + 1]), pack_bf16(d[4 * j1], d[4 * j1 + 1]));
                dst[(r0 + 8) * 32 + slot] = make_uint2(pack_bf16(d[4 * j0 + 2], d[4 * j0 + 3]), pack_bf16(d[4 * j1 + 2], d[4 * j1 + 3]));
            }
        } else {
            mbar_wait(mbar, 0);
        }
    }
    __syncthreads();
    TSM(tid == 0, 10);
    const float cc[4] = { -LOG2E * bf_lo(wc.x), -LOG2E * bf_hi(wc.x), -LOG2E * bf_lo(wc.y), -LOG2E * bf_hi(wc.y) };
    const int ovf_n = s_off[MAXNB + 1];

    if (ovf_n != 0) {
        slow_path(smem, out, node0, nn, ovf_n, cc[0], cc[1], cc[2], cc[3]);
        __syncthreads();
        if (tid == 0) {
            __threadfence();
            int t = atomicAdd(&g_done, 1);
            if (t == (int)gridDim.x - 1) { g_done = 0; __threadfence(); g_ovf_cnt = 0; }
        }
        return;
    }

    const char* Tl = reinterpret_cast<const char*>(g_T) + lane * 16;
    const int G = s_off[MAXNB] / K2_GS;
    int g = (G * warp) / K2_NW;
    const int g1 = (G * (warp + 1)) / K2_NW;
    int ln;
    {
        int c_lo = 0;
        #pragma unroll
        for (int i = 0; i < 4; i++) {
            int node = i * 32 + lane;
            int o = (node < nn) ? s_off[node] : 0x7fffffff;
            c_lo += __popc(__ballot_sync(0xffffffffu, o < g * K2_GS));
        }
        ln = c_lo;
    }
    bool head = ln > 0;
    if (head) ln--;
    float a[4], num[4] = {0.f, 0.f, 0.f, 0.f}, den[4] = {0.f, 0.f, 0.f, 0.f};
    int node_end;

    auto load_node = [&]() {
        load_a(smem, ln, lane, a);
        node_end = s_off[ln + 1] / K2_GS;
    };
    auto finish_node = [&]() { write_node(smem, out, ln, node0 + ln, lane, num, den); };
    auto close_node = [&]() {
        if (head) {
            s_part[warp * 64 + lane] = make_float4(num[0], num[1], num[2], num[3]);
            s_part[warp * 64 + 32 + lane] = make_float4(den[0], den[1], den[2], den[3]);
            head = false;
        } else {
            finish_node();
        }
        #pragma unroll
        for (int i = 0; i < 4; i++) { num[i] = 0.f; den[i] = 0.f; }
    };

    bool tail = false;
    if (g < g1 || warp == K2_NW - 1) {
        load_node();
        Grp b[K2_D];
        #pragma unroll
        for (int d = 0; d < K2_D; d++)
            if (g + d < g1) grp_load(b[d], s_sorted + K2_GS * (g + d), Tl);
        while (g < g1) {
            #pragma unroll
            for (int d = 0; d < K2_D; d++) {
                if (g < g1) {
                    while (g == node_end) { close_node(); ln++; load_node(); }
                    grp_consume(b[d], s_sorted + K2_GS * g, a, cc, num, den);
                    if (g + K2_D < g1) grp_load(b[d], s_sorted + K2_GS * (g + K2_D), Tl);
                    g++;
                }
            }
        }
        if (warp == K2_NW - 1) {
            while (true) { close_node(); ln++; if (ln >= nn) break; load_node(); }
        } else if (node_end == g1 || head) {
            close_node();
        } else {
            tail = true;
        }
    }
    TSM(tid == 0, 11);
    __syncthreads();
    TSM(tid == 0, 12);
    if (tail) {
        for (int w2 = warp + 1; w2 < K2_NW && (G * w2) / K2_NW < node_end; w2++) {
            const float4 pn = s_part[w2 * 64 + lane], pd = s_part[w2 * 64 + 32 + lane];
            num[0] += pn.x; num[1] += pn.y; num[2] += pn.z; num[3] += pn.w;
            den[0] += pd.x; den[1] += pd.y; den[2] += pd.z; den[3] += pd.w;
        }
        finish_node();
    }
}

extern "C" void kernel_launch(void* const* d_in, const int* in_sizes, int n_in,
                              void* d_out, int out_size) {
    const __nv_bfloat16* x      = (const __nv_bfloat16*)d_in[0];
    const __nv_bfloat16* e_attr = (const __nv_bfloat16*)d_in[1];
    const int* src = (const int*)d_in[2];
    const int* dst = (const int*)d_in[3];
    const __nv_bfloat16* w_a = (const __nv_bfloat16*)d_in[4];
    const __nv_bfloat16* w_b = (const __nv_bfloat16*)d_in[5];
    const __nv_bfloat16* w_c = (const __nv_bfloat16*)d_in[6];
    const __nv_bfloat16* w_u = (const __nv_bfloat16*)d_in[7];
    const __nv_bfloat16* w_v = (const __nv_bfloat16*)d_in[8];
    __nv_bfloat16* out = (__nv_bfloat16*)d_out;
    const int N = in_sizes[0] / D_FEAT;
    const int E = in_sizes[2];
    if (N > MAX_N || 2 * E > MAX_E || N <= 0) return;

    static int num_sms = 0;
    if (num_sms == 0) {
        int dev = 0;
        cudaGetDevice(&dev);
        cudaDeviceGetAttribute(&num_sms, cudaDevAttrMultiProcessorCount, dev);
        if (num_sms <= 0 || num_sms > MAXBINS) num_sms = 132;
        cudaFuncSetAttribute(k1_kernel, cudaFuncAttributeMaxDynamicSharedMemorySize, K1_SMEM);
        cudaFuncSetAttribute(k2_kernel, cudaFuncAttributeMaxDynamicSharedMemorySize, K2_DYN_SMEM);
    }
    typedef CUresult (*EncodeFn)(CUtensorMap*, CUtensorMapDataType, cuuint32_t, void*, const cuuint64_t*, const cuuint64_t*,
                                 const cuuint32_t*, const cuuint32_t*, CUtensorMapInterleave, CUtensorMapSwizzle,
                                 CUtensorMapL2promotion, CUtensorMapFloatOOBfill);
    static EncodeFn encode = nullptr;
    if (!encode) {
        void* fn = nullptr;
        cudaDriverEntryPointQueryResult qres;
        if (cudaGetDriverEntryPoint("cuTensorMapEncodeTiled", &fn, cudaEnableDefault, &qres) != cudaSuccess || !fn) return;
        encode = (EncodeFn)fn;
    }
    auto make_map = [&](CUtensorMap* m, const void* base, int rows, int box_rows) {
        cuuint64_t dims[2] = { D_FEAT, (cuuint64_t)rows };
        cuuint64_t strides[1] = { D_FEAT * 2 };
        cuuint32_t box[2] = { 64, (cuuint32_t)box_rows };
        cuuint32_t es[2] = { 1, 1 };
        return encode(m, CU_TENSOR_MAP_DATA_TYPE_BFLOAT16, 2, const_cast<void*>(base), dims, strides, box, es,
                      CU_TENSOR_MAP_INTERLEAVE_NONE, CU_TENSOR_MAP_SWIZZLE_128B, CU_TENSOR_MAP_L2_PROMOTION_L2_128B,
                      CU_TENSOR_MAP_FLOAT_OOB_FILL_NONE);
    };
    CUtensorMap tm_x, tm_wa, tm_wb, tm_wu, tm_wv;
    if (make_map(&tm_x, x, N, 64) != CUDA_SUCCESS || make_map(&tm_wa, w_a, D_FEAT, 128) != CUDA_SUCCESS ||
        make_map(&tm_wb, w_b, D_FEAT, 128) != CUDA_SUCCESS || make_map(&tm_wu, w_u, D_FEAT, 128) != CUDA_SUCCESS ||
        make_map(&tm_wv, w_v, D_FEAT, 128) != CUDA_SUCCESS) return;
    cudaStream_t st = cudaStreamPerThread;
    int NB = (N + num_sms - 1) / num_sms;
    if (NB > MAXNB) NB = MAXNB;
    const int nbins = (N + NB - 1) / NB;
    const uint32_t magic = (uint32_t)(((1u << 24) + NB - 1) / NB);
    const int P = num_sms;
    int chunk = (E + P - 1) / P;
    if (chunk > P1_CHUNK) chunk = P1_CHUNK;
    if (chunk < 1) chunk = 1;
    k1_kernel<<<P, K1_THREADS, K1_SMEM, st>>>(tm_x, tm_wb, tm_wv, x, e_attr, src, dst, w_b, w_v, w_a, w_u, N, E, chunk, NB, nbins, magic);

    cudaLaunchConfig_t cfg = {};
    cfg.gridDim = dim3(nbins);
    cfg.blockDim = dim3(K2_THREADS);
    cfg.dynamicSmemBytes = K2_DYN_SMEM;
    cfg.stream = st;
    cudaLaunchAttribute at[1];
    at[0].id = cudaLaunchAttributeProgrammaticStreamSerialization;
    at[0].val.programmaticStreamSerializationAllowed = 1;
    cfg.attrs = at; cfg.numAttrs = 1;
    cudaLaunchKernelEx(&cfg, k2_kernel, tm_x, tm_wa, tm_wu, w_c, out, N, NB);
}
```

```cpp
#include <cuda_runtime.h>
#include <cuda.h>
#include <cuda_bf16.h>
#include <stdint.h>

#define D_FEAT 128
#define MAX_N 16384
#define MAX_E (1 << 20)
#define LOG2E 1.4426950408889634f

#define MAXBINS 256
#define MAXNB 128
#define BINCAP 3072
__device__ uint4 g_AU[MAX_N * 32];
__device__ uint4 g_T[(MAX_N + 1) * 32];
#define CNT_STRIDE 1
__device__ int g_bin_cnt[MAXBINS * CNT_STRIDE];
__device__ uint2 g_bins[MAXBINS * BINCAP];
__device__ int g_ovf[MAX_E];
__device__ int g_ovf_cnt;
__device__ int g_done;

#define TSM(cond, i)
__device__ __forceinline__ float ex2_approx(float x) {
    float y; asm("ex2.approx.ftz.f32 %0, %1;" : "=f"(y) : "f"(x)); return y;
}
__device__ __forceinline__ float rcp_approx(float x) {
    float y; asm("rcp.approx.ftz.f32 %0, %1;" : "=f"(y) : "f"(x)); return y;
}
__device__ __forceinline__ uint32_t pack_bf16(float lo, float hi) {
    __nv_bfloat162 t = __floats2bfloat162_rn(lo, hi);
    return *reinterpret_cast<uint32_t*>(&t);
}
__device__ __forceinline__ float bf_lo(uint32_t v) { return __uint_as_float(v << 16); }
__device__ __forceinline__ float bf_hi(uint32_t v) { return __uint_as_float(v & 0xffff0000u); }
__device__ __forceinline__ float round_bf16(float x) { return __bfloat162float(__float2bfloat16_rn(x)); }

__device__ __forceinline__ void mma_bf16(float c[4], uint32_t a0, uint32_t a1, uint32_t a2, uint32_t a3,
                                         uint32_t b0, uint32_t b1) {
    asm volatile("mma.sync.aligned.m16n8k16.row.col.f32.bf16.bf16.f32 "
                 "{%0,%1,%2,%3}, {%4,%5,%6,%7}, {%8,%9}, {%0,%1,%2,%3};"
                 : "+f"(c[0]), "+f"(c[1]), "+f"(c[2]), "+f"(c[3])
                 : "r"(a0), "r"(a1), "r"(a2), "r"(a3), "r"(b0), "r"(b1));
}
__device__ __forceinline__ void ldmatrix_x4_trans(uint32_t& r0, uint32_t& r1, uint32_t& r2, uint32_t& r3, uint32_t addr) {
    asm volatile("ldmatrix.sync.aligned.m8n8.x4.trans.shared.b16 {%0,%1,%2,%3}, [%4];"
                 : "=r"(r0), "=r"(r1), "=r"(r2), "=r"(r3) : "r"(addr));
}

__device__ __forceinline__ void cp_async16(uint32_t saddr, const void* g) {
    asm volatile("cp.async.cg.shared.global [%0], [%1], 16;" :: "r"(saddr), "l"(g) : "memory");
}
__device__ __forceinline__ void cp_async16_zfill(uint32_t saddr, const void* g, int src_size) {
    asm volatile("cp.async.cg.shared.global [%0], [%1], 16, %2;" :: "r"(saddr), "l"(g), "r"(src_size) : "memory");
}
__device__ __forceinline__ void stage_weight(uint32_t sdst, const __nv_bfloat16* w, int mtx, int tid, int nthreads) {
    const uint4* W = reinterpret_cast<const uint4*>(w);
    for (int u = tid; u < 2048; u += nthreads) {
        int k = u >> 4, c16 = u & 15;
        int kg = k >> 3, rr = k & 7;
        int h = mtx * 2 + (c16 >> 3);
        cp_async16(sdst + kg * 4096 + h * 1024 + rr * 128 + (((c16 & 7) ^ rr) << 4), W + u);
    }
}
__device__ __forceinline__ void stage_x_tile(uint32_t sdst, const __nv_bfloat16* x, int row0, int N, int tid, int nthreads) {
    const uint4* X = reinterpret_cast<const uint4*>(x);
    for (int u = tid; u < 1024; u += nthreads) {
        int r = u >> 4, c16 = u & 15;
        int gr = row0 + r;
        bool ok = gr < N;
        cp_async16_zfill(sdst + (c16 >> 3) * 8192 + r * 128 + (((c16 & 7) ^ (r & 7)) << 4),
                         X + (size_t)(ok ? gr : 0) * 16 + c16, ok ? 16 : 0);
    }
}

__device__ __forceinline__ void mbar_init(uint32_t bar, int cnt) {
    asm volatile("mbarrier.init.shared::cta.b64 [%0], %1;" :: "r"(bar), "r"(cnt) : "memory");
    asm volatile("fence.mbarrier_init.release.cluster;" ::: "memory");
    asm volatile("fence.proxy.async.shared::cta;" ::: "memory");
}
__device__ __forceinline__ void mbar_expect_tx(uint32_t bar, uint32_t bytes) {
    asm volatile("mbarrier.arrive.expect_tx.shared::cta.b64 _, [%0], %1;" :: "r"(bar), "r"(bytes) : "memory");
}
__device__ __forceinline__ void mbar_wait(uint32_t bar, uint32_t parity) {
    asm volatile("{\n.reg .pred p;\nWAIT_LOOP:\n"
                 "mbarrier.try_wait.parity.shared::cta.b64 p, [%0], %1;\n"
                 "@p bra WAIT_DONE;\nbra WAIT_LOOP;\nWAIT_DONE:\n}" :: "r"(bar), "r"(parity) : "memory");
}
__device__ __forceinline__ void tma_2d(uint32_t sdst, const CUtensorMap* tm, int c0, int c1, uint32_t bar) {
    asm volatile("cp.async.bulk.tensor.2d.shared::cluster.global.mbarrier::complete_tx::bytes [%0], [%1, {%3, %4}], [%2];"
                 :: "r"(sdst), "l"(reinterpret_cast<uint64_t>(tm)), "r"(bar), "r"(c0), "r"(c1) : "memory");
}
__device__ __forceinline__ void tma_weights(uint32_t sdst, const CUtensorMap* m0, const CUtensorMap* m1, uint32_t bar) {
    tma_2d(sdst, m0, 0, 0, bar);
    tma_2d(sdst + 16384, m0, 64, 0, bar);
    tma_2d(sdst + 32768, m1, 0, 0, bar);
    tma_2d(sdst + 49152, m1, 64, 0, bar);
}
__device__ __forceinline__ void tma_x_tile(uint32_t sdst, const CUtensorMap* mx, int row0, uint32_t bar) {
    tma_2d(sdst, mx, 0, row0, bar);
    tma_2d(sdst + 8192, mx, 64, row0, bar);
}

__device__ __forceinline__ void wgmma_m64n128k16(float d[64], uint64_t desc_a, uint64_t desc_b, int scale_d) {
    asm volatile("{\n.reg .pred p;\nsetp.ne.b32 p, %66, 0;\n"
                 "wgmma.mma_async.sync.aligned.m64n128k16.f32.bf16.bf16 {%0,%1,%2,%3,%4,%5,%6,%7,%8,%9,%10,%11,%12,%13,%14,%15,%16,%17,%18,%19,%20,%21,%22,%23,%24,%25,%26,%27,%28,%29,%30,%31,%32,%33,%34,%35,%36,%37,%38,%39,%40,%41,%42,%43,%44,%45,%46,%47,%48,%49,%50,%51,%52,%53,%54,%55,%56,%57,%58,%59,%60,%61,%62,%63}, %64, %65, p, 1, 1, 0, 1;\n}"
                 : "+f"(d[0]),"+f"(d[1]),"+f"(d[2]),"+f"(d[3]),"+f"(d[4]),"+f"(d[5]),"+f"(d[6]),"+f"(d[7]),"+f"(d[8]),"+f"(d[9]),"+f"(d[10]),"+f"(d[11]),"+f"(d[12]),"+f"(d[13]),"+f"(d[14]),"+f"(d[15]),"+f"(d[16]),"+f"(d[17]),"+f"(d[18]),"+f"(d[19]),"+f"(d[20]),"+f"(d[21]),"+f"(d[22]),"+f"(d[23]),"+f"(d[24]),"+f"(d[25]),"+f"(d[26]),"+f"(d[27]),"+f"(d[28]),"+f"(d[29]),"+f"(d[30]),"+f"(d[31]),"+f"(d[32]),"+f"(d[33]),"+f"(d[34]),"+f"(d[35]),"+f"(d[36]),"+f"(d[37]),"+f"(d[38]),"+f"(d[39]),"+f"(d[40]),"+f"(d[41]),"+f"(d[42]),"+f"(d[43]),"+f"(d[44]),"+f"(d[45]),"+f"(d[46]),"+f"(d[47]),"+f"(d[48]),"+f"(d[49]),"+f"(d[50]),"+f"(d[51]),"+f"(d[52]),"+f"(d[53]),"+f"(d[54]),"+f"(d[55]),"+f"(d[56]),"+f"(d[57]),"+f"(d[58]),"+f"(d[59]),"+f"(d[60]),"+f"(d[61]),"+f"(d[62]),"+f"(d[63])
                 : "l"(desc_a), "l"(desc_b), "r"(scale_d));
}

__device__ __forceinline__ void wgmma_m64n64k16(float d[32], uint64_t desc_a, uint64_t desc_b, int scale_d) {
    asm volatile("{\n.reg .pred p;\nsetp.ne.b32 p, %34, 0;\n"
                 "wgmma.mma_async.sync.aligned.m64n64k16.f32.bf16.bf16 {%0,%1,%2,%3,%4,%5,%6,%7,%8,%9,%10,%11,%12,%13,%14,%15,%16,%17,%18,%19,%20,%21,%22,%23,%24,%25,%26,%27,%28,%29,%30,%31}, %32, %33, p, 1, 1, 0, 1;\n}"
                 : "+f"(d[0]),"+f"(d[1]),"+f"(d[2]),"+f"(d[3]),"+f"(d[4]),"+f"(d[5]),"+f"(d[6]),"+f"(d[7]),"+f"(d[8]),"+f"(d[9]),"+f"(d[10]),"+f"(d[11]),"+f"(d[12]),"+f"(d[13]),"+f"(d[14]),"+f"(d[15]),"+f"(d[16]),"+f"(d[17]),"+f"(d[18]),"+f"(d[19]),"+f"(d[20]),"+f"(d[21]),"+f"(d[22]),"+f"(d[23]),"+f"(d[24]),"+f"(d[25]),"+f"(d[26]),"+f"(d[27]),"+f"(d[28]),"+f"(d[29]),"+f"(d[30]),"+f"(d[31])
                 : "l"(desc_a), "l"(desc_b), "r"(scale_d));
}

#define K1_GW 12
#define P1_FIRST
#define P1_T 256
#define K1_THREADS (K1_GW * 32 + P1_T)
#define P1_EPT ((2560 + P1_T - 1) / P1_T)
#define P1_CHUNK (P1_T * P1_EPT)
#define K1_WBYTES (131072 + 2 * 16384)
#define K1_SMEM (K1_WBYTES + 3 * MAXBINS * 4 + P1_CHUNK * 8 + 16)

__device__ __forceinline__ void p1_bar() { asm volatile("bar.sync 1, %0;" :: "n"(P1_T) : "memory"); }

__global__ void __launch_bounds__(K1_THREADS, 1) k1_kernel(
    const __grid_constant__ CUtensorMap tm_x, const __grid_constant__ CUtensorMap tm_wb, const __grid_constant__ CUtensorMap tm_wv,
    const __grid_constant__ CUtensorMap tm_wa, const __grid_constant__ CUtensorMap tm_wu,
    const __nv_bfloat16* __restrict__ x, const __nv_bfloat16* __restrict__ e_attr,
    const int* __restrict__ src, const int* __restrict__ dst,
    const __nv_bfloat16* __restrict__ w_b, const __nv_bfloat16* __restrict__ w_v,
    const __nv_bfloat16* __restrict__ w_a, const __nv_bfloat16* __restrict__ w_u,
    int N, int E, int chunk, int NB, int nbins, uint32_t magic)
{
    extern __shared__ __align__(1024) uint8_t smem[];
    asm volatile("griddepcontrol.launch_dependents;");
    TSM(threadIdx.x == 0, 0);

    const int warp = threadIdx.x >> 5, lane = threadIdx.x & 31;

    if (warp >= K1_GW) {
        const int tid = threadIdx.x - K1_GW * 32;
        if (blockIdx.x == 0 && tid < 32)
            g_T[(size_t)N * 32 + tid] = make_uint4(0xff80ff80u, 0xff80ff80u, 0u, 0u);
        int* hist = reinterpret_cast<int*>(smem + K1_WBYTES);
        int* loff = hist + MAXBINS;
        int* gbase = loff + MAXBINS;
        uint2* sorted = reinterpret_cast<uint2*>(smem + K1_WBYTES + 3 * MAXBINS * 4);
        for (int beg = blockIdx.x * chunk; beg < E; beg += gridDim.x * chunk) {
            const int end = min(E, beg + chunk);
            int d[P1_EPT]; uint32_t rec[P1_EPT]; int rk[P1_EPT]; int bn[P1_EPT];
            #pragma unroll
            for (int i = 0; i < P1_EPT; i++) {
                int e = beg + i * P1_T + tid;
                d[i] = -1;
                if (e < end) {
                    d[i] = __ldg(dst + e);
                    uint32_t s = (uint32_t)__ldg(src + e);
                    uint32_t ev = (uint32_t)__ldg(reinterpret_cast<const unsigned short*>(e_attr) + e);
                    rec[i] = (ev << 16) | s;
                }
            }
            if (beg == (int)blockIdx.x * chunk) asm volatile("bar.arrive 3, %0;" :: "n"(K1_THREADS) : "memory");
            if (tid < MAXBINS) hist[tid] = 0;
            TSM(tid == 0 && d[P1_EPT - 2] != -5 && rec[P1_EPT - 2] != 0xfffffff5u, 14);
            p1_bar();
            #pragma unroll
            for (int i = 0; i < P1_EPT; i++) {
                if (d[i] >= 0) {
                    bn[i] = (int)(((uint64_t)(uint32_t)d[i] * magic) >> 24);
                    rk[i] = atomicAdd(&hist[bn[i]], 1);
                }
            }
            p1_bar();
            TSM(tid == 0, 3);
            {
                int h = (tid < MAXBINS) ? hist[tid] : 0;
                if (tid < nbins && h > 0) gbase[tid] = atomicAdd(&g_bin_cnt[tid * CNT_STRIDE], h);
                if (tid < 32) {
                    int v[8]; int sum = 0;
                    #pragma unroll
                    for (int i = 0; i < 8; i++) { v[i] = hist[lane * 8 + i]; sum += v[i]; }
                    int inc = sum;
                    #pragma unroll
                    for (int o = 1; o < 32; o <<= 1) { int t = __shfl_up_sync(0xffffffffu, inc, o); if (lane >= o) inc += t; }
                    int run = inc - sum;
                    #pragma unroll
                    for (int i = 0; i < 8; i++) { loff[lane * 8 + i] = run; run += v[i]; }
                }
            }
            p1_bar();
            TSM(tid == 0, 6);
            #pragma unroll
            for (int i = 0; i < P1_EPT; i++) {
                if (d[i] >= 0) sorted[loff[bn[i]] + rk[i]] = make_uint2(rec[i], (uint32_t)d[i]);
            }
            p1_bar();
            TSM(tid == 0, 7);
            const int cnt = end - beg;
            {
                uint2 r[P1_EPT]; int b[P1_EPT], pos[P1_EPT];
                #pragma unroll
                for (int k = 0; k < P1_EPT; k++) {
                    const int i = k * P1_T + tid;
                    r[k] = sorted[min(i, P1_CHUNK - 1)];
                }
                #pragma unroll
                for (int k = 0; k < P1_EPT; k++) {
                    const int i = k * P1_T + tid;
                    b[k] = (i < cnt) ? (int)(((uint64_t)r[k].y * magic) >> 24) : 0;
                    pos[k] = gbase[b[k]] + (i - loff[b[k]]);
                }
                #pragma unroll
                for (int k = 0; k < P1_EPT; k++) {
                    const int i = k * P1_T + tid;
                    if (i < cnt) {
                        if (pos[k] < BINCAP) {
                            g_bins[b[k] * BINCAP + pos[k]] = make_uint2(r[k].x, r[k].y - (uint32_t)(b[k] * NB));
                        } else {
                            int p = atomicAdd(&g_ovf_cnt, 2);
                            g_ovf[p] = (int)r[k].y; g_ovf[p + 1] = (int)r[k].x;
                        }
                    }
                }
            }
            p1_bar();
        }
        TSM(tid == 0, 4);
        return;
    }

    if ((int)blockIdx.x * chunk < E) asm volatile("bar.sync 3, %0;" :: "n"(K1_THREADS) : "memory");
    const int q = lane & 3;
    const int wg = warp >> 2;
    const int n_tasks = ((N + 63) >> 6) * 2;
    const uint32_t sbase = (uint32_t)__cvta_generic_to_shared(smem);
    const uint32_t xbase = sbase + 131072;
    bool w_staged = false;
    const uint32_t mbar = sbase + K1_SMEM - 16, mbar2 = mbar + 8;
    uint32_t phase = 0;
    if (threadIdx.x == 0) { mbar_init(mbar, 1); mbar_init(mbar2, 1); }
    int t_beg = (int)(((long long)n_tasks * blockIdx.x) / gridDim.x);
    const int t_end = (int)(((long long)n_tasks * (blockIdx.x + 1)) / gridDim.x);
    while (t_beg < t_end) {
        const int tile0 = t_beg >> 1;
        const int t_stop = min(t_end, (tile0 + 2) << 1);
        if (threadIdx.x == 0) {
            const bool two = ((t_stop - 1) >> 1) > tile0;
            mbar_expect_tx(mbar, (two ? 32768u : 16384u) + (w_staged ? 0u : 65536u));
            tma_x_tile(xbase, &tm_x, tile0 * 64, mbar);
            if (!w_staged) tma_weights(sbase, &tm_wb, &tm_wv, mbar);
            if (two) tma_x_tile(xbase + 16384, &tm_x, tile0 * 64 + 64, mbar);
            if (!w_staged) {
                mbar_expect_tx(mbar2, 65536u);
                tma_weights(sbase + 65536, &tm_wa, &tm_wu, mbar2);
            }
        }
        if (!w_staged) asm volatile("bar.sync 2, %0;" :: "n"(K1_GW * 32) : "memory");
        w_staged = true;
        mbar_wait(mbar, phase);
        phase ^= 1;
        TSM(threadIdx.x == 0, 1);
        #pragma unroll 1
        for (int type = 0; type < 2; type++) {
            if (type == 1) mbar_wait(mbar2, 0);
            uint4* outp = type ? g_AU : g_T;
            for (int task = t_beg + wg; task < t_stop; task += K1_GW / 4) {
                const int tile = task >> 1, hf = task & 1;
                const uint32_t baddr = sbase + type * 65536 + hf * 16384;
                const uint64_t descb = (uint64_t)((baddr & 0x3FFFF) >> 4) | ((uint64_t)(32768 >> 4) << 16) |
                                       ((uint64_t)(1024 >> 4) << 32) | ((uint64_t)1 << 62);
                const uint32_t aaddr = xbase + (tile - tile0) * 16384;
                const uint64_t desca = (uint64_t)((aaddr & 0x3FFFF) >> 4) | ((uint64_t)1 << 16) |
                                       ((uint64_t)(1024 >> 4) << 32) | ((uint64_t)1 << 62);
                float d[64];
                asm volatile("wgmma.fence.sync.aligned;" ::: "memory");
                #pragma unroll
                for (int ks = 0; ks < 8; ks++) {
                    wgmma_m64n128k16(d, desca + (uint64_t)(((ks >> 2) * 8192 + (ks & 3) * 32) >> 4),
                                     descb + (uint64_t)(ks * (2048 >> 4)), ks > 0 ? 1 : 0);
                }
                asm volatile("wgmma.commit_group.sync.aligned;" ::: "memory");
                asm volatile("wgmma.wait_group.sync.aligned 0;" ::: "memory");
                TSM(threadIdx.x == 0 && type == 0, 13);
                const int r0 = tile * 64 + (warp & 3) * 16 + (lane >> 2);
                #pragma unroll
                for (int mm = 0; mm < 4; mm++) {
                    const int j0 = 2 * mm, j1 = 2 * mm + 1, j2 = 8 + 2 * mm, j3 = 9 + 2 * mm;
                    uint4 o0 = make_uint4(pack_bf16(d[4 * j0], d[4 * j0 + 1]), pack_bf16(d[4 * j1], d[4 * j1 + 1]),
                                          pack_bf16(d[4 * j2], d[4 * j2 + 1]), pack_bf16(d[4 * j3], d[4 * j3 + 1]));
                    uint4 o1 = make_uint4(pack_bf16(d[4 * j0 + 2], d[4 * j0 + 3]), pack_bf16(d[4 * j1 + 2], d[4 * j1 + 3]),
                                          pack_bf16(d[4 * j2 + 2], d[4 * j2 + 3]), pack_bf16(d[4 * j3 + 2], d[4 * j3 + 3]));
                    const int m = 4 * hf + mm;
                    if (r0 < N) outp[(size_t)r0 * 32 + 4 * m + q] = o0;
                    if (r0 + 8 < N) outp[(size_t)(r0 + 8) * 32 + 4 * m + q] = o1;
                }
            }
        }
        t_beg = t_stop;
        if (t_beg < t_end) asm volatile("bar.sync 2, %0;" :: "n"(K1_GW * 32) : "memory");
    }
    TSM(threadIdx.x == 0, 2);
}

__device__ __forceinline__ void edge_accum(const uint4 v, const float e, const float a[4], const float cc[4],
                                           float num[4], float den[4]) {
    float y0 = fmaf(bf_lo(v.x), -LOG2E, fmaf(e, cc[0], a[0]));
    float y1 = fmaf(bf_hi(v.x), -LOG2E, fmaf(e, cc[1], a[1]));
    float y2 = fmaf(bf_lo(v.y), -LOG2E, fmaf(e, cc[2], a[2]));
    float y3 = fmaf(bf_hi(v.y), -LOG2E, fmaf(e, cc[3], a[3]));
    float s0 = rcp_approx(1.f + ex2_approx(y0));
    float s1 = rcp_approx(1.f + ex2_approx(y1));
    float s2 = rcp_approx(1.f + ex2_approx(y2));
    float s3 = rcp_approx(1.f + ex2_approx(y3));
    den[0] += s0; den[1] += s1; den[2] += s2; den[3] += s3;
    num[0] = fmaf(s0, bf_lo(v.z), num[0]);
    num[1] = fmaf(s1, bf_hi(v.z), num[1]);
    num[2] = fmaf(s2, bf_lo(v.w), num[2]);
    num[3] = fmaf(s3, bf_hi(v.w), num[3]);
}

#define K2_THREADS 1024
#define K2_D 2
#define K2_GS 2
#define K2_RPT ((BINCAP + K2_THREADS - 1) / K2_THREADS)
#define K2_NW (K2_THREADS / 32)
#define SORT_WORDS (BINCAP + 4 * MAXNB)
#define K2_OFF_AU 0
#define K2_OFF_X (K2_OFF_AU + MAXNB * 512)
#define K2_OFF_PART (K2_OFF_X + MAXNB * 256)
#define K2_OFF_SORT (K2_OFF_PART + K2_NW * 1024)
#define K2_OFF_HIST (K2_OFF_SORT + SORT_WORDS * 4)
#define K2_OFF_OFF (K2_OFF_HIST + MAXNB * 4)
#define K2_DYN_SMEM (K2_OFF_OFF + (MAXNB + 4) * 4)

struct Grp { uint4 v[K2_GS]; };

__device__ __forceinline__ const uint4* row_ptr(const char* Tl, uint32_t rec) {
    return reinterpret_cast<const uint4*>(Tl + (size_t)((rec & 0xffffu) * 512u));
}
__device__ __forceinline__ void grp_load(Grp& g, const uint32_t* sp, const char* Tl) {
    const uint2 t = *reinterpret_cast<const uint2*>(sp);
    g.v[0] = __ldg(row_ptr(Tl, t.x));
    g.v[1] = __ldg(row_ptr(Tl, t.y));
}
__device__ __forceinline__ void grp_consume(const Grp& g, const uint32_t* sp, const float a[4], const float cc[4],
                                            float num[4], float den[4]) {
    const uint2 t = *reinterpret_cast<const uint2*>(sp);
    edge_accum(g.v[0], bf_hi(t.x), a, cc, num, den);
    edge_accum(g.v[1], bf_hi(t.y), a, cc, num, den);
}

__device__ __forceinline__ void load_a(const uint8_t* smem, int ln, int lane, float a[4]) {
    const uint2 av = *reinterpret_cast<const uint2*>(smem + K2_OFF_AU + ln * 512 + lane * 16);
    a[0] = -LOG2E * bf_lo(av.x); a[1] = -LOG2E * bf_hi(av.x); a[2] = -LOG2E * bf_lo(av.y); a[3] = -LOG2E * bf_hi(av.y);
}
__device__ __forceinline__ void write_node(const uint8_t* smem, __nv_bfloat16* out, int ln, int n,
                                           int lane, const float num[4], const float den[4]) {
    const uint2 uv = *reinterpret_cast<const uint2*>(smem + K2_OFF_AU + ln * 512 + lane * 16 + 8);
    const uint32_t* xr = reinterpret_cast<const uint32_t*>(smem + K2_OFF_X) + ln * 64 + (lane >> 2) * 8 + (lane & 3);
    const uint32_t x0 = xr[0], x1 = xr[4];
    const float u4[4] = { bf_lo(uv.x), bf_hi(uv.x), bf_lo(uv.y), bf_hi(uv.y) };
    const float x4[4] = { bf_lo(x0), bf_hi(x0), bf_lo(x1), bf_hi(x1) };
    float o[4];
    #pragma unroll
    for (int i = 0; i < 4; i++) {
        float agg = round_bf16(__fdividef(num[i], den[i] + 1e-6f));
        float z = round_bf16(u4[i] + agg);
        float rz = (z > 0.f) ? z : 0.f * z;
        o[i] = x4[i] + rz;
    }
    uint32_t* o32 = reinterpret_cast<uint32_t*>(out) + (size_t)n * 64 + (lane >> 2) * 8 + (lane & 3);
    o32[0] = pack_bf16(o[0], o[1]); o32[4] = pack_bf16(o[2], o[3]);
}

__device__ __noinline__ void slow_path(const uint8_t* smem, __nv_bfloat16* out, int node0, int nn, int ovf_n,
                                       float c0, float c1, float c2, float c3) {
    const uint32_t* s_sorted = reinterpret_cast<const uint32_t*>(smem + K2_OFF_SORT);
    const int* s_off = reinterpret_cast<const int*>(smem + K2_OFF_OFF);
    const int lane = threadIdx.x & 31, warp = threadIdx.x >> 5;
    const float cc[4] = { c0, c1, c2, c3 };
    const char* Tl = reinterpret_cast<const char*>(g_T) + lane * 16;
    for (int ln = warp; ln < nn; ln += K2_NW) {
        float a[4];
        load_a(smem, ln, lane, a);
        float num[4] = {0.f, 0.f, 0.f, 0.f}, den[4] = {0.f, 0.f, 0.f, 0.f};
        for (int i = s_off[ln]; i < s_off[ln + 1]; i++) {
            const uint32_t r = s_sorted[i];
            edge_accum(__ldg(row_ptr(Tl, r)), bf_hi(r), a, cc, num, den);
        }
        const int n = node0 + ln;
        for (int base = 0; base < ovf_n; base += 64) {
            int i2 = base + 2 * lane;
            int od = (i2 < ovf_n) ? g_ovf[i2] : -1;
            uint32_t orec = (i2 < ovf_n) ? (uint32_t)g_ovf[i2 + 1] : 0u;
            unsigned msk = __ballot_sync(0xffffffffu, od == n);
            while (msk) {
                int l = __ffs(msk) - 1; msk &= msk - 1;
                uint32_t r = __shfl_sync(0xffffffffu, orec, l);
                edge_accum(__ldg(row_ptr(Tl, r)), bf_hi(r), a, cc, num, den);
            }
        }
        write_node(smem, out, ln, n, lane, num, den);
    }
}

__global__ void __launch_bounds__(K2_THREADS, 1) k2_kernel(
    const __nv_bfloat16* __restrict__ x, const __nv_bfloat16* __restrict__ w_a, const __nv_bfloat16* __restrict__ w_u,
    const __nv_bfloat16* __restrict__ w_c, __nv_bfloat16* __restrict__ out, int N, int NB)
{
    extern __shared__ __align__(1024) uint8_t smem[];
    float4* s_part = reinterpret_cast<float4*>(smem + K2_OFF_PART);
    uint32_t* s_sorted = reinterpret_cast<uint32_t*>(smem + K2_OFF_SORT);
    int* s_hist = reinterpret_cast<int*>(smem + K2_OFF_HIST);
    int* s_off = reinterpret_cast<int*>(smem + K2_OFF_OFF);

    const int tid = threadIdx.x;
    const int lane = tid & 31, warp = tid >> 5;
    const int bin = blockIdx.x;
    const int node0 = bin * NB;
    const int nn = min(NB, N - node0);
    const uint32_t sb = (uint32_t)__cvta_generic_to_shared(smem);
    TSM(tid == 0, 5);

    const int fw = (lane >> 2) * 8 + (lane & 3);
    const uint2 wc = make_uint2(__ldg(reinterpret_cast<const uint32_t*>(w_c) + fw), __ldg(reinterpret_cast<const uint32_t*>(w_c) + fw + 4));
    s_part[warp * 64 + lane] = make_float4(0.f, 0.f, 0.f, 0.f);
    s_part[warp * 64 + 32 + lane] = make_float4(0.f, 0.f, 0.f, 0.f);
    for (int i = tid; i < nn * 16; i += K2_THREADS)
        cp_async16(sb + K2_OFF_X + i * 16, reinterpret_cast<const uint4*>(x) + (size_t)node0 * 16 + i);
    if (tid < MAXNB) s_hist[tid] = 0;
    for (int i = tid; i < SORT_WORDS; i += K2_THREADS) s_sorted[i] = (uint32_t)N;
    __syncthreads();
    asm volatile("griddepcontrol.wait;" ::: "memory");
    TSM(tid == 0, 8);
    {
        uint2 r[K2_RPT]; int rk[K2_RPT];
        const int cnt = min(g_bin_cnt[bin * CNT_STRIDE], BINCAP);
        if (tid == 64) s_off[MAXNB + 1] = g_ovf_cnt;
        #pragma unroll
        for (int i = 0; i < K2_RPT; i++) {
            int idx = i * K2_THREADS + tid;
            if (idx < cnt) r[i] = g_bins[bin * BINCAP + idx];
        }
        for (int i = tid; i < nn * 32; i += K2_THREADS)
            cp_async16(sb + K2_OFF_AU + i * 16, g_AU + (size_t)node0 * 32 + i);
        #pragma unroll
        for (int i = 0; i < K2_RPT; i++) {
            int idx = i * K2_THREADS + tid;
            if (idx < cnt) rk[i] = atomicAdd(&s_hist[r[i].y], 1);
        }
        __syncthreads();
        if (warp == 0) {
            int v[4]; int sum = 0;
            #pragma unroll
            for (int i = 0; i < 4; i++) { v[i] = (s_hist[lane * 4 + i] + K2_GS - 1) & ~(K2_GS - 1); sum += v[i]; }
            int inc = sum;
            #pragma unroll
            for (int o = 1; o < 32; o <<= 1) { int t = __shfl_up_sync(0xffffffffu, inc, o); if (lane >= o) inc += t; }
            int run = inc - sum;
            #pragma unroll
            for (int i = 0; i < 4; i++) { s_off[lane * 4 + i] = run; run += v[i]; }
            if (lane == 31) s_off[MAXNB] = run;
        }
        if (tid == 32) g_bin_cnt[bin * CNT_STRIDE] = 0;
        __syncthreads();
        #pragma unroll
        for (int i = 0; i < K2_RPT; i++) {
            int idx = i * K2_THREADS + tid;
            if (idx < cnt) s_sorted[s_off[r[i].y] + rk[i]] = r[i].x;
        }
        TSM(tid == 0, 9);
        asm volatile("cp.async.wait_all;" ::: "memory");
    }
    __syncthreads();
    TSM(tid == 0, 10);
    const float cc[4] = { -LOG2E * bf_lo(wc.x), -LOG2E * bf_hi(wc.x), -LOG2E * bf_lo(wc.y), -LOG2E * bf_hi(wc.y) };
    const int ovf_n = s_off[MAXNB + 1];

    if (ovf_n != 0) {
        slow_path(smem, out, node0, nn, ovf_n, cc[0], cc[1], cc[2], cc[3]);
        __syncthreads();
        if (tid == 0) {
            __threadfence();
            int t = atomicAdd(&g_done, 1);
            if (t == (int)gridDim.x - 1) { g_done = 0; __threadfence(); g_ovf_cnt = 0; }
        }
        return;
    }

    const char* Tl = reinterpret_cast<const char*>(g_T) + lane * 16;
    const int G = s_off[MAXNB] / K2_GS;
    int g = (G * warp) / K2_NW;
    const int g1 = (G * (warp + 1)) / K2_NW;
    int ln;
    {
        int c_lo = 0;
        #pragma unroll
        for (int i = 0; i < 4; i++) {
            int node = i * 32 + lane;
            int o = (node < nn) ? s_off[node] : 0x7fffffff;
            c_lo += __popc(__ballot_sync(0xffffffffu, o < g * K2_GS));
        }
        ln = c_lo;
    }
    bool head = ln > 0;
    if (head) ln--;
    float a[4], num[4] = {0.f, 0.f, 0.f, 0.f}, den[4] = {0.f, 0.f, 0.f, 0.f};
    int node_end;

    auto load_node = [&]() {
        load_a(smem, ln, lane, a);
        node_end = s_off[ln + 1] / K2_GS;
    };
    auto finish_node = [&]() { write_node(smem, out, ln, node0 + ln, lane, num, den); };
    auto close_node = [&]() {
        if (head) {
            s_part[warp * 64 + lane] = make_float4(num[0], num[1], num[2], num[3]);
            s_part[warp * 64 + 32 + lane] = make_float4(den[0], den[1], den[2], den[3]);
            head = false;
        } else {
            finish_node();
        }
        #pragma unroll
        for (int i = 0; i < 4; i++) { num[i] = 0.f; den[i] = 0.f; }
    };

    bool tail = false;
    if (g < g1 || warp == K2_NW - 1) {
        load_node();
        Grp b[K2_D];
        #pragma unroll
        for (int d = 0; d < K2_D; d++)
            if (g + d < g1) grp_load(b[d], s_sorted + K2_GS * (g + d), Tl);
        while (g < g1) {
            #pragma unroll
            for (int d = 0; d < K2_D; d++) {
                if (g < g1) {
                    while (g == node_end) { close_node(); ln++; load_node(); }
                    grp_consume(b[d], s_sorted + K2_GS * g, a, cc, num, den);
                    if (g + K2_D < g1) grp_load(b[d], s_sorted + K2_GS * (g + K2_D), Tl);
                    g++;
                }
            }
        }
        if (warp == K2_NW - 1) {
            while (true) { close_node(); ln++; if (ln >= nn) break; load_node(); }
        } else if (node_end == g1 || head) {
            close_node();
        } else {
            tail = true;
        }
    }
    TSM(tid == 0, 11);
    __syncthreads();
    TSM(tid == 0, 12);
    if (tail) {
        for (int w2 = warp + 1; w2 < K2_NW && (G * w2) / K2_NW < node_end; w2++) {
            const float4 pn = s_part[w2 * 64 + lane], pd = s_part[w2 * 64 + 32 + lane];
            num[0] += pn.x; num[1] += pn.y; num[2] += pn.z; num[3] += pn.w;
            den[0] += pd.x; den[1] += pd.y; den[2] += pd.z; den[3] += pd.w;
        }
        finish_node();
    }
}

extern "C" void kernel_launch(void* const* d_in, const int* in_sizes, int n_in,
                              void* d_out, int out_size) {
    const __nv_bfloat16* x      = (const __nv_bfloat16*)d_in[0];
    const __nv_bfloat16* e_attr = (const __nv_bfloat16*)d_in[1];
    const int* src = (const int*)d_in[2];
    const int* dst = (const int*)d_in[3];
    const __nv_bfloat16* w_a = (const __nv_bfloat16*)d_in[4];
    const __nv_bfloat16* w_b = (const __nv_bfloat16*)d_in[5];
    const __nv_bfloat16* w_c = (const __nv_bfloat16*)d_in[6];
    const __nv_bfloat16* w_u = (const __nv_bfloat16*)d_in[7];
    const __nv_bfloat16* w_v = (const __nv_bfloat16*)d_in[8];
    __nv_bfloat16* out = (__nv_bfloat16*)d_out;
    const int N = in_sizes[0] / D_FEAT;
    const int E = in_sizes[2];
    if (N > MAX_N || 2 * E > MAX_E || N <= 0) return;

    static int num_sms = 0;
    if (num_sms == 0) {
        int dev = 0;
        cudaGetDevice(&dev);
        cudaDeviceGetAttribute(&num_sms, cudaDevAttrMultiProcessorCount, dev);
        if (num_sms <= 0 || num_sms > MAXBINS) num_sms = 132;
        cudaFuncSetAttribute(k1_kernel, cudaFuncAttributeMaxDynamicSharedMemorySize, K1_SMEM);
        cudaFuncSetAttribute(k2_kernel, cudaFuncAttributeMaxDynamicSharedMemorySize, K2_DYN_SMEM);
    }
    typedef CUresult (*EncodeFn)(CUtensorMap*, CUtensorMapDataType, cuuint32_t, void*, const cuuint64_t*, const cuuint64_t*,
                                 const cuuint32_t*, const cuuint32_t*, CUtensorMapInterleave, CUtensorMapSwizzle,
                                 CUtensorMapL2promotion, CUtensorMapFloatOOBfill);
    static EncodeFn encode = nullptr;
    if (!encode) {
        void* fn = nullptr;
        cudaDriverEntryPointQueryResult qres;
        if (cudaGetDriverEntryPoint("cuTensorMapEncodeTiled", &fn, cudaEnableDefault, &qres) != cudaSuccess || !fn) return;
        encode = (EncodeFn)fn;
    }
    auto make_map = [&](CUtensorMap* m, const void* base, int rows, int box_rows) {
        cuuint64_t dims[2] = { D_FEAT, (cuuint64_t)rows };
        cuuint64_t strides[1] = { D_FEAT * 2 };
        cuuint32_t box[2] = { 64, (cuuint32_t)box_rows };
        cuuint32_t es[2] = { 1, 1 };
        return encode(m, CU_TENSOR_MAP_DATA_TYPE_BFLOAT16, 2, const_cast<void*>(base), dims, strides, box, es,
                      CU_TENSOR_MAP_INTERLEAVE_NONE, CU_TENSOR_MAP_SWIZZLE_128B, CU_TENSOR_MAP_L2_PROMOTION_L2_128B,
                      CU_TENSOR_MAP_FLOAT_OOB_FILL_NONE);
    };
    CUtensorMap tm_x, tm_wa, tm_wb, tm_wu, tm_wv;
    if (make_map(&tm_x, x, N, 64) != CUDA_SUCCESS || make_map(&tm_wa, w_a, D_FEAT, 128) != CUDA_SUCCESS ||
        make_map(&tm_wb, w_b, D_FEAT, 128) != CUDA_SUCCESS || make_map(&tm_wu, w_u, D_FEAT, 128) != CUDA_SUCCESS ||
        make_map(&tm_wv, w_v, D_FEAT, 128) != CUDA_SUCCESS) return;
    cudaStream_t st = cudaStreamPerThread;
    int NB = (N + num_sms - 1) / num_sms;
    if (NB > MAXNB) NB = MAXNB;
    const int nbins = (N + NB - 1) / NB;
    const uint32_t magic = (uint32_t)(((1u << 24) + NB - 1) / NB);
    const int P = num_sms;
    int chunk = (E + P - 1) / P;
    if (chunk > P1_CHUNK) chunk = P1_CHUNK;
    if (chunk < 1) chunk = 1;
    k1_kernel<<<P, K1_THREADS, K1_SMEM, st>>>(tm_x, tm_wb, tm_wv, tm_wa, tm_wu, x, e_attr, src, dst, w_b, w_v, w_a, w_u, N, E, chunk, NB, nbins, magic);

    cudaLaunchConfig_t cfg = {};
    cfg.gridDim = dim3(nbins);
    cfg.blockDim = dim3(K2_THREADS);
    cfg.dynamicSmemBytes = K2_DYN_SMEM;
    cfg.stream = st;
    cudaLaunchAttribute at[1];
    at[0].id = cudaLaunchAttributeProgrammaticStreamSerialization;
    at[0].val.programmaticStreamSerializationAllowed = 1;
    cfg.attrs = at; cfg.numAttrs = 1;
    cudaLaunchKernelEx(&cfg, k2_kernel, x, w_a, w_u, w_c, out, N, NB);
}
```

```cpp
#include <cuda_runtime.h>
#include <cuda.h>
#include <cuda_bf16.h>
#include <stdint.h>

#define D_FEAT 128
#define MAX_N 16384
#define MAX_E (1 << 20)
#define LOG2E 1.4426950408889634f

#define MAXBINS 256
#define MAXNB 128
#define BINCAP 3072
__device__ uint4 g_T[(MAX_N + 1) * 32];
#define CNT_STRIDE 1
__device__ int g_bin_cnt[MAXBINS * CNT_STRIDE];
__device__ uint2 g_bins[MAXBINS * BINCAP];
__device__ int g_ovf[MAX_E];
__device__ int g_ovf_cnt;
__device__ int g_done;

#define TSM(cond, i)
__device__ __forceinline__ float ex2_approx(float x) {
    float y; asm("ex2.approx.ftz.f32 %0, %1;" : "=f"(y) : "f"(x)); return y;
}
__device__ __forceinline__ float rcp_approx(float x) {
    float y; asm("rcp.approx.ftz.f32 %0, %1;" : "=f"(y) : "f"(x)); return y;
}
__device__ __forceinline__ uint32_t pack_bf16(float lo, float hi) {
    __nv_bfloat162 t = __floats2bfloat162_rn(lo, hi);
    return *reinterpret_cast<uint32_t*>(&t);
}
__device__ __forceinline__ float bf_lo(uint32_t v) { return __uint_as_float(v << 16); }
__device__ __forceinline__ float bf_hi(uint32_t v) { return __uint_as_float(v & 0xffff0000u); }
__device__ __forceinline__ float round_bf16(float x) { return __bfloat162float(__float2bfloat16_rn(x)); }

__device__ __forceinline__ void mma_bf16(float c[4], uint32_t a0, uint32_t a1, uint32_t a2, uint32_t a3,
                                         uint32_t b0, uint32_t b1) {
    asm volatile("mma.sync.aligned.m16n8k16.row.col.f32.bf16.bf16.f32 "
                 "{%0,%1,%2,%3}, {%4,%5,%6,%7}, {%8,%9}, {%0,%1,%2,%3};"
                 : "+f"(c[0]), "+f"(c[1]), "+f"(c[2]), "+f"(c[3])
                 : "r"(a0), "r"(a1), "r"(a2), "r"(a3), "r"(b0), "r"(b1));
}
__device__ __forceinline__ void ldmatrix_x4_trans(uint32_t& r0, uint32_t& r1, uint32_t& r2, uint32_t& r3, uint32_t addr) {
    asm volatile("ldmatrix.sync.aligned.m8n8.x4.trans.shared.b16 {%0,%1,%2,%3}, [%4];"
                 : "=r"(r0), "=r"(r1), "=r"(r2), "=r"(r3) : "r"(addr));
}

__device__ __forceinline__ void cp_async16(uint32_t saddr, const void* g) {
    asm volatile("cp.async.cg.shared.global [%0], [%1], 16;" :: "r"(saddr), "l"(g) : "memory");
}
__device__ __forceinline__ void cp_async16_zfill(uint32_t saddr, const void* g, int src_size) {
    asm volatile("cp.async.cg.shared.global [%0], [%1], 16, %2;" :: "r"(saddr), "l"(g), "r"(src_size) : "memory");
}
__device__ __forceinline__ void stage_weight(uint32_t sdst, const __nv_bfloat16* w, int mtx, int tid, int nthreads) {
    const uint4* W = reinterpret_cast<const uint4*>(w);
    for (int u = tid; u < 2048; u += nthreads) {
        int k = u >> 4, c16 = u & 15;
        int kg = k >> 3, rr = k & 7;
        int h = mtx * 2 + (c16 >> 3);
        cp_async16(sdst + kg * 4096 + h * 1024 + rr * 128 + (((c16 & 7) ^ rr) << 4), W + u);
    }
}
__device__ __forceinline__ void stage_x_tile(uint32_t sdst, const __nv_bfloat16* x, int row0, int N, int tid, int nthreads) {
    const uint4* X = reinterpret_cast<const uint4*>(x);
    for (int u = tid; u < 1024; u += nthreads) {
        int r = u >> 4, c16 = u & 15;
        int gr = row0 + r;
        bool ok = gr < N;
        cp_async16_zfill(sdst + (c16 >> 3) * 8192 + r * 128 + (((c16 & 7) ^ (r & 7)) << 4),
                         X + (size_t)(ok ? gr : 0) * 16 + c16, ok ? 16 : 0);
    }
}

__device__ __forceinline__ void mbar_init(uint32_t bar, int cnt) {
    asm volatile("mbarrier.init.shared::cta.b64 [%0], %1;" :: "r"(bar), "r"(cnt) : "memory");
    asm volatile("fence.mbarrier_init.release.cluster;" ::: "memory");
    asm volatile("fence.proxy.async.shared::cta;" ::: "memory");
}
__device__ __forceinline__ void mbar_expect_tx(uint32_t bar, uint32_t bytes) {
    asm volatile("mbarrier.arrive.expect_tx.shared::cta.b64 _, [%0], %1;" :: "r"(bar), "r"(bytes) : "memory");
}
__device__ __forceinline__ void mbar_wait(uint32_t bar, uint32_t parity) {
    asm volatile("{\n.reg .pred p;\nWAIT_LOOP:\n"
                 "mbarrier.try_wait.parity.shared::cta.b64 p, [%0], %1;\n"
                 "@p bra WAIT_DONE;\nbra WAIT_LOOP;\nWAIT_DONE:\n}" :: "r"(bar), "r"(parity) : "memory");
}
__device__ __forceinline__ void tma_2d(uint32_t sdst, const CUtensorMap* tm, int c0, int c1, uint32_t bar) {
    asm volatile("cp.async.bulk.tensor.2d.shared::cluster.global.mbarrier::complete_tx::bytes [%0], [%1, {%3, %4}], [%2];"
                 :: "r"(sdst), "l"(reinterpret_cast<uint64_t>(tm)), "r"(bar), "r"(c0), "r"(c1) : "memory");
}
__device__ __forceinline__ void tma_weights(uint32_t sdst, const CUtensorMap* m0, const CUtensorMap* m1, uint32_t bar) {
    tma_2d(sdst, m0, 0, 0, bar);
    tma_2d(sdst + 16384, m0, 64, 0, bar);
    tma_2d(sdst + 32768, m1, 0, 0, bar);
    tma_2d(sdst + 49152, m1, 64, 0, bar);
}
__device__ __forceinline__ void tma_x_tile(uint32_t sdst, const CUtensorMap* mx, int row0, uint32_t bar) {
    tma_2d(sdst, mx, 0, row0, bar);
    tma_2d(sdst + 8192, mx, 64, row0, bar);
}

__device__ __forceinline__ void wgmma_m64n128k16(float d[64], uint64_t desc_a, uint64_t desc_b, int scale_d) {
    asm volatile("{\n.reg .pred p;\nsetp.ne.b32 p, %66, 0;\n"
                 "wgmma.mma_async.sync.aligned.m64n128k16.f32.bf16.bf16 {%0,%1,%2,%3,%4,%5,%6,%7,%8,%9,%10,%11,%12,%13,%14,%15,%16,%17,%18,%19,%20,%21,%22,%23,%24,%25,%26,%27,%28,%29,%30,%31,%32,%33,%34,%35,%36,%37,%38,%39,%40,%41,%42,%43,%44,%45,%46,%47,%48,%49,%50,%51,%52,%53,%54,%55,%56,%57,%58,%59,%60,%61,%62,%63}, %64, %65, p, 1, 1, 0, 1;\n}"
                 : "+f"(d[0]),"+f"(d[1]),"+f"(d[2]),"+f"(d[3]),"+f"(d[4]),"+f"(d[5]),"+f"(d[6]),"+f"(d[7]),"+f"(d[8]),"+f"(d[9]),"+f"(d[10]),"+f"(d[11]),"+f"(d[12]),"+f"(d[13]),"+f"(d[14]),"+f"(d[15]),"+f"(d[16]),"+f"(d[17]),"+f"(d[18]),"+f"(d[19]),"+f"(d[20]),"+f"(d[21]),"+f"(d[22]),"+f"(d[23]),"+f"(d[24]),"+f"(d[25]),"+f"(d[26]),"+f"(d[27]),"+f"(d[28]),"+f"(d[29]),"+f"(d[30]),"+f"(d[31]),"+f"(d[32]),"+f"(d[33]),"+f"(d[34]),"+f"(d[35]),"+f"(d[36]),"+f"(d[37]),"+f"(d[38]),"+f"(d[39]),"+f"(d[40]),"+f"(d[41]),"+f"(d[42]),"+f"(d[43]),"+f"(d[44]),"+f"(d[45]),"+f"(d[46]),"+f"(d[47]),"+f"(d[48]),"+f"(d[49]),"+f"(d[50]),"+f"(d[51]),"+f"(d[52]),"+f"(d[53]),"+f"(d[54]),"+f"(d[55]),"+f"(d[56]),"+f"(d[57]),"+f"(d[58]),"+f"(d[59]),"+f"(d[60]),"+f"(d[61]),"+f"(d[62]),"+f"(d[63])
                 : "l"(desc_a), "l"(desc_b), "r"(scale_d));
}

__device__ __forceinline__ void wgmma_m64n64k16(float d[32], uint64_t desc_a, uint64_t desc_b, int scale_d) {
    asm volatile("{\n.reg .pred p;\nsetp.ne.b32 p, %34, 0;\n"
                 "wgmma.mma_async.sync.aligned.m64n64k16.f32.bf16.bf16 {%0,%1,%2,%3,%4,%5,%6,%7,%8,%9,%10,%11,%12,%13,%14,%15,%16,%17,%18,%19,%20,%21,%22,%23,%24,%25,%26,%27,%28,%29,%30,%31}, %32, %33, p, 1, 1, 0, 1;\n}"
                 : "+f"(d[0]),"+f"(d[1]),"+f"(d[2]),"+f"(d[3]),"+f"(d[4]),"+f"(d[5]),"+f"(d[6]),"+f"(d[7]),"+f"(d[8]),"+f"(d[9]),"+f"(d[10]),"+f"(d[11]),"+f"(d[12]),"+f"(d[13]),"+f"(d[14]),"+f"(d[15]),"+f"(d[16]),"+f"(d[17]),"+f"(d[18]),"+f"(d[19]),"+f"(d[20]),"+f"(d[21]),"+f"(d[22]),"+f"(d[23]),"+f"(d[24]),"+f"(d[25]),"+f"(d[26]),"+f"(d[27]),"+f"(d[28]),"+f"(d[29]),"+f"(d[30]),"+f"(d[31])
                 : "l"(desc_a), "l"(desc_b), "r"(scale_d));
}

#define K1_GW 12
#define P1_FIRST
#define P1_T 256
#define K1_THREADS (K1_GW * 32 + P1_T)
#define P1_EPT ((2560 + P1_T - 1) / P1_T)
#define P1_CHUNK (P1_T * P1_EPT)
#define K1_WBYTES (65536 + 2 * 16384)
#define K1_SMEM (K1_WBYTES + 3 * MAXBINS * 4 + P1_CHUNK * 8 + 16)

__device__ __forceinline__ void p1_bar() { asm volatile("bar.sync 1, %0;" :: "n"(P1_T) : "memory"); }

__global__ void __launch_bounds__(K1_THREADS, 1) k1_kernel(
    const __grid_constant__ CUtensorMap tm_x, const __grid_constant__ CUtensorMap tm_wb, const __grid_constant__ CUtensorMap tm_wv,
    const __nv_bfloat16* __restrict__ x, const __nv_bfloat16* __restrict__ e_attr,
    const int* __restrict__ src, const int* __restrict__ dst,
    const __nv_bfloat16* __restrict__ w_b, const __nv_bfloat16* __restrict__ w_v,
    const __nv_bfloat16* __restrict__ w_a, const __nv_bfloat16* __restrict__ w_u,
    int N, int E, int chunk, int NB, int nbins, uint32_t magic)
{
    extern __shared__ __align__(1024) uint8_t smem[];
    asm volatile("griddepcontrol.launch_dependents;");
    TSM(threadIdx.x == 0, 0);

    const int warp = threadIdx.x >> 5, lane = threadIdx.x & 31;

    if (warp >= K1_GW) {
        const int tid = threadIdx.x - K1_GW * 32;
        if (blockIdx.x == 0 && tid < 32)
            g_T[(size_t)N * 32 + tid] = make_uint4(0xff80ff80u, 0xff80ff80u, 0u, 0u);
        int* hist = reinterpret_cast<int*>(smem + K1_WBYTES);
        int* loff = hist + MAXBINS;
        int* gbase = loff + MAXBINS;
        uint2* sorted = reinterpret_cast<uint2*>(smem + K1_WBYTES + 3 * MAXBINS * 4);
        for (int beg = blockIdx.x * chunk; beg < E; beg += gridDim.x * chunk) {
            const int end = min(E, beg + chunk);
            int d[P1_EPT]; uint32_t rec[P1_EPT]; int rk[P1_EPT]; int bn[P1_EPT];
            #pragma unroll
            for (int i = 0; i < P1_EPT; i++) {
                int e = beg + i * P1_T + tid;
                d[i] = -1;
                if (e < end) {
                    d[i] = __ldg(dst + e);
                    uint32_t s = (uint32_t)__ldg(src + e);
                    uint32_t ev = (uint32_t)__ldg(reinterpret_cast<const unsigned short*>(e_attr) + e);
                    rec[i] = (ev << 16) | s;
                }
            }
            if (beg == (int)blockIdx.x * chunk) asm volatile("bar.arrive 3, %0;" :: "n"(K1_THREADS) : "memory");
            if (tid < MAXBINS) hist[tid] = 0;
            TSM(tid == 0 && d[P1_EPT - 2] != -5 && rec[P1_EPT - 2] != 0xfffffff5u, 14);
            p1_bar();
            #pragma unroll
            for (int i = 0; i < P1_EPT; i++) {
                if (d[i] >= 0) {
                    bn[i] = (int)(((uint64_t)(uint32_t)d[i] * magic) >> 24);
                    rk[i] = atomicAdd(&hist[bn[i]], 1);
                }
            }
            p1_bar();
            TSM(tid == 0, 3);
            {
                int h = (tid < MAXBINS) ? hist[tid] : 0;
                if (tid < nbins && h > 0) gbase[tid] = atomicAdd(&g_bin_cnt[tid * CNT_STRIDE], h);
                if (tid < 32) {
                    int v[8]; int sum = 0;
                    #pragma unroll
                    for (int i = 0; i < 8; i++) { v[i] = hist[lane * 8 + i]; sum += v[i]; }
                    int inc = sum;
                    #pragma unroll
                    for (int o = 1; o < 32; o <<= 1) { int t = __shfl_up_sync(0xffffffffu, inc, o); if (lane >= o) inc += t; }
                    int run = inc - sum;
                    #pragma unroll
                    for (int i = 0; i < 8; i++) { loff[lane * 8 + i] = run; run += v[i]; }
                }
            }
            p1_bar();
            TSM(tid == 0, 6);
            #pragma unroll
            for (int i = 0; i < P1_EPT; i++) {
                if (d[i] >= 0) sorted[loff[bn[i]] + rk[i]] = make_uint2(rec[i], (uint32_t)d[i]);
            }
            p1_bar();
            TSM(tid == 0, 7);
            const int cnt = end - beg;
            {
                uint2 r[P1_EPT]; int b[P1_EPT], pos[P1_EPT];
                #pragma unroll
                for (int k = 0; k < P1_EPT; k++) {
                    const int i = k * P1_T + tid;
                    r[k] = sorted[min(i, P1_CHUNK - 1)];
                }
                #pragma unroll
                for (int k = 0; k < P1_EPT; k++) {
                    const int i = k * P1_T + tid;
                    b[k] = (i < cnt) ? (int)(((uint64_t)r[k].y * magic) >> 24) : 0;
                    pos[k] = gbase[b[k]] + (i - loff[b[k]]);
                }
                #pragma unroll
                for (int k = 0; k < P1_EPT; k++) {
                    const int i = k * P1_T + tid;
                    if (i < cnt) {
                        if (pos[k] < BINCAP) {
                            g_bins[b[k] * BINCAP + pos[k]] = make_uint2(r[k].x, r[k].y - (uint32_t)(b[k] * NB));
                        } else {
                            int p = atomicAdd(&g_ovf_cnt, 2);
                            g_ovf[p] = (int)r[k].y; g_ovf[p + 1] = (int)r[k].x;
                        }
                    }
                }
            }
            p1_bar();
        }
        TSM(tid == 0, 4);
        return;
    }

    if ((int)blockIdx.x * chunk < E) asm volatile("bar.sync 3, %0;" :: "n"(K1_THREADS) : "memory");
    if (blockIdx.x < 4 && threadIdx.x < 128) {
        const char* pw = reinterpret_cast<const char*>((blockIdx.x & 2) ? w_u : w_a) + (blockIdx.x & 1) * 16384 + threadIdx.x * 128;
        asm volatile("prefetch.global.L2 [%0];" :: "l"(pw));
    }
    const int q = lane & 3;
    const int wg = warp >> 2;
    const int n_tasks = ((N + 63) >> 6) * 2;
    const uint32_t sbase = (uint32_t)__cvta_generic_to_shared(smem);
    const uint32_t xbase = sbase + 65536;
    bool w_staged = false;
    const uint32_t mbar = sbase + K1_SMEM - 16;
    uint32_t phase = 0;
    if (threadIdx.x == 0) mbar_init(mbar, 1);
    int t_beg = (int)(((long long)n_tasks * blockIdx.x) / gridDim.x);
    const int t_end = (int)(((long long)n_tasks * (blockIdx.x + 1)) / gridDim.x);
    while (t_beg < t_end) {
        const int tile0 = t_beg >> 1;
        const int t_stop = min(t_end, (tile0 + 2) << 1);
        if (threadIdx.x == 0) {
            const bool two = ((t_stop - 1) >> 1) > tile0;
            mbar_expect_tx(mbar, (two ? 32768u : 16384u) + (w_staged ? 0u : 65536u));
            tma_x_tile(xbase, &tm_x, tile0 * 64, mbar);
            if (!w_staged) tma_weights(sbase, &tm_wb, &tm_wv, mbar);
            if (two) tma_x_tile(xbase + 16384, &tm_x, tile0 * 64 + 64, mbar);
        }
        if (!w_staged) asm volatile("bar.sync 2, %0;" :: "n"(K1_GW * 32) : "memory");
        w_staged = true;
        mbar_wait(mbar, phase);
        phase ^= 1;
        TSM(threadIdx.x == 0, 1);
        for (int task = t_beg + wg; task < t_stop; task += K1_GW / 4) {
            const int tile = task >> 1, hf = task & 1;
            const uint32_t baddr = sbase + hf * 16384;
            const uint64_t descb = (uint64_t)((baddr & 0x3FFFF) >> 4) | ((uint64_t)(32768 >> 4) << 16) |
                                   ((uint64_t)(1024 >> 4) << 32) | ((uint64_t)1 << 62);
            const uint32_t aaddr = xbase + (tile - tile0) * 16384;
            const uint64_t desca = (uint64_t)((aaddr & 0x3FFFF) >> 4) | ((uint64_t)1 << 16) |
                                   ((uint64_t)(1024 >> 4) << 32) | ((uint64_t)1 << 62);
            float d[64];
            asm volatile("wgmma.fence.sync.aligned;" ::: "memory");
            #pragma unroll
            for (int ks = 0; ks < 8; ks++) {
                wgmma_m64n128k16(d, desca + (uint64_t)(((ks >> 2) * 8192 + (ks & 3) * 32) >> 4),
                                 descb + (uint64_t)(ks * (2048 >> 4)), ks > 0 ? 1 : 0);
            }
            asm volatile("wgmma.commit_group.sync.aligned;" ::: "memory");
            asm volatile("wgmma.wait_group.sync.aligned 0;" ::: "memory");
            TSM(threadIdx.x == 0, 13);
            const int r0 = tile * 64 + (warp & 3) * 16 + (lane >> 2);
            #pragma unroll
            for (int mm = 0; mm < 4; mm++) {
                const int j0 = 2 * mm, j1 = 2 * mm + 1, j2 = 8 + 2 * mm, j3 = 9 + 2 * mm;
                uint4 o0 = make_uint4(pack_bf16(d[4 * j0], d[4 * j0 + 1]), pack_bf16(d[4 * j1], d[4 * j1 + 1]),
                                      pack_bf16(d[4 * j2], d[4 * j2 + 1]), pack_bf16(d[4 * j3], d[4 * j3 + 1]));
                uint4 o1 = make_uint4(pack_bf16(d[4 * j0 + 2], d[4 * j0 + 3]), pack_bf16(d[4 * j1 + 2], d[4 * j1 + 3]),
                                      pack_bf16(d[4 * j2 + 2], d[4 * j2 + 3]), pack_bf16(d[4 * j3 + 2], d[4 * j3 + 3]));
                const int m = 4 * hf + mm;
                if (r0 < N) g_T[(size_t)r0 * 32 + 4 * m + q] = o0;
                if (r0 + 8 < N) g_T[(size_t)(r0 + 8) * 32 + 4 * m + q] = o1;
            }
        }
        t_beg = t_stop;
        if (t_beg < t_end) asm volatile("bar.sync 2, %0;" :: "n"(K1_GW * 32) : "memory");
    }
    TSM(threadIdx.x == 0, 2);
}

__device__ __forceinline__ void edge_accum(const uint4 v, const float e, const float a[4], const float cc[4],
                                           float num[4], float den[4]) {
    float y0 = fmaf(bf_lo(v.x), -LOG2E, fmaf(e, cc[0], a[0]));
    float y1 = fmaf(bf_hi(v.x), -LOG2E, fmaf(e, cc[1], a[1]));
    float y2 = fmaf(bf_lo(v.y), -LOG2E, fmaf(e, cc[2], a[2]));
    float y3 = fmaf(bf_hi(v.y), -LOG2E, fmaf(e, cc[3], a[3]));
    float d0 = 1.f + ex2_approx(fminf(y0, 63.f)), d1 = 1.f + ex2_approx(fminf(y1, 63.f));
    float d2 = 1.f + ex2_approx(fminf(y2, 63.f)), d3 = 1.f + ex2_approx(fminf(y3, 63.f));
    float r01 = rcp_approx(d0 * d1), r23 = rcp_approx(d2 * d3);
    float s0 = r01 * d1, s1 = r01 * d0, s2 = r23 * d3, s3 = r23 * d2;
    den[0] += s0; den[1] += s1; den[2] += s2; den[3] += s3;
    num[0] = fmaf(s0, bf_lo(v.z), num[0]);
    num[1] = fmaf(s1, bf_hi(v.z), num[1]);
    num[2] = fmaf(s2, bf_lo(v.w), num[2]);
    num[3] = fmaf(s3, bf_hi(v.w), num[3]);
}

#define K2_THREADS 1024
#define K2_D 2
#define K2_GS 2
#define K2_RPT ((BINCAP + K2_THREADS - 1) / K2_THREADS)
#define K2_NW (K2_THREADS / 32)
#define SORT_WORDS (BINCAP + 4 * MAXNB)
#define K2_OFF_W 0
#define K2_OFF_X 65536
#define K2_OFF_A (K2_OFF_X + 32768)
#define K2_OFF_U (K2_OFF_A + MAXNB * 256)
#define K2_OFF_PART (K2_OFF_U + MAXNB * 256)
#define K2_OFF_SORT (K2_OFF_PART + K2_NW * 1024)
#define K2_OFF_HIST (K2_OFF_SORT + SORT_WORDS * 4)
#define K2_OFF_OFF (K2_OFF_HIST + MAXNB * 4)
#define K2_OFF_MBAR (K2_OFF_OFF + (MAXNB + 4) * 4)
#define K2_DYN_SMEM (K2_OFF_MBAR + 16)
#define K2_ST (K2_THREADS - 512)
#define K2_SRPT ((BINCAP + K2_ST - 1) / K2_ST)

struct Grp { uint4 v[K2_GS]; };

__device__ __forceinline__ const uint4* row_ptr(const char* Tl, uint32_t rec) {
    return reinterpret_cast<const uint4*>(Tl + (size_t)((rec & 0xffffu) * 512u));
}
__device__ __forceinline__ void grp_load(Grp& g, const uint32_t* sp, const char* Tl) {
    const uint2 t = *reinterpret_cast<const uint2*>(sp);
    g.v[0] = __ldg(row_ptr(Tl, t.x));
    g.v[1] = __ldg(row_ptr(Tl, t.y));
}
__device__ __forceinline__ void grp_consume(const Grp& g, const uint32_t* sp, const float a[4], const float cc[4],
                                            float num[4], float den[4]) {
    const uint2 t = *reinterpret_cast<const uint2*>(sp);
    edge_accum(g.v[0], bf_hi(t.x), a, cc, num, den);
    edge_accum(g.v[1], bf_hi(t.y), a, cc, num, den);
}

__device__ __forceinline__ void load_a(const uint8_t* smem, int ln, int lane, float a[4]) {
    const uint2 av = reinterpret_cast<const uint2*>(smem + K2_OFF_A)[ln * 32 + (lane ^ ((ln & 3) << 2))];
    a[0] = -LOG2E * bf_lo(av.x); a[1] = -LOG2E * bf_hi(av.x); a[2] = -LOG2E * bf_lo(av.y); a[3] = -LOG2E * bf_hi(av.y);
}
__device__ __forceinline__ void write_node(const uint8_t* smem, __nv_bfloat16* out, int ln, int n,
                                           int lane, const float num[4], const float den[4]) {
    const uint2 uv = reinterpret_cast<const uint2*>(smem + K2_OFF_U)[ln * 32 + (lane ^ ((ln & 3) << 2))];
    const int r = ln & 63, c16 = (lane >> 2) * 2;
    const uint8_t* xr = smem + K2_OFF_X + (ln >> 6) * 16384 + (c16 >> 3) * 8192 + r * 128 + (lane & 3) * 4;
    const uint32_t x0 = *reinterpret_cast<const uint32_t*>(xr + (((c16 & 7) ^ (r & 7)) << 4));
    const uint32_t x1 = *reinterpret_cast<const uint32_t*>(xr + ((((c16 + 1) & 7) ^ (r & 7)) << 4));
    const float u4[4] = { bf_lo(uv.x), bf_hi(uv.x), bf_lo(uv.y), bf_hi(uv.y) };
    const float x4[4] = { bf_lo(x0), bf_hi(x0), bf_lo(x1), bf_hi(x1) };
    float o[4];
    #pragma unroll
    for (int i = 0; i < 4; i++) {
        float agg = round_bf16(__fdividef(num[i], den[i] + 1e-6f));
        float z = round_bf16(u4[i] + agg);
        float rz = (z > 0.f) ? z : 0.f * z;
        o[i] = x4[i] + rz;
    }
    uint32_t* o32 = reinterpret_cast<uint32_t*>(out) + (size_t)n * 64 + (lane >> 2) * 8 + (lane & 3);
    o32[0] = pack_bf16(o[0], o[1]); o32[4] = pack_bf16(o[2], o[3]);
}

__device__ __noinline__ void slow_path(const uint8_t* smem, __nv_bfloat16* out, int node0, int nn, int ovf_n,
                                       float c0, float c1, float c2, float c3) {
    const uint32_t* s_sorted = reinterpret_cast<const uint32_t*>(smem + K2_OFF_SORT);
    const int* s_off = reinterpret_cast<const int*>(smem + K2_OFF_OFF);
    const int lane = threadIdx.x & 31, warp = threadIdx.x >> 5;
    const float cc[4] = { c0, c1, c2, c3 };
    const char* Tl = reinterpret_cast<const char*>(g_T) + lane * 16;
    for (int ln = warp; ln < nn; ln += K2_NW) {
        float a[4];
        load_a(smem, ln, lane, a);
        float num[4] = {0.f, 0.f, 0.f, 0.f}, den[4] = {0.f, 0.f, 0.f, 0.f};
        for (int i = s_off[ln]; i < s_off[ln + 1]; i++) {
            const uint32_t r = s_sorted[i];
            edge_accum(__ldg(row_ptr(Tl, r)), bf_hi(r), a, cc, num, den);
        }
        const int n = node0 + ln;
        for (int base = 0; base < ovf_n; base += 64) {
            int i2 = base + 2 * lane;
            int od = (i2 < ovf_n) ? g_ovf[i2] : -1;
            uint32_t orec = (i2 < ovf_n) ? (uint32_t)g_ovf[i2 + 1] : 0u;
            unsigned msk = __ballot_sync(0xffffffffu, od == n);
            while (msk) {
                int l = __ffs(msk) - 1; msk &= msk - 1;
                uint32_t r = __shfl_sync(0xffffffffu, orec, l);
                edge_accum(__ldg(row_ptr(Tl, r)), bf_hi(r), a, cc, num, den);
            }
        }
        write_node(smem, out, ln, n, lane, num, den);
    }
}

__global__ void __launch_bounds__(K2_THREADS, 1) k2_kernel(
    const __grid_constant__ CUtensorMap tm_x, const __grid_constant__ CUtensorMap tm_wa, const __grid_constant__ CUtensorMap tm_wu,
    const __nv_bfloat16* __restrict__ w_c, __nv_bfloat16* __restrict__ out, int N, int NB)
{
    extern __shared__ __align__(1024) uint8_t smem[];
    float4* s_part = reinterpret_cast<float4*>(smem + K2_OFF_PART);
    uint32_t* s_sorted = reinterpret_cast<uint32_t*>(smem + K2_OFF_SORT);
    int* s_hist = reinterpret_cast<int*>(smem + K2_OFF_HIST);
    int* s_off = reinterpret_cast<int*>(smem + K2_OFF_OFF);

    const int tid = threadIdx.x;
    const int lane = tid & 31, warp = tid >> 5;
    const int bin = blockIdx.x;
    const int node0 = bin * NB;
    const int nn = min(NB, N - node0);
    const uint32_t sb = (uint32_t)__cvta_generic_to_shared(smem);
    TSM(tid == 0, 5);

    const int fw = (lane >> 2) * 8 + (lane & 3);
    const uint2 wc = make_uint2(__ldg(reinterpret_cast<const uint32_t*>(w_c) + fw), __ldg(reinterpret_cast<const uint32_t*>(w_c) + fw + 4));
    s_part[warp * 64 + lane] = make_float4(0.f, 0.f, 0.f, 0.f);
    s_part[warp * 64 + 32 + lane] = make_float4(0.f, 0.f, 0.f, 0.f);
    if (warp < 16) {
        const uint32_t mbar = sb + K2_OFF_MBAR;
        if (tid == 0) {
            mbar_init(mbar, 1);
            mbar_expect_tx(mbar, (nn > 64 ? 32768u : 16384u) + 65536u);
            tma_x_tile(sb + K2_OFF_X, &tm_x, node0, mbar);
            tma_weights(sb + K2_OFF_W, &tm_wa, &tm_wu, mbar);
            if (nn > 64) tma_x_tile(sb + K2_OFF_X + 16384, &tm_x, node0 + 64, mbar);
        }
        asm volatile("bar.sync 2, 512;" ::: "memory");
        mbar_wait(mbar, 0);
        const int wg = warp >> 2, tile = wg >> 1, mtx = wg & 1;
        if (tile * 64 < nn) {
            const uint32_t aaddr = sb + K2_OFF_X + tile * 16384;
            const uint64_t desca = (uint64_t)((aaddr & 0x3FFFF) >> 4) | ((uint64_t)1 << 16) |
                                   ((uint64_t)(1024 >> 4) << 32) | ((uint64_t)1 << 62);
            uint2* dst = reinterpret_cast<uint2*>(smem + (mtx ? K2_OFF_U : K2_OFF_A));
            const int r0 = tile * 64 + (warp & 3) * 16 + (lane >> 2);
            const int sw = (r0 & 3) << 2;
            #pragma unroll 1
            for (int hf = 0; hf < 2; hf++) {
                const uint32_t baddr = sb + K2_OFF_W + (mtx * 2 + hf) * 16384;
                const uint64_t descb = (uint64_t)((baddr & 0x3FFFF) >> 4) | ((uint64_t)(32768 >> 4) << 16) |
                                       ((uint64_t)(1024 >> 4) << 32) | ((uint64_t)1 << 62);
                float d[32];
                asm volatile("wgmma.fence.sync.aligned;" ::: "memory");
                #pragma unroll
                for (int ks = 0; ks < 8; ks++) {
                    wgmma_m64n64k16(d, desca + (uint64_t)(((ks >> 2) * 8192 + (ks & 3) * 32) >> 4),
                                    descb + (uint64_t)(ks * (2048 >> 4)), ks > 0 ? 1 : 0);
                }
                asm volatile("wgmma.commit_group.sync.aligned;" ::: "memory");
                asm volatile("wgmma.wait_group.sync.aligned 0;" ::: "memory");
                TSM(tid == 0 && hf == 0, 15);
                #pragma unroll
                for (int mm = 0; mm < 4; mm++) {
                    const int j0 = 2 * mm, j1 = 2 * mm + 1;
                    const int slot = (4 * (4 * hf + mm) + (lane & 3)) ^ sw;
                    dst[r0 * 32 + slot] = make_uint2(pack_bf16(d[4 * j0], d[4 * j0 + 1]), pack_bf16(d[4 * j1], d[4 * j1 + 1]));
                    dst[(r0 + 8) * 32 + slot] = make_uint2(pack_bf16(d[4 * j0 + 2], d[4 * j0 + 3]), pack_bf16(d[4 * j1 + 2], d[4 * j1 + 3]));
                }
            }
        }
        asm volatile("griddepcontrol.wait;" ::: "memory");
    } else {
        const int st = tid - 512;
        if (st < MAXNB) s_hist[st] = 0;
        for (int i = st; i < SORT_WORDS; i += K2_ST) s_sorted[i] = (uint32_t)N;
        asm volatile("bar.sync 1, %0;" :: "n"(K2_ST) : "memory");
        asm volatile("griddepcontrol.wait;" ::: "memory");
        TSM(st == 0, 8);
        uint2 r[K2_SRPT]; int rk[K2_SRPT];
        const int cnt = min(g_bin_cnt[bin * CNT_STRIDE], BINCAP);
        if (st == 64) s_off[MAXNB + 1] = g_ovf_cnt;
        #pragma unroll
        for (int i = 0; i < K2_SRPT; i++) {
            int idx = i * K2_ST + st;
            if (idx < cnt) r[i] = g_bins[bin * BINCAP + idx];
        }
        #pragma unroll
        for (int i = 0; i < K2_SRPT; i++) {
            int idx = i * K2_ST + st;
            if (idx < cnt) rk[i] = atomicAdd(&s_hist[r[i].y], 1);
        }
        asm volatile("bar.sync 1, %0;" :: "n"(K2_ST) : "memory");
        if (warp == 16) {
            int v[4]; int sum = 0;
            #pragma unroll
            for (int i = 0; i < 4; i++) { v[i] = (s_hist[lane * 4 + i] + K2_GS - 1) & ~(K2_GS - 1); sum += v[i]; }
            int inc = sum;
            #pragma unroll
            for (int o = 1; o < 32; o <<= 1) { int t = __shfl_up_sync(0xffffffffu, inc, o); if (lane >= o) inc += t; }
            int run = inc - sum;
            #pragma unroll
            for (int i = 0; i < 4; i++) { s_off[lane * 4 + i] = run; run += v[i]; }
            if (lane == 31) s_off[MAXNB] = run;
        }
        if (st == 32) g_bin_cnt[bin * CNT_STRIDE] = 0;
        asm volatile("bar.sync 1, %0;" :: "n"(K2_ST) : "memory");
        #pragma unroll
        for (int i = 0; i < K2_SRPT; i++) {
            int idx = i * K2_ST + st;
            if (idx < cnt) s_sorted[s_off[r[i].y] + rk[i]] = r[i].x;
        }
        TSM(st == 0, 9);
    }
    __syncthreads();
    TSM(tid == 0, 10);
    const float cc[4] = { -LOG2E * bf_lo(wc.x), -LOG2E * bf_hi(wc.x), -LOG2E * bf_lo(wc.y), -LOG2E * bf_hi(wc.y) };
    const int ovf_n = s_off[MAXNB + 1];

    if (ovf_n != 0) {
        slow_path(smem, out, node0, nn, ovf_n, cc[0], cc[1], cc[2], cc[3]);
        __syncthreads();
        if (tid == 0) {
            __threadfence();
            int t = atomicAdd(&g_done, 1);
            if (t == (int)gridDim.x - 1) { g_done = 0; __threadfence(); g_ovf_cnt = 0; }
        }
        return;
    }

    const char* Tl = reinterpret_cast<const char*>(g_T) + lane * 16;
    const int G = s_off[MAXNB] / K2_GS;
    int g = (G * warp) / K2_NW;
    const int g1 = (G * (warp + 1)) / K2_NW;
    int ln;
    {
        int c_lo = 0;
        #pragma unroll
        for (int i = 0; i < 4; i++) {
            int node = i * 32 + lane;
            int o = (node < nn) ? s_off[node] : 0x7fffffff;
            c_lo += __popc(__ballot_sync(0xffffffffu, o < g * K2_GS));
        }
        ln = c_lo;
    }
    bool head = ln > 0;
    if (head) ln--;
    float a[4], num[4] = {0.f, 0.f, 0.f, 0.f}, den[4] = {0.f, 0.f, 0.f, 0.f};
    int node_end;

    auto load_node = [&]() {
        load_a(smem, ln, lane, a);
        node_end = s_off[ln + 1] / K2_GS;
    };
    auto finish_node = [&]() { write_node(smem, out, ln, node0 + ln, lane, num, den); };
    auto close_node = [&]() {
        if (head) {
            s_part[warp * 64 + lane] = make_float4(num[0], num[1], num[2], num[3]);
            s_part[warp * 64 + 32 + lane] = make_float4(den[0], den[1], den[2], den[3]);
            head = false;
        } else {
            finish_node();
        }
        #pragma unroll
        for (int i = 0; i < 4; i++) { num[i] = 0.f; den[i] = 0.f; }
    };

    bool tail = false;
    if (g < g1 || warp == K2_NW - 1) {
        load_node();
        Grp b[K2_D];
        #pragma unroll
        for (int d = 0; d < K2_D; d++)
            if (g + d < g1) grp_load(b[d], s_sorted + K2_GS * (g + d), Tl);
        while (g < g1) {
            #pragma unroll
            for (int d = 0; d < K2_D; d++) {
                if (g < g1) {
                    while (g == node_end) { close_node(); ln++; load_node(); }
                    grp_consume(b[d], s_sorted + K2_GS * g, a, cc, num, den);
                    if (g + K2_D < g1) grp_load(b[d], s_sorted + K2_GS * (g + K2_D), Tl);
                    g++;
                }
            }
        }
        if (warp == K2_NW - 1) {
            while (true) { close_node(); ln++; if (ln >= nn) break; load_node(); }
        } else if (node_end == g1 || head) {
            close_node();
        } else {
            tail = true;
        }
    }
    TSM(tid == 0, 11);
    __syncthreads();
    TSM(tid == 0, 12);
    if (tail) {
        for (int w2 = warp + 1; w2 < K2_NW && (G * w2) / K2_NW < node_end; w2++) {
            const float4 pn = s_part[w2 * 64 + lane], pd = s_part[w2 * 64 + 32 + lane];
            num[0] += pn.x; num[1] += pn.y; num[2] += pn.z; num[3] += pn.w;
            den[0] += pd.x; den[1] += pd.y; den[2] += pd.z; den[3] += pd.w;
        }
        finish_node();
    }
}

extern "C" void kernel_launch(void* const* d_in, const int* in_sizes, int n_in,
                              void* d_out, int out_size) {
    const __nv_bfloat16* x      = (const __nv_bfloat16*)d_in[0];
    const __nv_bfloat16* e_attr = (const __nv_bfloat16*)d_in[1];
    const int* src = (const int*)d_in[2];
    const int* dst = (const int*)d_in[3];
    const __nv_bfloat16* w_a = (const __nv_bfloat16*)d_in[4];
    const __nv_bfloat16* w_b = (const __nv_bfloat16*)d_in[5];
    const __nv_bfloat16* w_c = (const __nv_bfloat16*)d_in[6];
    const __nv_bfloat16* w_u = (const __nv_bfloat16*)d_in[7];
    const __nv_bfloat16* w_v = (const __nv_bfloat16*)d_in[8];
    __nv_bfloat16* out = (__nv_bfloat16*)d_out;
    const int N = in_sizes[0] / D_FEAT;
    const int E = in_sizes[2];
    if (N > MAX_N || 2 * E > MAX_E || N <= 0) return;

    static int num_sms = 0;
    if (num_sms == 0) {
        int dev = 0;
        cudaGetDevice(&dev);
        cudaDeviceGetAttribute(&num_sms, cudaDevAttrMultiProcessorCount, dev);
        if (num_sms <= 0 || num_sms > MAXBINS) num_sms = 132;
        cudaFuncSetAttribute(k1_kernel, cudaFuncAttributeMaxDynamicSharedMemorySize, K1_SMEM);
        cudaFuncSetAttribute(k2_kernel, cudaFuncAttributeMaxDynamicSharedMemorySize, K2_DYN_SMEM);
    }
    typedef CUresult (*EncodeFn)(CUtensorMap*, CUtensorMapDataType, cuuint32_t, void*, const cuuint64_t*, const cuuint64_t*,
                                 const cuuint32_t*, const cuuint32_t*, CUtensorMapInterleave, CUtensorMapSwizzle,
                                 CUtensorMapL2promotion, CUtensorMapFloatOOBfill);
    static EncodeFn encode = nullptr;
    if (!encode) {
        void* fn = nullptr;
        cudaDriverEntryPointQueryResult qres;
        if (cudaGetDriverEntryPoint("cuTensorMapEncodeTiled", &fn, cudaEnableDefault, &qres) != cudaSuccess || !fn) return;
        encode = (EncodeFn)fn;
    }
    auto make_map = [&](CUtensorMap* m, const void* base, int rows, int box_rows) {
        cuuint64_t dims[2] = { D_FEAT, (cuuint64_t)rows };
        cuuint64_t strides[1] = { D_FEAT * 2 };
        cuuint32_t box[2] = { 64, (cuuint32_t)box_rows };
        cuuint32_t es[2] = { 1, 1 };
        return encode(m, CU_TENSOR_MAP_DATA_TYPE_BFLOAT16, 2, const_cast<void*>(base), dims, strides, box, es,
                      CU_TENSOR_MAP_INTERLEAVE_NONE, CU_TENSOR_MAP_SWIZZLE_128B, CU_TENSOR_MAP_L2_PROMOTION_L2_128B,
                      CU_TENSOR_MAP_FLOAT_OOB_FILL_NONE);
    };
    CUtensorMap tm_x, tm_wa, tm_wb, tm_wu, tm_wv;
    if (make_map(&tm_x, x, N, 64) != CUDA_SUCCESS || make_map(&tm_wa, w_a, D_FEAT, 128) != CUDA_SUCCESS ||
        make_map(&tm_wb, w_b, D_FEAT, 128) != CUDA_SUCCESS || make_map(&tm_wu, w_u, D_FEAT, 128) != CUDA_SUCCESS ||
        make_map(&tm_wv, w_v, D_FEAT, 128) != CUDA_SUCCESS) return;
    cudaStream_t st = cudaStreamPerThread;
    int NB = (N + num_sms - 1) / num_sms;
    if (NB > MAXNB) NB = MAXNB;
    const int nbins = (N + NB - 1) / NB;
    const uint32_t magic = (uint32_t)(((1u << 24) + NB - 1) / NB);
    const int P = num_sms;
    int chunk = (E + P - 1) / P;
    if (chunk > P1_CHUNK) chunk = P1_CHUNK;
    if (chunk < 1) chunk = 1;
    k1_kernel<<<P, K1_THREADS, K1_SMEM, st>>>(tm_x, tm_wb, tm_wv, x, e_attr, src, dst, w_b, w_v, w_a, w_u, N, E, chunk, NB, nbins, magic);

    cudaLaunchConfig_t cfg = {};
    cfg.gridDim = dim3(nbins);
    cfg.blockDim = dim3(K2_THREADS);
    cfg.dynamicSmemBytes = K2_DYN_SMEM;
    cfg.stream = st;
    cudaLaunchAttribute at[1];
    at[0].id = cudaLaunchAttributeProgrammaticStreamSerialization;
    at[0].val.programmaticStreamSerializationAllowed = 1;
    cfg.attrs = at; cfg.numAttrs = 1;
    cudaLaunchKernelEx(&cfg, k2_kernel, tm_x, tm_wa, tm_wu, w_c, out, N, NB);
}
```

```cpp
#include <cuda_runtime.h>
#include <cuda.h>
#include <cuda_bf16.h>
#include <stdint.h>

#define D_FEAT 128
#define MAX_N 16384
#define MAX_E (1 << 20)
#define LOG2E 1.4426950408889634f

#define MAXBINS 256
#define MAXNB 128
#define BINCAP 3072
__device__ uint4 g_T[(MAX_N + 1) * 32];
#define CNT_STRIDE 1
__device__ int g_bin_cnt[MAXBINS * CNT_STRIDE];
__device__ uint2 g_bins[MAXBINS * BINCAP];
__device__ int g_ovf[MAX_E];
__device__ int g_ovf_cnt;
__device__ int g_done;

#define TSM(cond, i)
__device__ __forceinline__ float ex2_approx(float x) {
    float y; asm("ex2.approx.ftz.f32 %0, %1;" : "=f"(y) : "f"(x)); return y;
}
__device__ __forceinline__ float rcp_approx(float x) {
    float y; asm("rcp.approx.ftz.f32 %0, %1;" : "=f"(y) : "f"(x)); return y;
}
__device__ __forceinline__ uint32_t pack_bf16(float lo, float hi) {
    __nv_bfloat162 t = __floats2bfloat162_rn(lo, hi);
    return *reinterpret_cast<uint32_t*>(&t);
}
__device__ __forceinline__ float bf_lo(uint32_t v) { return __uint_as_float(v << 16); }
__device__ __forceinline__ float bf_hi(uint32_t v) { return __uint_as_float(v & 0xffff0000u); }
__device__ __forceinline__ float round_bf16(float x) { return __bfloat162float(__float2bfloat16_rn(x)); }

__device__ __forceinline__ void mma_bf16(float c[4], uint32_t a0, uint32_t a1, uint32_t a2, uint32_t a3,
                                         uint32_t b0, uint32_t b1) {
    asm volatile("mma.sync.aligned.m16n8k16.row.col.f32.bf16.bf16.f32 "
                 "{%0,%1,%2,%3}, {%4,%5,%6,%7}, {%8,%9}, {%0,%1,%2,%3};"
                 : "+f"(c[0]), "+f"(c[1]), "+f"(c[2]), "+f"(c[3])
                 : "r"(a0), "r"(a1), "r"(a2), "r"(a3), "r"(b0), "r"(b1));
}
__device__ __forceinline__ void ldmatrix_x4_trans(uint32_t& r0, uint32_t& r1, uint32_t& r2, uint32_t& r3, uint32_t addr) {
    asm volatile("ldmatrix.sync.aligned.m8n8.x4.trans.shared.b16 {%0,%1,%2,%3}, [%4];"
                 : "=r"(r0), "=r"(r1), "=r"(r2), "=r"(r3) : "r"(addr));
}

__device__ __forceinline__ void cp_async16(uint32_t saddr, const void* g) {
    asm volatile("cp.async.cg.shared.global [%0], [%1], 16;" :: "r"(saddr), "l"(g) : "memory");
}
__device__ __forceinline__ void cp_async16_zfill(uint32_t saddr, const void* g, int src_size) {
    asm volatile("cp.async.cg.shared.global [%0], [%1], 16, %2;" :: "r"(saddr), "l"(g), "r"(src_size) : "memory");
}
__device__ __forceinline__ void stage_weight(uint32_t sdst, const __nv_bfloat16* w, int mtx, int tid, int nthreads) {
    const uint4* W = reinterpret_cast<const uint4*>(w);
    for (int u = tid; u < 2048; u += nthreads) {
        int k = u >> 4, c16 = u & 15;
        int kg = k >> 3, rr = k & 7;
        int h = mtx * 2 + (c16 >> 3);
        cp_async16(sdst + kg * 4096 + h * 1024 + rr * 128 + (((c16 & 7) ^ rr) << 4), W + u);
    }
}
__device__ __forceinline__ void stage_x_tile(uint32_t sdst, const __nv_bfloat16* x, int row0, int N, int tid, int nthreads) {
    const uint4* X = reinterpret_cast<const uint4*>(x);
    for (int u = tid; u < 1024; u += nthreads) {
        int r = u >> 4, c16 = u & 15;
        int gr = row0 + r;
        bool ok = gr < N;
        cp_async16_zfill(sdst + (c16 >> 3) * 8192 + r * 128 + (((c16 & 7) ^ (r & 7)) << 4),
                         X + (size_t)(ok ? gr : 0) * 16 + c16, ok ? 16 : 0);
    }
}

__device__ __forceinline__ void mbar_init(uint32_t bar, int cnt) {
    asm volatile("mbarrier.init.shared::cta.b64 [%0], %1;" :: "r"(bar), "r"(cnt) : "memory");
    asm volatile("fence.mbarrier_init.release.cluster;" ::: "memory");
    asm volatile("fence.proxy.async.shared::cta;" ::: "memory");
}
__device__ __forceinline__ void mbar_expect_tx(uint32_t bar, uint32_t bytes) {
    asm volatile("mbarrier.arrive.expect_tx.shared::cta.b64 _, [%0], %1;" :: "r"(bar), "r"(bytes) : "memory");
}
__device__ __forceinline__ void mbar_wait(uint32_t bar, uint32_t parity) {
    asm volatile("{\n.reg .pred p;\nWAIT_LOOP:\n"
                 "mbarrier.try_wait.parity.shared::cta.b64 p, [%0], %1;\n"
                 "@p bra WAIT_DONE;\nbra WAIT_LOOP;\nWAIT_DONE:\n}" :: "r"(bar), "r"(parity) : "memory");
}
__device__ __forceinline__ void tma_2d(uint32_t sdst, const CUtensorMap* tm, int c0, int c1, uint32_t bar) {
    asm volatile("cp.async.bulk.tensor.2d.shared::cluster.global.mbarrier::complete_tx::bytes [%0], [%1, {%3, %4}], [%2];"
                 :: "r"(sdst), "l"(reinterpret_cast<uint64_t>(tm)), "r"(bar), "r"(c0), "r"(c1) : "memory");
}
__device__ __forceinline__ void tma_weights(uint32_t sdst, const CUtensorMap* m0, const CUtensorMap* m1, uint32_t bar) {
    tma_2d(sdst, m0, 0, 0, bar);
    tma_2d(sdst + 16384, m0, 64, 0, bar);
    tma_2d(sdst + 32768, m1, 0, 0, bar);
    tma_2d(sdst + 49152, m1, 64, 0, bar);
}
__device__ __forceinline__ void tma_x_tile(uint32_t sdst, const CUtensorMap* mx, int row0, uint32_t bar) {
    tma_2d(sdst, mx, 0, row0, bar);
    tma_2d(sdst + 8192, mx, 64, row0, bar);
}

__device__ __forceinline__ void wgmma_m64n128k16(float d[64], uint64_t desc_a, uint64_t desc_b, int scale_d) {
    asm volatile("{\n.reg .pred p;\nsetp.ne.b32 p, %66, 0;\n"
                 "wgmma.mma_async.sync.aligned.m64n128k16.f32.bf16.bf16 {%0,%1,%2,%3,%4,%5,%6,%7,%8,%9,%10,%11,%12,%13,%14,%15,%16,%17,%18,%19,%20,%21,%22,%23,%24,%25,%26,%27,%28,%29,%30,%31,%32,%33,%34,%35,%36,%37,%38,%39,%40,%41,%42,%43,%44,%45,%46,%47,%48,%49,%50,%51,%52,%53,%54,%55,%56,%57,%58,%59,%60,%61,%62,%63}, %64, %65, p, 1, 1, 0, 1;\n}"
                 : "+f"(d[0]),"+f"(d[1]),"+f"(d[2]),"+f"(d[3]),"+f"(d[4]),"+f"(d[5]),"+f"(d[6]),"+f"(d[7]),"+f"(d[8]),"+f"(d[9]),"+f"(d[10]),"+f"(d[11]),"+f"(d[12]),"+f"(d[13]),"+f"(d[14]),"+f"(d[15]),"+f"(d[16]),"+f"(d[17]),"+f"(d[18]),"+f"(d[19]),"+f"(d[20]),"+f"(d[21]),"+f"(d[22]),"+f"(d[23]),"+f"(d[24]),"+f"(d[25]),"+f"(d[26]),"+f"(d[27]),"+f"(d[28]),"+f"(d[29]),"+f"(d[30]),"+f"(d[31]),"+f"(d[32]),"+f"(d[33]),"+f"(d[34]),"+f"(d[35]),"+f"(d[36]),"+f"(d[37]),"+f"(d[38]),"+f"(d[39]),"+f"(d[40]),"+f"(d[41]),"+f"(d[42]),"+f"(d[43]),"+f"(d[44]),"+f"(d[45]),"+f"(d[46]),"+f"(d[47]),"+f"(d[48]),"+f"(d[49]),"+f"(d[50]),"+f"(d[51]),"+f"(d[52]),"+f"(d[53]),"+f"(d[54]),"+f"(d[55]),"+f"(d[56]),"+f"(d[57]),"+f"(d[58]),"+f"(d[59]),"+f"(d[60]),"+f"(d[61]),"+f"(d[62]),"+f"(d[63])
                 : "l"(desc_a), "l"(desc_b), "r"(scale_d));
}

__device__ __forceinline__ void wgmma_m64n64k16(float d[32], uint64_t desc_a, uint64_t desc_b, int scale_d) {
    asm volatile("{\n.reg .pred p;\nsetp.ne.b32 p, %34, 0;\n"
                 "wgmma.mma_async.sync.aligned.m64n64k16.f32.bf16.bf16 {%0,%1,%2,%3,%4,%5,%6,%7,%8,%9,%10,%11,%12,%13,%14,%15,%16,%17,%18,%19,%20,%21,%22,%23,%24,%25,%26,%27,%28,%29,%30,%31}, %32, %33, p, 1, 1, 0, 1;\n}"
                 : "+f"(d[0]),"+f"(d[1]),"+f"(d[2]),"+f"(d[3]),"+f"(d[4]),"+f"(d[5]),"+f"(d[6]),"+f"(d[7]),"+f"(d[8]),"+f"(d[9]),"+f"(d[10]),"+f"(d[11]),"+f"(d[12]),"+f"(d[13]),"+f"(d[14]),"+f"(d[15]),"+f"(d[16]),"+f"(d[17]),"+f"(d[18]),"+f"(d[19]),"+f"(d[20]),"+f"(d[21]),"+f"(d[22]),"+f"(d[23]),"+f"(d[24]),"+f"(d[25]),"+f"(d[26]),"+f"(d[27]),"+f"(d[28]),"+f"(d[29]),"+f"(d[30]),"+f"(d[31])
                 : "l"(desc_a), "l"(desc_b), "r"(scale_d));
}

#define K1_GW 12
#define P1_FIRST
#define P1_T 256
#define K1_THREADS (K1_GW * 32 + P1_T)
#define P1_EPT ((2560 + P1_T - 1) / P1_T)
#define P1_CHUNK (P1_T * P1_EPT)
#define K1_WBYTES (65536 + 2 * 16384)
#define K1_SMEM (K1_WBYTES + 3 * MAXBINS * 4 + P1_CHUNK * 8 + 16)

__device__ __forceinline__ void p1_bar() { asm volatile("bar.sync 1, %0;" :: "n"(P1_T) : "memory"); }

__global__ void __launch_bounds__(K1_THREADS, 1) k1_kernel(
    const __grid_constant__ CUtensorMap tm_x, const __grid_constant__ CUtensorMap tm_wb, const __grid_constant__ CUtensorMap tm_wv,
    const __nv_bfloat16* __restrict__ x, const __nv_bfloat16* __restrict__ e_attr,
    const int* __restrict__ src, const int* __restrict__ dst,
    const __nv_bfloat16* __restrict__ w_b, const __nv_bfloat16* __restrict__ w_v,
    const __nv_bfloat16* __restrict__ w_a, const __nv_bfloat16* __restrict__ w_u,
    int N, int E, int chunk, int NB, int nbins, uint32_t magic)
{
    extern __shared__ __align__(1024) uint8_t smem[];
    asm volatile("griddepcontrol.launch_dependents;");
    TSM(threadIdx.x == 0, 0);

    const int warp = threadIdx.x >> 5, lane = threadIdx.x & 31;

    if (warp >= K1_GW) {
        const int tid = threadIdx.x - K1_GW * 32;
        if (blockIdx.x == 0 && tid < 32)
            g_T[(size_t)N * 32 + tid] = make_uint4(0xff80ff80u, 0xff80ff80u, 0u, 0u);
        int* hist = reinterpret_cast<int*>(smem + K1_WBYTES);
        int* loff = hist + MAXBINS;
        int* gbase = loff + MAXBINS;
        uint2* sorted = reinterpret_cast<uint2*>(smem + K1_WBYTES + 3 * MAXBINS * 4);
        for (int beg = blockIdx.x * chunk; beg < E; beg += gridDim.x * chunk) {
            const int end = min(E, beg + chunk);
            int d[P1_EPT]; uint32_t rec[P1_EPT]; int rk[P1_EPT]; int bn[P1_EPT];
            #pragma unroll
            for (int i = 0; i < P1_EPT; i++) {
                int e = beg + i * P1_T + tid;
                d[i] = -1;
                if (e < end) {
                    d[i] = __ldg(dst + e);
                    uint32_t s = (uint32_t)__ldg(src + e);
                    uint32_t ev = (uint32_t)__ldg(reinterpret_cast<const unsigned short*>(e_attr) + e);
                    rec[i] = (ev << 16) | s;
                }
            }
            if (beg == (int)blockIdx.x * chunk) asm volatile("bar.arrive 3, %0;" :: "n"(K1_THREADS) : "memory");
            if (tid < MAXBINS) hist[tid] = 0;
            TSM(tid == 0 && d[P1_EPT - 2] != -5 && rec[P1_EPT - 2] != 0xfffffff5u, 14);
            p1_bar();
            #pragma unroll
            for (int i = 0; i < P1_EPT; i++) {
                if (d[i] >= 0) {
                    bn[i] = (int)(((uint64_t)(uint32_t)d[i] * magic) >> 24);
                    rk[i] = atomicAdd(&hist[bn[i]], 1);
                }
            }
            p1_bar();
            TSM(tid == 0, 3);
            {
                int h = (tid < MAXBINS) ? hist[tid] : 0;
                if (tid < nbins && h > 0) gbase[tid] = atomicAdd(&g_bin_cnt[tid * CNT_STRIDE], h);
                if (tid < 32) {
                    int v[8]; int sum = 0;
                    #pragma unroll
                    for (int i = 0; i < 8; i++) { v[i] = hist[lane * 8 + i]; sum += v[i]; }
                    int inc = sum;
                    #pragma unroll
                    for (int o = 1; o < 32; o <<= 1) { int t = __shfl_up_sync(0xffffffffu, inc, o); if (lane >= o) inc += t; }
                    int run = inc - sum;
                    #pragma unroll
                    for (int i = 0; i < 8; i++) { loff[lane * 8 + i] = run; run += v[i]; }
                }
            }
            p1_bar();
            TSM(tid == 0, 6);
            #pragma unroll
            for (int i = 0; i < P1_EPT; i++) {
                if (d[i] >= 0) sorted[loff[bn[i]] + rk[i]] = make_uint2(rec[i], (uint32_t)d[i]);
            }
            p1_bar();
            TSM(tid == 0, 7);
            const int cnt = end - beg;
            {
                uint2 r[P1_EPT]; int b[P1_EPT], pos[P1_EPT];
                #pragma unroll
                for (int k = 0; k < P1_EPT; k++) {
                    const int i = k * P1_T + tid;
                    r[k] = sorted[min(i, P1_CHUNK - 1)];
                }
                #pragma unroll
                for (int k = 0; k < P1_EPT; k++) {
                    const int i = k * P1_T + tid;
                    b[k] = (i < cnt) ? (int)(((uint64_t)r[k].y * magic) >> 24) : 0;
                    pos[k] = gbase[b[k]] + (i - loff[b[k]]);
                }
                #pragma unroll
                for (int k = 0; k < P1_EPT; k++) {
                    const int i = k * P1_T + tid;
                    if (i < cnt) {
                        if (pos[k] < BINCAP) {
                            g_bins[b[k] * BINCAP + pos[k]] = make_uint2(r[k].x, r[k].y - (uint32_t)(b[k] * NB));
                        } else {
                            int p = atomicAdd(&g_ovf_cnt, 2);
                            g_ovf[p] = (int)r[k].y; g_ovf[p + 1] = (int)r[k].x;
                        }
                    }
                }
            }
            p1_bar();
        }
        TSM(tid == 0, 4);
        return;
    }

    if ((int)blockIdx.x * chunk < E) asm volatile("bar.sync 3, %0;" :: "n"(K1_THREADS) : "memory");
    if (blockIdx.x < 4 && threadIdx.x < 128) {
        const char* pw = reinterpret_cast<const char*>((blockIdx.x & 2) ? w_u : w_a) + (blockIdx.x & 1) * 16384 + threadIdx.x * 128;
        asm volatile("prefetch.global.L2 [%0];" :: "l"(pw));
    }
    const int q = lane & 3;
    const int wg = warp >> 2;
    const int n_tasks = ((N + 63) >> 6) * 2;
    const uint32_t sbase = (uint32_t)__cvta_generic_to_shared(smem);
    const uint32_t xbase = sbase + 65536;
    bool w_staged = false;
    const uint32_t mbar = sbase + K1_SMEM - 16;
    uint32_t phase = 0;
    if (threadIdx.x == 0) mbar_init(mbar, 1);
    int t_beg = (int)(((long long)n_tasks * blockIdx.x) / gridDim.x);
    const int t_end = (int)(((long long)n_tasks * (blockIdx.x + 1)) / gridDim.x);
    while (t_beg < t_end) {
        const int tile0 = t_beg >> 1;
        const int t_stop = min(t_end, (tile0 + 2) << 1);
        if (threadIdx.x == 0) {
            const bool two = ((t_stop - 1) >> 1) > tile0;
            mbar_expect_tx(mbar, (two ? 32768u : 16384u) + (w_staged ? 0u : 65536u));
            tma_x_tile(xbase, &tm_x, tile0 * 64, mbar);
            if (!w_staged) tma_weights(sbase, &tm_wb, &tm_wv, mbar);
            if (two) tma_x_tile(xbase + 16384, &tm_x, tile0 * 64 + 64, mbar);
        }
        if (!w_staged) asm volatile("bar.sync 2, %0;" :: "n"(K1_GW * 32) : "memory");
        w_staged = true;
        mbar_wait(mbar, phase);
        phase ^= 1;
        TSM(threadIdx.x == 0, 1);
        for (int task = t_beg + wg; task < t_stop; task += K1_GW / 4) {
            const int tile = task >> 1, hf = task & 1;
            const uint32_t baddr = sbase + hf * 16384;
            const uint64_t descb = (uint64_t)((baddr & 0x3FFFF) >> 4) | ((uint64_t)(32768 >> 4) << 16) |
                                   ((uint64_t)(1024 >> 4) << 32) | ((uint64_t)1 << 62);
            const uint32_t aaddr = xbase + (tile - tile0) * 16384;
            const uint64_t desca = (uint64_t)((aaddr & 0x3FFFF) >> 4) | ((uint64_t)1 << 16) |
                                   ((uint64_t)(1024 >> 4) << 32) | ((uint64_t)1 << 62);
            float d[64];
            asm volatile("wgmma.fence.sync.aligned;" ::: "memory");
            #pragma unroll
            for (int ks = 0; ks < 8; ks++) {
                wgmma_m64n128k16(d, desca + (uint64_t)(((ks >> 2) * 8192 + (ks & 3) * 32) >> 4),
                                 descb + (uint64_t)(ks * (2048 >> 4)), ks > 0 ? 1 : 0);
            }
            asm volatile("wgmma.commit_group.sync.aligned;" ::: "memory");
            asm volatile("wgmma.wait_group.sync.aligned 0;" ::: "memory");
            TSM(threadIdx.x == 0, 13);
            const int r0 = tile * 64 + (warp & 3) * 16 + (lane >> 2);
            #pragma unroll
            for (int mm = 0; mm < 4; mm++) {
                const int j0 = 2 * mm, j1 = 2 * mm + 1, j2 = 8 + 2 * mm, j3 = 9 + 2 * mm;
                uint4 o0 = make_uint4(pack_bf16(d[4 * j0], d[4 * j0 + 1]), pack_bf16(d[4 * j1], d[4 * j1 + 1]),
                                      pack_bf16(d[4 * j2], d[4 * j2 + 1]), pack_bf16(d[4 * j3], d[4 * j3 + 1]));
                uint4 o1 = make_uint4(pack_bf16(d[4 * j0 + 2], d[4 * j0 + 3]), pack_bf16(d[4 * j1 + 2], d[4 * j1 + 3]),
                                      pack_bf16(d[4 * j2 + 2], d[4 * j2 + 3]), pack_bf16(d[4 * j3 + 2], d[4 * j3 + 3]));
                const int m = 4 * hf + mm;
                if (r0 < N) g_T[(size_t)r0 * 32 + 4 * m + q] = o0;
                if (r0 + 8 < N) g_T[(size_t)(r0 + 8) * 32 + 4 * m + q] = o1;
            }
        }
        t_beg = t_stop;
        if (t_beg < t_end) asm volatile("bar.sync 2, %0;" :: "n"(K1_GW * 32) : "memory");
    }
    TSM(threadIdx.x == 0, 2);
}

__device__ __forceinline__ void edge_accum(const uint4 v, const float e, const float a[4], const float cc[4],
                                           float num[4], float den[4]) {
    float y0 = fmaf(bf_lo(v.x), -LOG2E, fmaf(e, cc[0], a[0]));
    float y1 = fmaf(bf_hi(v.x), -LOG2E, fmaf(e, cc[1], a[1]));
    float y2 = fmaf(bf_lo(v.y), -LOG2E, fmaf(e, cc[2], a[2]));
    float y3 = fmaf(bf_hi(v.y), -LOG2E, fmaf(e, cc[3], a[3]));
    float d0 = 1.f + ex2_approx(fminf(y0, 63.f)), d1 = 1.f + ex2_approx(fminf(y1, 63.f));
    float d2 = 1.f + ex2_approx(fminf(y2, 63.f)), d3 = 1.f + ex2_approx(fminf(y3, 63.f));
    float r01 = rcp_approx(d0 * d1), r23 = rcp_approx(d2 * d3);
    float s0 = r01 * d1, s1 = r01 * d0, s2 = r23 * d3, s3 = r23 * d2;
    den[0] += s0; den[1] += s1; den[2] += s2; den[3] += s3;
    num[0] = fmaf(s0, bf_lo(v.z), num[0]);
    num[1] = fmaf(s1, bf_hi(v.z), num[1]);
    num[2] = fmaf(s2, bf_lo(v.w), num[2]);
    num[3] = fmaf(s3, bf_hi(v.w), num[3]);
}

#define K2_THREADS 1024
#define K2_D 2
#define K2_GS 2
#define K2_RPT ((BINCAP + K2_THREADS - 1) / K2_THREADS)
#define K2_NW (K2_THREADS / 32)
#define SORT_WORDS (BINCAP + 4 * MAXNB)
#define K2_OFF_W 0
#define K2_OFF_X 65536
#define K2_OFF_A (K2_OFF_X + 32768)
#define K2_OFF_U (K2_OFF_A + MAXNB * 256)
#define K2_OFF_PART (K2_OFF_U + MAXNB * 256)
#define K2_OFF_SORT (K2_OFF_PART + K2_NW * 1024)
#define K2_OFF_HIST (K2_OFF_SORT + SORT_WORDS * 8)
#define K2_OFF_OFF (K2_OFF_HIST + MAXNB * 4)
#define K2_OFF_MBAR (K2_OFF_OFF + (MAXNB + 4) * 4)
#define K2_DYN_SMEM (K2_OFF_MBAR + 16)
#define K2_ST (K2_THREADS - 512)
#define K2_SRPT ((BINCAP + K2_ST - 1) / K2_ST)

struct Grp { uint4 v[K2_GS]; };

__device__ __forceinline__ const uint4* row_ptr(const char* Tl, uint32_t rec) {
    return reinterpret_cast<const uint4*>(Tl + (size_t)((rec & 0xffffu) * 512u));
}
__device__ __forceinline__ const uint4* row_at(const char* Tl, uint32_t off) {
    return reinterpret_cast<const uint4*>(Tl + (size_t)off);
}
__device__ __forceinline__ void grp_load(Grp& g, const uint32_t* sp, const char* Tl) {
    const uint2 t = *reinterpret_cast<const uint2*>(sp);
    g.v[0] = __ldg(row_at(Tl, t.x));
    g.v[1] = __ldg(row_at(Tl, t.y));
}
__device__ __forceinline__ void grp_consume(const Grp& g, const uint32_t* sp, const float a[4], const float cc[4],
                                            float num[4], float den[4]) {
    const float2 t = *reinterpret_cast<const float2*>(sp + SORT_WORDS);
    edge_accum(g.v[0], t.x, a, cc, num, den);
    edge_accum(g.v[1], t.y, a, cc, num, den);
}

__device__ __forceinline__ void load_a(const uint8_t* smem, int ln, int lane, float a[4]) {
    const uint2 av = reinterpret_cast<const uint2*>(smem + K2_OFF_A)[ln * 32 + (lane ^ ((ln & 3) << 2))];
    a[0] = -LOG2E * bf_lo(av.x); a[1] = -LOG2E * bf_hi(av.x); a[2] = -LOG2E * bf_lo(av.y); a[3] = -LOG2E * bf_hi(av.y);
}
__device__ __forceinline__ void write_node(const uint8_t* smem, __nv_bfloat16* out, int ln, int n,
                                           int lane, const float num[4], const float den[4]) {
    const uint2 uv = reinterpret_cast<const uint2*>(smem + K2_OFF_U)[ln * 32 + (lane ^ ((ln & 3) << 2))];
    const int r = ln & 63, c16 = (lane >> 2) * 2;
    const uint8_t* xr = smem + K2_OFF_X + (ln >> 6) * 16384 + (c16 >> 3) * 8192 + r * 128 + (lane & 3) * 4;
    const uint32_t x0 = *reinterpret_cast<const uint32_t*>(xr + (((c16 & 7) ^ (r & 7)) << 4));
    const uint32_t x1 = *reinterpret_cast<const uint32_t*>(xr + ((((c16 + 1) & 7) ^ (r & 7)) << 4));
    const float u4[4] = { bf_lo(uv.x), bf_hi(uv.x), bf_lo(uv.y), bf_hi(uv.y) };
    const float x4[4] = { bf_lo(x0), bf_hi(x0), bf_lo(x1), bf_hi(x1) };
    float o[4];
    #pragma unroll
    for (int i = 0; i < 4; i++) {
        float agg = round_bf16(__fdividef(num[i], den[i] + 1e-6f));
        float z = round_bf16(u4[i] + agg);
        float rz = (z > 0.f) ? z : 0.f * z;
        o[i] = x4[i] + rz;
    }
    uint32_t* o32 = reinterpret_cast<uint32_t*>(out) + (size_t)n * 64 + (lane >> 2) * 8 + (lane & 3);
    o32[0] = pack_bf16(o[0], o[1]); o32[4] = pack_bf16(o[2], o[3]);
}

__device__ __noinline__ void slow_path(const uint8_t* smem, __nv_bfloat16* out, int node0, int nn, int ovf_n,
                                       float c0, float c1, float c2, float c3) {
    const uint32_t* s_sorted = reinterpret_cast<const uint32_t*>(smem + K2_OFF_SORT);
    const int* s_off = reinterpret_cast<const int*>(smem + K2_OFF_OFF);
    const int lane = threadIdx.x & 31, warp = threadIdx.x >> 5;
    const float cc[4] = { c0, c1, c2, c3 };
    const char* Tl = reinterpret_cast<const char*>(g_T) + lane * 16;
    for (int ln = warp; ln < nn; ln += K2_NW) {
        float a[4];
        load_a(smem, ln, lane, a);
        float num[4] = {0.f, 0.f, 0.f, 0.f}, den[4] = {0.f, 0.f, 0.f, 0.f};
        for (int i = s_off[ln]; i < s_off[ln + 1]; i++) {
            edge_accum(__ldg(row_at(Tl, s_sorted[i])), __uint_as_float(s_sorted[SORT_WORDS + i]), a, cc, num, den);
        }
        const int n = node0 + ln;
        for (int base = 0; base < ovf_n; base += 64) {
            int i2 = base + 2 * lane;
            int od = (i2 < ovf_n) ? g_ovf[i2] : -1;
            uint32_t orec = (i2 < ovf_n) ? (uint32_t)g_ovf[i2 + 1] : 0u;
            unsigned msk = __ballot_sync(0xffffffffu, od == n);
            while (msk) {
                int l = __ffs(msk) - 1; msk &= msk - 1;
                uint32_t r = __shfl_sync(0xffffffffu, orec, l);
                edge_accum(__ldg(row_ptr(Tl, r)), bf_hi(r), a, cc, num, den);
            }
        }
        write_node(smem, out, ln, n, lane, num, den);
    }
}

__global__ void __launch_bounds__(K2_THREADS, 1) k2_kernel(
    const __grid_constant__ CUtensorMap tm_x, const __grid_constant__ CUtensorMap tm_wa, const __grid_constant__ CUtensorMap tm_wu,
    const __nv_bfloat16* __restrict__ w_c, __nv_bfloat16* __restrict__ out, int N, int NB)
{
    extern __shared__ __align__(1024) uint8_t smem[];
    float4* s_part = reinterpret_cast<float4*>(smem + K2_OFF_PART);
    uint32_t* s_sorted = reinterpret_cast<uint32_t*>(smem + K2_OFF_SORT);
    int* s_hist = reinterpret_cast<int*>(smem + K2_OFF_HIST);
    int* s_off = reinterpret_cast<int*>(smem + K2_OFF_OFF);

    const int tid = threadIdx.x;
    const int lane = tid & 31, warp = tid >> 5;
    const int bin = blockIdx.x;
    const int node0 = bin * NB;
    const int nn = min(NB, N - node0);
    const uint32_t sb = (uint32_t)__cvta_generic_to_shared(smem);
    TSM(tid == 0, 5);

    const int fw = (lane >> 2) * 8 + (lane & 3);
    const uint2 wc = make_uint2(__ldg(reinterpret_cast<const uint32_t*>(w_c) + fw), __ldg(reinterpret_cast<const uint32_t*>(w_c) + fw + 4));
    s_part[warp * 64 + lane] = make_float4(0.f, 0.f, 0.f, 0.f);
    s_part[warp * 64 + 32 + lane] = make_float4(0.f, 0.f, 0.f, 0.f);
    if (warp < 16) {
        const uint32_t mbar = sb + K2_OFF_MBAR;
        if (tid == 0) {
            mbar_init(mbar, 1);
            mbar_expect_tx(mbar, (nn > 64 ? 32768u : 16384u) + 65536u);
            tma_x_tile(sb + K2_OFF_X, &tm_x, node0, mbar);
            tma_weights(sb + K2_OFF_W, &tm_wa, &tm_wu, mbar);
            if (nn > 64) tma_x_tile(sb + K2_OFF_X + 16384, &tm_x, node0 + 64, mbar);
        }
        asm volatile("bar.sync 2, 512;" ::: "memory");
        mbar_wait(mbar, 0);
        const int wg = warp >> 2, tile = wg >> 1, mtx = wg & 1;
        if (tile * 64 < nn) {
            const uint32_t aaddr = sb + K2_OFF_X + tile * 16384;
            const uint64_t desca = (uint64_t)((aaddr & 0x3FFFF) >> 4) | ((uint64_t)1 << 16) |
                                   ((uint64_t)(1024 >> 4) << 32) | ((uint64_t)1 << 62);
            uint2* dst = reinterpret_cast<uint2*>(smem + (mtx ? K2_OFF_U : K2_OFF_A));
            const int r0 = tile * 64 + (warp & 3) * 16 + (lane >> 2);
            const int sw = (r0 & 3) << 2;
            #pragma unroll 1
            for (int hf = 0; hf < 2; hf++) {
                const uint32_t baddr = sb + K2_OFF_W + (mtx * 2 + hf) * 16384;
                const uint64_t descb = (uint64_t)((baddr & 0x3FFFF) >> 4) | ((uint64_t)(32768 >> 4) << 16) |
                                       ((uint64_t)(1024 >> 4) << 32) | ((uint64_t)1 << 62);
                float d[32];
                asm volatile("wgmma.fence.sync.aligned;" ::: "memory");
                #pragma unroll
                for (int ks = 0; ks < 8; ks++) {
                    wgmma_m64n64k16(d, desca + (uint64_t)(((ks >> 2) * 8192 + (ks & 3) * 32) >> 4),
                                    descb + (uint64_t)(ks * (2048 >> 4)), ks > 0 ? 1 : 0);
                }
                asm volatile("wgmma.commit_group.sync.aligned;" ::: "memory");
                asm volatile("wgmma.wait_group.sync.aligned 0;" ::: "memory");
                TSM(tid == 0 && hf == 0, 15);
                #pragma unroll
                for (int mm = 0; mm < 4; mm++) {
                    const int j0 = 2 * mm, j1 = 2 * mm + 1;
                    const int slot = (4 * (4 * hf + mm) + (lane & 3)) ^ sw;
                    dst[r0 * 32 + slot] = make_uint2(pack_bf16(d[4 * j0], d[4 * j0 + 1]), pack_bf16(d[4 * j1], d[4 * j1 + 1]));
                    dst[(r0 + 8) * 32 + slot] = make_uint2(pack_bf16(d[4 * j0 + 2], d[4 * j0 + 3]), pack_bf16(d[4 * j1 + 2], d[4 * j1 + 3]));
                }
            }
        }
        asm volatile("griddepcontrol.wait;" ::: "memory");
    } else {
        const int st = tid - 512;
        if (st < MAXNB) s_hist[st] = 0;
        for (int i = st; i < SORT_WORDS; i += K2_ST) {
            s_sorted[i] = (uint32_t)N * 512u; s_sorted[SORT_WORDS + i] = 0u;
        }
        asm volatile("bar.sync 1, %0;" :: "n"(K2_ST) : "memory");
        asm volatile("griddepcontrol.wait;" ::: "memory");
        TSM(st == 0, 8);
        uint2 r[K2_SRPT]; int rk[K2_SRPT];
        const int cnt = min(g_bin_cnt[bin * CNT_STRIDE], BINCAP);
        if (st == 64) s_off[MAXNB + 1] = g_ovf_cnt;
        #pragma unroll
        for (int i = 0; i < K2_SRPT; i++) {
            int idx = i * K2_ST + st;
            if (idx < cnt) r[i] = g_bins[bin * BINCAP + idx];
        }
        #pragma unroll
        for (int i = 0; i < K2_SRPT; i++) {
            int idx = i * K2_ST + st;
            if (idx < cnt) rk[i] = atomicAdd(&s_hist[r[i].y], 1);
        }
        asm volatile("bar.sync 1, %0;" :: "n"(K2_ST) : "memory");
        if (warp == 16) {
            int v[4]; int sum = 0;
            #pragma unroll
            for (int i = 0; i < 4; i++) { v[i] = (s_hist[lane * 4 + i] + K2_GS - 1) & ~(K2_GS - 1); sum += v[i]; }
            int inc = sum;
            #pragma unroll
            for (int o = 1; o < 32; o <<= 1) { int t = __shfl_up_sync(0xffffffffu, inc, o); if (lane >= o) inc += t; }
            int run = inc - sum;
            #pragma unroll
            for (int i = 0; i < 4; i++) { s_off[lane * 4 + i] = run; run += v[i]; }
            if (lane == 31) s_off[MAXNB] = run;
        }
        if (st == 32) g_bin_cnt[bin * CNT_STRIDE] = 0;
        asm volatile("bar.sync 1, %0;" :: "n"(K2_ST) : "memory");
        #pragma unroll
        for (int i = 0; i < K2_SRPT; i++) {
            int idx = i * K2_ST + st;
            if (idx < cnt) {
                const int pos = s_off[r[i].y] + rk[i];
                s_sorted[pos] = (r[i].x & 0xffffu) * 512u;
                s_sorted[SORT_WORDS + pos] = r[i].x & 0xffff0000u;
            }
        }
        TSM(st == 0, 9);
    }
    __syncthreads();
    TSM(tid == 0, 10);
    const float cc[4] = { -LOG2E * bf_lo(wc.x), -LOG2E * bf_hi(wc.x), -LOG2E * bf_lo(wc.y), -LOG2E * bf_hi(wc.y) };
    const int ovf_n = s_off[MAXNB + 1];

    if (ovf_n != 0) {
        slow_path(smem, out, node0, nn, ovf_n, cc[0], cc[1], cc[2], cc[3]);
        __syncthreads();
        if (tid == 0) {
            __threadfence();
            int t = atomicAdd(&g_done, 1);
            if (t == (int)gridDim.x - 1) { g_done = 0; __threadfence(); g_ovf_cnt = 0; }
        }
        return;
    }

    const char* Tl = reinterpret_cast<const char*>(g_T) + lane * 16;
    const int G = s_off[MAXNB] / K2_GS;
    int g = (G * warp) / K2_NW;
    const int g1 = (G * (warp + 1)) / K2_NW;
    int ln;
    {
        int c_lo = 0;
        #pragma unroll
        for (int i = 0; i < 4; i++) {
            int node = i * 32 + lane;
            int o = (node < nn) ? s_off[node] : 0x7fffffff;
            c_lo += __popc(__ballot_sync(0xffffffffu, o < g * K2_GS));
        }
        ln = c_lo;
    }
    bool head = ln > 0;
    if (head) ln--;
    float a[4], num[4] = {0.f, 0.f, 0.f, 0.f}, den[4] = {0.f, 0.f, 0.f, 0.f};
    int node_end;

    auto load_node = [&]() {
        load_a(smem, ln, lane, a);
        node_end = s_off[ln + 1] / K2_GS;
    };
    auto finish_node = [&]() { write_node(smem, out, ln, node0 + ln, lane, num, den); };
    auto close_node = [&]() {
        if (head) {
            s_part[warp * 64 + lane] = make_float4(num[0], num[1], num[2], num[3]);
            s_part[warp * 64 + 32 + lane] = make_float4(den[0], den[1], den[2], den[3]);
            head = false;
        } else {
            finish_node();
        }
        #pragma unroll
        for (int i = 0; i < 4; i++) { num[i] = 0.f; den[i] = 0.f; }
    };

    bool tail = false;
    if (g < g1 || warp == K2_NW - 1) {
        load_node();
        Grp b[K2_D];
        #pragma unroll
        for (int d = 0; d < K2_D; d++)
            if (g + d < g1) grp_load(b[d], s_sorted + K2_GS * (g + d), Tl);
        while (g < g1) {
            #pragma unroll
            for (int d = 0; d < K2_D; d++) {
                if (g < g1) {
                    while (g == node_end) { close_node(); ln++; load_node(); }
                    grp_consume(b[d], s_sorted + K2_GS * g, a, cc, num, den);
                    if (g + K2_D < g1) grp_load(b[d], s_sorted + K2_GS * (g + K2_D), Tl);
                    g++;
                }
            }
        }
        if (warp == K2_NW - 1) {
            while (true) { close_node(); ln++; if (ln >= nn) break; load_node(); }
        } else if (node_end == g1 || head) {
            close_node();
        } else {
            tail = true;
        }
    }
    TSM(tid == 0, 11);
    __syncthreads();
    TSM(tid == 0, 12);
    if (tail) {
        for (int w2 = warp + 1; w2 < K2_NW && (G * w2) / K2_NW < node_end; w2++) {
            const float4 pn = s_part[w2 * 64 + lane], pd = s_part[w2 * 64 + 32 + lane];
            num[0] += pn.x; num[1] += pn.y; num[2] += pn.z; num[3] += pn.w;
            den[0] += pd.x; den[1] += pd.y; den[2] += pd.z; den[3] += pd.w;
        }
        finish_node();
    }
}

extern "C" void kernel_launch(void* const* d_in, const int* in_sizes, int n_in,
                              void* d_out, int out_size) {
    const __nv_bfloat16* x      = (const __nv_bfloat16*)d_in[0];
    const __nv_bfloat16* e_attr = (const __nv_bfloat16*)d_in[1];
    const int* src = (const int*)d_in[2];
    const int* dst = (const int*)d_in[3];
    const __nv_bfloat16* w_a = (const __nv_bfloat16*)d_in[4];
    const __nv_bfloat16* w_b = (const __nv_bfloat16*)d_in[5];
    const __nv_bfloat16* w_c = (const __nv_bfloat16*)d_in[6];
    const __nv_bfloat16* w_u = (const __nv_bfloat16*)d_in[7];
    const __nv_bfloat16* w_v = (const __nv_bfloat16*)d_in[8];
    __nv_bfloat16* out = (__nv_bfloat16*)d_out;
    const int N = in_sizes[0] / D_FEAT;
    const int E = in_sizes[2];
    if (N > MAX_N || 2 * E > MAX_E || N <= 0) return;

    static int num_sms = 0;
    if (num_sms == 0) {
        int dev = 0;
        cudaGetDevice(&dev);
        cudaDeviceGetAttribute(&num_sms, cudaDevAttrMultiProcessorCount, dev);
        if (num_sms <= 0 || num_sms > MAXBINS) num_sms = 132;
        cudaFuncSetAttribute(k1_kernel, cudaFuncAttributeMaxDynamicSharedMemorySize, K1_SMEM);
        cudaFuncSetAttribute(k2_kernel, cudaFuncAttributeMaxDynamicSharedMemorySize, K2_DYN_SMEM);
    }
    typedef CUresult (*EncodeFn)(CUtensorMap*, CUtensorMapDataType, cuuint32_t, void*, const cuuint64_t*, const cuuint64_t*,
                                 const cuuint32_t*, const cuuint32_t*, CUtensorMapInterleave, CUtensorMapSwizzle,
                                 CUtensorMapL2promotion, CUtensorMapFloatOOBfill);
    static EncodeFn encode = nullptr;
    if (!encode) {
        void* fn = nullptr;
        cudaDriverEntryPointQueryResult qres;
        if (cudaGetDriverEntryPoint("cuTensorMapEncodeTiled", &fn, cudaEnableDefault, &qres) != cudaSuccess || !fn) return;
        encode = (EncodeFn)fn;
    }
    auto make_map = [&](CUtensorMap* m, const void* base, int rows, int box_rows) {
        cuuint64_t dims[2] = { D_FEAT, (cuuint64_t)rows };
        cuuint64_t strides[1] = { D_FEAT * 2 };
        cuuint32_t box[2] = { 64, (cuuint32_t)box_rows };
        cuuint32_t es[2] = { 1, 1 };
        return encode(m, CU_TENSOR_MAP_DATA_TYPE_BFLOAT16, 2, const_cast<void*>(base), dims, strides, box, es,
                      CU_TENSOR_MAP_INTERLEAVE_NONE, CU_TENSOR_MAP_SWIZZLE_128B, CU_TENSOR_MAP_L2_PROMOTION_L2_128B,
                      CU_TENSOR_MAP_FLOAT_OOB_FILL_NONE);
    };
    CUtensorMap tm_x, tm_wa, tm_wb, tm_wu, tm_wv;
    if (make_map(&tm_x, x, N, 64) != CUDA_SUCCESS || make_map(&tm_wa, w_a, D_FEAT, 128) != CUDA_SUCCESS ||
        make_map(&tm_wb, w_b, D_FEAT, 128) != CUDA_SUCCESS || make_map(&tm_wu, w_u, D_FEAT, 128) != CUDA_SUCCESS ||
        make_map(&tm_wv, w_v, D_FEAT, 128) != CUDA_SUCCESS) return;
    cudaStream_t st = cudaStreamPerThread;
    int NB = (N + num_sms - 1) / num_sms;
    if (NB > MAXNB) NB = MAXNB;
    const int nbins = (N + NB - 1) / NB;
    const uint32_t magic = (uint32_t)(((1u << 24) + NB - 1) / NB);
    const int P = num_sms;
    int chunk = (E + P - 1) / P;
    if (chunk > P1_CHUNK) chunk = P1_CHUNK;
    if (chunk < 1) chunk = 1;
    k1_kernel<<<P, K1_THREADS, K1_SMEM, st>>>(tm_x, tm_wb, tm_wv, x, e_attr, src, dst, w_b, w_v, w_a, w_u, N, E, chunk, NB, nbins, magic);

    cudaLaunchConfig_t cfg = {};
    cfg.gridDim = dim3(nbins);
    cfg.blockDim = dim3(K2_THREADS);
    cfg.dynamicSmemBytes = K2_DYN_SMEM;
    cfg.stream = st;
    cudaLaunchAttribute at[1];
    at[0].id = cudaLaunchAttributeProgrammaticStreamSerialization;
    at[0].val.programmaticStreamSerializationAllowed = 1;
    cfg.attrs = at; cfg.numAttrs = 1;
    cudaLaunchKernelEx(&cfg, k2_kernel, tm_x, tm_wa, tm_wu, w_c, out, N, NB);
}
```

```cpp
#include <cuda_runtime.h>
#include <cuda.h>
#include <cuda_bf16.h>
#include <stdint.h>

#define D_FEAT 128
#define MAX_N 16384
#define MAX_E (1 << 20)
#define LOG2E 1.4426950408889634f

#define MAXBINS 256
#define MAXNB 128
#define BINCAP 3072
__device__ uint4 g_T[(MAX_N + 1) * 32];
#define CNT_STRIDE 1
__device__ int g_bin_cnt[MAXBINS * CNT_STRIDE];
__device__ uint2 g_bins[MAXBINS * BINCAP];
__device__ int g_ovf[MAX_E];
__device__ int g_ovf_cnt;
__device__ int g_done;

#define TSM(cond, i)
__device__ __forceinline__ float ex2_approx(float x) {
    float y; asm("ex2.approx.ftz.f32 %0, %1;" : "=f"(y) : "f"(x)); return y;
}
__device__ __forceinline__ float rcp_approx(float x) {
    float y; asm("rcp.approx.ftz.f32 %0, %1;" : "=f"(y) : "f"(x)); return y;
}
__device__ __forceinline__ uint32_t pack_bf16(float lo, float hi) {
    __nv_bfloat162 t = __floats2bfloat162_rn(lo, hi);
    return *reinterpret_cast<uint32_t*>(&t);
}
__device__ __forceinline__ float bf_lo(uint32_t v) { return __uint_as_float(v << 16); }
__device__ __forceinline__ float bf_hi(uint32_t v) { return __uint_as_float(v & 0xffff0000u); }
__device__ __forceinline__ float round_bf16(float x) { return __bfloat162float(__float2bfloat16_rn(x)); }

__device__ __forceinline__ void mma_bf16(float c[4], uint32_t a0, uint32_t a1, uint32_t a2, uint32_t a3,
                                         uint32_t b0, uint32_t b1) {
    asm volatile("mma.sync.aligned.m16n8k16.row.col.f32.bf16.bf16.f32 "
                 "{%0,%1,%2,%3}, {%4,%5,%6,%7}, {%8,%9}, {%0,%1,%2,%3};"
                 : "+f"(c[0]), "+f"(c[1]), "+f"(c[2]), "+f"(c[3])
                 : "r"(a0), "r"(a1), "r"(a2), "r"(a3), "r"(b0), "r"(b1));
}
__device__ __forceinline__ void ldmatrix_x4_trans(uint32_t& r0, uint32_t& r1, uint32_t& r2, uint32_t& r3, uint32_t addr) {
    asm volatile("ldmatrix.sync.aligned.m8n8.x4.trans.shared.b16 {%0,%1,%2,%3}, [%4];"
                 : "=r"(r0), "=r"(r1), "=r"(r2), "=r"(r3) : "r"(addr));
}

__device__ __forceinline__ void cp_async16(uint32_t saddr, const void* g) {
    asm volatile("cp.async.cg.shared.global [%0], [%1], 16;" :: "r"(saddr), "l"(g) : "memory");
}
__device__ __forceinline__ void cp_async16_zfill(uint32_t saddr, const void* g, int src_size) {
    asm volatile("cp.async.cg.shared.global [%0], [%1], 16, %2;" :: "r"(saddr), "l"(g), "r"(src_size) : "memory");
}
__device__ __forceinline__ void stage_weight(uint32_t sdst, const __nv_bfloat16* w, int mtx, int tid, int nthreads) {
    const uint4* W = reinterpret_cast<const uint4*>(w);
    for (int u = tid; u < 2048; u += nthreads) {
        int k = u >> 4, c16 = u & 15;
        int kg = k >> 3, rr = k & 7;
        int h = mtx * 2 + (c16 >> 3);
        cp_async16(sdst + kg * 4096 + h * 1024 + rr * 128 + (((c16 & 7) ^ rr) << 4), W + u);
    }
}
__device__ __forceinline__ void stage_x_tile(uint32_t sdst, const __nv_bfloat16* x, int row0, int N, int tid, int nthreads) {
    const uint4* X = reinterpret_cast<const uint4*>(x);
    for (int u = tid; u < 1024; u += nthreads) {
        int r = u >> 4, c16 = u & 15;
        int gr = row0 + r;
        bool ok = gr < N;
        cp_async16_zfill(sdst + (c16 >> 3) * 8192 + r * 128 + (((c16 & 7) ^ (r & 7)) << 4),
                         X + (size_t)(ok ? gr : 0) * 16 + c16, ok ? 16 : 0);
    }
}

__device__ __forceinline__ void mbar_init(uint32_t bar, int cnt) {
    asm volatile("mbarrier.init.shared::cta.b64 [%0], %1;" :: "r"(bar), "r"(cnt) : "memory");
    asm volatile("fence.mbarrier_init.release.cluster;" ::: "memory");
    asm volatile("fence.proxy.async.shared::cta;" ::: "memory");
}
__device__ __forceinline__ void mbar_expect_tx(uint32_t bar, uint32_t bytes) {
    asm volatile("mbarrier.arrive.expect_tx.shared::cta.b64 _, [%0], %1;" :: "r"(bar), "r"(bytes) : "memory");
}
__device__ __forceinline__ void mbar_wait(uint32_t bar, uint32_t parity) {
    asm volatile("{\n.reg .pred p;\nWAIT_LOOP:\n"
                 "mbarrier.try_wait.parity.shared::cta.b64 p, [%0], %1;\n"
                 "@p bra WAIT_DONE;\nbra WAIT_LOOP;\nWAIT_DONE:\n}" :: "r"(bar), "r"(parity) : "memory");
}
__device__ __forceinline__ void tma_2d(uint32_t sdst, const CUtensorMap* tm, int c0, int c1, uint32_t bar) {
    asm volatile("cp.async.bulk.tensor.2d.shared::cluster.global.mbarrier::complete_tx::bytes [%0], [%1, {%3, %4}], [%2];"
                 :: "r"(sdst), "l"(reinterpret_cast<uint64_t>(tm)), "r"(bar), "r"(c0), "r"(c1) : "memory");
}
__device__ __forceinline__ void tma_weights(uint32_t sdst, const CUtensorMap* m0, const CUtensorMap* m1, uint32_t bar) {
    tma_2d(sdst, m0, 0, 0, bar);
    tma_2d(sdst + 16384, m0, 64, 0, bar);
    tma_2d(sdst + 32768, m1, 0, 0, bar);
    tma_2d(sdst + 49152, m1, 64, 0, bar);
}
__device__ __forceinline__ void tma_x_tile(uint32_t sdst, const CUtensorMap* mx, int row0, uint32_t bar) {
    tma_2d(sdst, mx, 0, row0, bar);
    tma_2d(sdst + 8192, mx, 64, row0, bar);
}

__device__ __forceinline__ void wgmma_m64n128k16(float d[64], uint64_t desc_a, uint64_t desc_b, int scale_d) {
    asm volatile("{\n.reg .pred p;\nsetp.ne.b32 p, %66, 0;\n"
                 "wgmma.mma_async.sync.aligned.m64n128k16.f32.bf16.bf16 {%0,%1,%2,%3,%4,%5,%6,%7,%8,%9,%10,%11,%12,%13,%14,%15,%16,%17,%18,%19,%20,%21,%22,%23,%24,%25,%26,%27,%28,%29,%30,%31,%32,%33,%34,%35,%36,%37,%38,%39,%40,%41,%42,%43,%44,%45,%46,%47,%48,%49,%50,%51,%52,%53,%54,%55,%56,%57,%58,%59,%60,%61,%62,%63}, %64, %65, p, 1, 1, 0, 1;\n}"
                 : "+f"(d[0]),"+f"(d[1]),"+f"(d[2]),"+f"(d[3]),"+f"(d[4]),"+f"(d[5]),"+f"(d[6]),"+f"(d[7]),"+f"(d[8]),"+f"(d[9]),"+f"(d[10]),"+f"(d[11]),"+f"(d[12]),"+f"(d[13]),"+f"(d[14]),"+f"(d[15]),"+f"(d[16]),"+f"(d[17]),"+f"(d[18]),"+f"(d[19]),"+f"(d[20]),"+f"(d[21]),"+f"(d[22]),"+f"(d[23]),"+f"(d[24]),"+f"(d[25]),"+f"(d[26]),"+f"(d[27]),"+f"(d[28]),"+f"(d[29]),"+f"(d[30]),"+f"(d[31]),"+f"(d[32]),"+f"(d[33]),"+f"(d[34]),"+f"(d[35]),"+f"(d[36]),"+f"(d[37]),"+f"(d[38]),"+f"(d[39]),"+f"(d[40]),"+f"(d[41]),"+f"(d[42]),"+f"(d[43]),"+f"(d[44]),"+f"(d[45]),"+f"(d[46]),"+f"(d[47]),"+f"(d[48]),"+f"(d[49]),"+f"(d[50]),"+f"(d[51]),"+f"(d[52]),"+f"(d[53]),"+f"(d[54]),"+f"(d[55]),"+f"(d[56]),"+f"(d[57]),"+f"(d[58]),"+f"(d[59]),"+f"(d[60]),"+f"(d[61]),"+f"(d[62]),"+f"(d[63])
                 : "l"(desc_a), "l"(desc_b), "r"(scale_d));
}

__device__ __forceinline__ void wgmma_m64n64k16(float d[32], uint64_t desc_a, uint64_t desc_b, int scale_d) {
    asm volatile("{\n.reg .pred p;\nsetp.ne.b32 p, %34, 0;\n"
                 "wgmma.mma_async.sync.aligned.m64n64k16.f32.bf16.bf16 {%0,%1,%2,%3,%4,%5,%6,%7,%8,%9,%10,%11,%12,%13,%14,%15,%16,%17,%18,%19,%20,%21,%22,%23,%24,%25,%26,%27,%28,%29,%30,%31}, %32, %33, p, 1, 1, 0, 1;\n}"
                 : "+f"(d[0]),"+f"(d[1]),"+f"(d[2]),"+f"(d[3]),"+f"(d[4]),"+f"(d[5]),"+f"(d[6]),"+f"(d[7]),"+f"(d[8]),"+f"(d[9]),"+f"(d[10]),"+f"(d[11]),"+f"(d[12]),"+f"(d[13]),"+f"(d[14]),"+f"(d[15]),"+f"(d[16]),"+f"(d[17]),"+f"(d[18]),"+f"(d[19]),"+f"(d[20]),"+f"(d[21]),"+f"(d[22]),"+f"(d[23]),"+f"(d[24]),"+f"(d[25]),"+f"(d[26]),"+f"(d[27]),"+f"(d[28]),"+f"(d[29]),"+f"(d[30]),"+f"(d[31])
                 : "l"(desc_a), "l"(desc_b), "r"(scale_d));
}

#define K1_GW 12
#define P1_FIRST
#define P1_T 256
#define K1_THREADS (K1_GW * 32 + P1_T)
#define P1_EPT ((2560 + P1_T - 1) / P1_T)
#define P1_CHUNK (P1_T * P1_EPT)
#define K1_WBYTES (65536 + 2 * 16384)
#define K1_SMEM (K1_WBYTES + 3 * MAXBINS * 4 + P1_CHUNK * 8 + 16)

__device__ __forceinline__ void p1_bar() { asm volatile("bar.sync 1, %0;" :: "n"(P1_T) : "memory"); }

__global__ void __launch_bounds__(K1_THREADS, 1) k1_kernel(
    const __grid_constant__ CUtensorMap tm_x, const __grid_constant__ CUtensorMap tm_wb, const __grid_constant__ CUtensorMap tm_wv,
    const __nv_bfloat16* __restrict__ x, const __nv_bfloat16* __restrict__ e_attr,
    const int* __restrict__ src, const int* __restrict__ dst,
    const __nv_bfloat16* __restrict__ w_b, const __nv_bfloat16* __restrict__ w_v,
    const __nv_bfloat16* __restrict__ w_a, const __nv_bfloat16* __restrict__ w_u,
    int N, int E, int chunk, int NB, int nbins, uint32_t magic)
{
    extern __shared__ __align__(1024) uint8_t smem[];
    asm volatile("griddepcontrol.launch_dependents;");
    TSM(threadIdx.x == 0, 0);

    const int warp = threadIdx.x >> 5, lane = threadIdx.x & 31;

    if (warp >= K1_GW) {
        const int tid = threadIdx.x - K1_GW * 32;
        if (blockIdx.x == 0 && tid < 32)
            g_T[(size_t)N * 32 + tid] = make_uint4(0xff80ff80u, 0xff80ff80u, 0u, 0u);
        int* hist = reinterpret_cast<int*>(smem + K1_WBYTES);
        int* loff = hist + MAXBINS;
        int* gbase = loff + MAXBINS;
        uint2* sorted = reinterpret_cast<uint2*>(smem + K1_WBYTES + 3 * MAXBINS * 4);
        for (int beg = blockIdx.x * chunk; beg < E; beg += gridDim.x * chunk) {
            const int end = min(E, beg + chunk);
            int d[P1_EPT]; uint32_t rec[P1_EPT]; int rk[P1_EPT]; int bn[P1_EPT];
            #pragma unroll
            for (int i = 0; i < P1_EPT; i++) {
                int e = beg + i * P1_T + tid;
                d[i] = -1;
                if (e < end) {
                    d[i] = __ldg(dst + e);
                    uint32_t s = (uint32_t)__ldg(src + e);
                    uint32_t ev = (uint32_t)__ldg(reinterpret_cast<const unsigned short*>(e_attr) + e);
                    rec[i] = (ev << 16) | s;
                }
            }
            if (beg == (int)blockIdx.x * chunk) asm volatile("bar.arrive 3, %0;" :: "n"(K1_THREADS) : "memory");
            if (tid < MAXBINS) hist[tid] = 0;
            TSM(tid == 0 && d[P1_EPT - 2] != -5 && rec[P1_EPT - 2] != 0xfffffff5u, 14);
            p1_bar();
            #pragma unroll
            for (int i = 0; i < P1_EPT; i++) {
                if (d[i] >= 0) {
                    bn[i] = (int)(((uint64_t)(uint32_t)d[i] * magic) >> 24);
                    rk[i] = atomicAdd(&hist[bn[i]], 1);
                }
            }
            p1_bar();
            TSM(tid == 0, 3);
            {
                int h = (tid < MAXBINS) ? hist[tid] : 0;
                if (tid < nbins && h > 0) gbase[tid] = atomicAdd(&g_bin_cnt[tid * CNT_STRIDE], h);
                if (tid < 32) {
                    int v[8]; int sum = 0;
                    #pragma unroll
                    for (int i = 0; i < 8; i++) { v[i] = hist[lane * 8 + i]; sum += v[i]; }
                    int inc = sum;
                    #pragma unroll
                    for (int o = 1; o < 32; o <<= 1) { int t = __shfl_up_sync(0xffffffffu, inc, o); if (lane >= o) inc += t; }
                    int run = inc - sum;
                    #pragma unroll
                    for (int i = 0; i < 8; i++) { loff[lane * 8 + i] = run; run += v[i]; }
                }
            }
            p1_bar();
            TSM(tid == 0, 6);
            #pragma unroll
            for (int i = 0; i < P1_EPT; i++) {
                if (d[i] >= 0) sorted[loff[bn[i]] + rk[i]] = make_uint2(rec[i], (uint32_t)d[i]);
            }
            p1_bar();
            TSM(tid == 0, 7);
            const int cnt = end - beg;
            {
                uint2 r[P1_EPT]; int b[P1_EPT], pos[P1_EPT];
                #pragma unroll
                for (int k = 0; k < P1_EPT; k++) {
                    const int i = k * P1_T + tid;
                    r[k] = sorted[min(i, P1_CHUNK - 1)];
                }
                #pragma unroll
                for (int k = 0; k < P1_EPT; k++) {
                    const int i = k * P1_T + tid;
                    b[k] = (i < cnt) ? (int)(((uint64_t)r[k].y * magic) >> 24) : 0;
                    pos[k] = gbase[b[k]] + (i - loff[b[k]]);
                }
                #pragma unroll
                for (int k = 0; k < P1_EPT; k++) {
                    const int i = k * P1_T + tid;
                    if (i < cnt) {
                        if (pos[k] < BINCAP) {
                            g_bins[b[k] * BINCAP + pos[k]] = make_uint2(r[k].x, r[k].y - (uint32_t)(b[k] * NB));
                        } else {
                            int p = atomicAdd(&g_ovf_cnt, 2);
                            g_ovf[p] = (int)r[k].y; g_ovf[p + 1] = (int)r[k].x;
                        }
                    }
                }
            }
            p1_bar();
        }
        TSM(tid == 0, 4);
        return;
    }

    if ((int)blockIdx.x * chunk < E) asm volatile("bar.sync 3, %0;" :: "n"(K1_THREADS) : "memory");
    if (blockIdx.x < 4 && threadIdx.x < 128) {
        const char* pw = reinterpret_cast<const char*>((blockIdx.x & 2) ? w_u : w_a) + (blockIdx.x & 1) * 16384 + threadIdx.x * 128;
        asm volatile("prefetch.global.L2 [%0];" :: "l"(pw));
    }
    const int q = lane & 3;
    const int wg = warp >> 2;
    const int n_tasks = ((N + 63) >> 6) * 2;
    const uint32_t sbase = (uint32_t)__cvta_generic_to_shared(smem);
    const uint32_t xbase = sbase + 65536;
    bool w_staged = false;
    const uint32_t mbar = sbase + K1_SMEM - 16;
    uint32_t phase = 0;
    if (threadIdx.x == 0) mbar_init(mbar, 1);
    int t_beg = (int)(((long long)n_tasks * blockIdx.x) / gridDim.x);
    const int t_end = (int)(((long long)n_tasks * (blockIdx.x + 1)) / gridDim.x);
    while (t_beg < t_end) {
        const int tile0 = t_beg >> 1;
        const int t_stop = min(t_end, (tile0 + 2) << 1);
        if (threadIdx.x == 0) {
            const bool two = ((t_stop - 1) >> 1) > tile0;
            mbar_expect_tx(mbar, (two ? 32768u : 16384u) + (w_staged ? 0u : 65536u));
            tma_x_tile(xbase, &tm_x, tile0 * 64, mbar);
            if (!w_staged) tma_weights(sbase, &tm_wb, &tm_wv, mbar);
            if (two) tma_x_tile(xbase + 16384, &tm_x, tile0 * 64 + 64, mbar);
        }
        if (!w_staged) asm volatile("bar.sync 2, %0;" :: "n"(K1_GW * 32) : "memory");
        w_staged = true;
        mbar_wait(mbar, phase);
        phase ^= 1;
        TSM(threadIdx.x == 0, 1);
        for (int task = t_beg + wg; task < t_stop; task += K1_GW / 4) {
            const int tile = task >> 1, hf = task & 1;
            const uint32_t baddr = sbase + hf * 16384;
            const uint64_t descb = (uint64_t)((baddr & 0x3FFFF) >> 4) | ((uint64_t)(32768 >> 4) << 16) |
                                   ((uint64_t)(1024 >> 4) << 32) | ((uint64_t)1 << 62);
            const uint32_t aaddr = xbase + (tile - tile0) * 16384;
            const uint64_t desca = (uint64_t)((aaddr & 0x3FFFF) >> 4) | ((uint64_t)1 << 16) |
                                   ((uint64_t)(1024 >> 4) << 32) | ((uint64_t)1 << 62);
            float d[64];
            asm volatile("wgmma.fence.sync.aligned;" ::: "memory");
            #pragma unroll
            for (int ks = 0; ks < 8; ks++) {
                wgmma_m64n128k16(d, desca + (uint64_t)(((ks >> 2) * 8192 + (ks & 3) * 32) >> 4),
                                 descb + (uint64_t)(ks * (2048 >> 4)), ks > 0 ? 1 : 0);
            }
            asm volatile("wgmma.commit_group.sync.aligned;" ::: "memory");
            asm volatile("wgmma.wait_group.sync.aligned 0;" ::: "memory");
            TSM(threadIdx.x == 0, 13);
            const int r0 = tile * 64 + (warp & 3) * 16 + (lane >> 2);
            #pragma unroll
            for (int mm = 0; mm < 4; mm++) {
                const int j0 = 2 * mm, j1 = 2 * mm + 1, j2 = 8 + 2 * mm, j3 = 9 + 2 * mm;
                uint4 o0 = make_uint4(pack_bf16(d[4 * j0], d[4 * j0 + 1]), pack_bf16(d[4 * j1], d[4 * j1 + 1]),
                                      pack_bf16(d[4 * j2], d[4 * j2 + 1]), pack_bf16(d[4 * j3], d[4 * j3 + 1]));
                uint4 o1 = make_uint4(pack_bf16(d[4 * j0 + 2], d[4 * j0 + 3]), pack_bf16(d[4 * j1 + 2], d[4 * j1 + 3]),
                                      pack_bf16(d[4 * j2 + 2], d[4 * j2 + 3]), pack_bf16(d[4 * j3 + 2], d[4 * j3 + 3]));
                const int m = 4 * hf + mm;
                if (r0 < N) g_T[(size_t)r0 * 32 + 4 * m + q] = o0;
                if (r0 + 8 < N) g_T[(size_t)(r0 + 8) * 32 + 4 * m + q] = o1;
            }
        }
        t_beg = t_stop;
        if (t_beg < t_end) asm volatile("bar.sync 2, %0;" :: "n"(K1_GW * 32) : "memory");
    }
    TSM(threadIdx.x == 0, 2);
}

__device__ __forceinline__ void edge_accum(const uint4 v, const float e, const float a[4], const float cc[4],
                                           float num[4], float den[4]) {
    float y0 = fmaf(bf_lo(v.x), -LOG2E, fmaf(e, cc[0], a[0]));
    float y1 = fmaf(bf_hi(v.x), -LOG2E, fmaf(e, cc[1], a[1]));
    float y2 = fmaf(bf_lo(v.y), -LOG2E, fmaf(e, cc[2], a[2]));
    float y3 = fmaf(bf_hi(v.y), -LOG2E, fmaf(e, cc[3], a[3]));
    const float t0 = ex2_approx(fminf(y0, 63.f)), d1 = 1.f + ex2_approx(fminf(y1, 63.f));
    const float t2 = ex2_approx(fminf(y2, 63.f)), d3 = 1.f + ex2_approx(fminf(y3, 63.f));
    const float r01 = rcp_approx(fmaf(t0, d1, d1)), r23 = rcp_approx(fmaf(t2, d3, d3));
    const float s0 = r01 * d1, s1 = fmaf(r01, t0, r01), s2 = r23 * d3, s3 = fmaf(r23, t2, r23);
    den[0] += s0; den[1] += s1; den[2] += s2; den[3] += s3;
    num[0] = fmaf(s0, bf_lo(v.z), num[0]);
    num[1] = fmaf(s1, bf_hi(v.z), num[1]);
    num[2] = fmaf(s2, bf_lo(v.w), num[2]);
    num[3] = fmaf(s3, bf_hi(v.w), num[3]);
}

#define K2_THREADS 1024
#define K2_D 1
#define K2_GS 2
#define K2_RPT ((BINCAP + K2_THREADS - 1) / K2_THREADS)
#define K2_NW (K2_THREADS / 32)
#define SORT_WORDS (BINCAP + 4 * MAXNB)
#define K2_OFF_W 0
#define K2_OFF_X 65536
#define K2_OFF_A (K2_OFF_X + 32768)
#define K2_OFF_U (K2_OFF_A + MAXNB * 256)
#define K2_OFF_PART (K2_OFF_U + MAXNB * 256)
#define K2_OFF_SORT (K2_OFF_PART + K2_NW * 1024)
#define K2_OFF_HIST (K2_OFF_SORT + SORT_WORDS * 8)
#define K2_OFF_OFF (K2_OFF_HIST + MAXNB * 4)
#define K2_OFF_MBAR (K2_OFF_OFF + (MAXNB + 4) * 4)
#define K2_DYN_SMEM (K2_OFF_MBAR + 16)
#define K2_ST (K2_THREADS - 512)
#define K2_SRPT ((BINCAP + K2_ST - 1) / K2_ST)

struct Grp { uint4 v[K2_GS]; };

__device__ __forceinline__ const uint4* row_ptr(const char* Tl, uint32_t rec) {
    return reinterpret_cast<const uint4*>(Tl + (size_t)((rec & 0xffffu) * 512u));
}
__device__ __forceinline__ const uint4* row_at(const char* Tl, uint32_t off) {
    return reinterpret_cast<const uint4*>(Tl + (size_t)off);
}
__device__ __forceinline__ void grp_load(Grp& g, const uint32_t* sp, const char* Tl) {
    const uint2 t = *reinterpret_cast<const uint2*>(sp);
    g.v[0] = __ldg(row_at(Tl, t.x));
    g.v[1] = __ldg(row_at(Tl, t.y));
}
__device__ __forceinline__ void grp_consume(const Grp& g, const uint32_t* sp, const float a[4], const float cc[4],
                                            float num[4], float den[4]) {
    const float2 t = *reinterpret_cast<const float2*>(sp + SORT_WORDS);
    edge_accum(g.v[0], t.x, a, cc, num, den);
    edge_accum(g.v[1], t.y, a, cc, num, den);
}

__device__ __forceinline__ void load_a(const uint8_t* smem, int ln, int lane, float a[4]) {
    const uint2 av = reinterpret_cast<const uint2*>(smem + K2_OFF_A)[ln * 32 + (lane ^ ((ln & 3) << 2))];
    a[0] = -LOG2E * bf_lo(av.x); a[1] = -LOG2E * bf_hi(av.x); a[2] = -LOG2E * bf_lo(av.y); a[3] = -LOG2E * bf_hi(av.y);
}
__device__ __forceinline__ void write_node(const uint8_t* smem, __nv_bfloat16* out, int ln, int n,
                                           int lane, const float num[4], const float den[4]) {
    const uint2 uv = reinterpret_cast<const uint2*>(smem + K2_OFF_U)[ln * 32 + (lane ^ ((ln & 3) << 2))];
    const int r = ln & 63, c16 = (lane >> 2) * 2;
    const uint8_t* xr = smem + K2_OFF_X + (ln >> 6) * 16384 + (c16 >> 3) * 8192 + r * 128 + (lane & 3) * 4;
    const uint32_t x0 = *reinterpret_cast<const uint32_t*>(xr + (((c16 & 7) ^ (r & 7)) << 4));
    const uint32_t x1 = *reinterpret_cast<const uint32_t*>(xr + ((((c16 + 1) & 7) ^ (r & 7)) << 4));
    const float u4[4] = { bf_lo(uv.x), bf_hi(uv.x), bf_lo(uv.y), bf_hi(uv.y) };
    const float x4[4] = { bf_lo(x0), bf_hi(x0), bf_lo(x1), bf_hi(x1) };
    float o[4];
    #pragma unroll
    for (int i = 0; i < 4; i++) {
        float agg = round_bf16(__fdividef(num[i], den[i] + 1e-6f));
        float z = round_bf16(u4[i] + agg);
        float rz = (z > 0.f) ? z : 0.f * z;
        o[i] = x4[i] + rz;
    }
    uint32_t* o32 = reinterpret_cast<uint32_t*>(out) + (size_t)n * 64 + (lane >> 2) * 8 + (lane & 3);
    o32[0] = pack_bf16(o[0], o[1]); o32[4] = pack_bf16(o[2], o[3]);
}

__device__ __noinline__ void slow_path(const uint8_t* smem, __nv_bfloat16* out, int node0, int nn, int ovf_n,
                                       float c0, float c1, float c2, float c3) {
    const uint32_t* s_sorted = reinterpret_cast<const uint32_t*>(smem + K2_OFF_SORT);
    const int* s_off = reinterpret_cast<const int*>(smem + K2_OFF_OFF);
    const int lane = threadIdx.x & 31, warp = threadIdx.x >> 5;
    const float cc[4] = { c0, c1, c2, c3 };
    const char* Tl = reinterpret_cast<const char*>(g_T) + lane * 16;
    for (int ln = warp; ln < nn; ln += K2_NW) {
        float a[4];
        load_a(smem, ln, lane, a);
        float num[4] = {0.f, 0.f, 0.f, 0.f}, den[4] = {0.f, 0.f, 0.f, 0.f};
        for (int i = s_off[ln]; i < s_off[ln + 1]; i++) {
            edge_accum(__ldg(row_at(Tl, s_sorted[i])), __uint_as_float(s_sorted[SORT_WORDS + i]), a, cc, num, den);
        }
        const int n = node0 + ln;
        for (int base = 0; base < ovf_n; base += 64) {
            int i2 = base + 2 * lane;
            int od = (i2 < ovf_n) ? g_ovf[i2] : -1;
            uint32_t orec = (i2 < ovf_n) ? (uint32_t)g_ovf[i2 + 1] : 0u;
            unsigned msk = __ballot_sync(0xffffffffu, od == n);
            while (msk) {
                int l = __ffs(msk) - 1; msk &= msk - 1;
                uint32_t r = __shfl_sync(0xffffffffu, orec, l);
                edge_accum(__ldg(row_ptr(Tl, r)), bf_hi(r), a, cc, num, den);
            }
        }
        write_node(smem, out, ln, n, lane, num, den);
    }
}

__global__ void __launch_bounds__(K2_THREADS, 1) k2_kernel(
    const __grid_constant__ CUtensorMap tm_x, const __grid_constant__ CUtensorMap tm_wa, const __grid_constant__ CUtensorMap tm_wu,
    const __nv_bfloat16* __restrict__ w_c, __nv_bfloat16* __restrict__ out, int N, int NB)
{
    extern __shared__ __align__(1024) uint8_t smem[];
    float4* s_part = reinterpret_cast<float4*>(smem + K2_OFF_PART);
    uint32_t* s_sorted = reinterpret_cast<uint32_t*>(smem + K2_OFF_SORT);
    int* s_hist = reinterpret_cast<int*>(smem + K2_OFF_HIST);
    int* s_off = reinterpret_cast<int*>(smem + K2_OFF_OFF);

    const int tid = threadIdx.x;
    const int lane = tid & 31, warp = tid >> 5;
    const int bin = blockIdx.x;
    const int node0 = bin * NB;
    const int nn = min(NB, N - node0);
    const uint32_t sb = (uint32_t)__cvta_generic_to_shared(smem);
    TSM(tid == 0, 5);

    const int fw = (lane >> 2) * 8 + (lane & 3);
    const uint2 wc = make_uint2(__ldg(reinterpret_cast<const uint32_t*>(w_c) + fw), __ldg(reinterpret_cast<const uint32_t*>(w_c) + fw + 4));
    s_part[warp * 64 + lane] = make_float4(0.f, 0.f, 0.f, 0.f);
    s_part[warp * 64 + 32 + lane] = make_float4(0.f, 0.f, 0.f, 0.f);
    if (warp < 16) {
        const uint32_t mbar = sb + K2_OFF_MBAR;
        if (tid == 0) {
            mbar_init(mbar, 1);
            mbar_expect_tx(mbar, (nn > 64 ? 32768u : 16384u) + 65536u);
            tma_x_tile(sb + K2_OFF_X, &tm_x, node0, mbar);
            tma_weights(sb + K2_OFF_W, &tm_wa, &tm_wu, mbar);
            if (nn > 64) tma_x_tile(sb + K2_OFF_X + 16384, &tm_x, node0 + 64, mbar);
        }
        asm volatile("bar.sync 2, 512;" ::: "memory");
        mbar_wait(mbar, 0);
        const int wg = warp >> 2, tile = wg >> 1, mtx = wg & 1;
        if (tile * 64 < nn) {
            const uint32_t aaddr = sb + K2_OFF_X + tile * 16384;
            const uint64_t desca = (uint64_t)((aaddr & 0x3FFFF) >> 4) | ((uint64_t)1 << 16) |
                                   ((uint64_t)(1024 >> 4) << 32) | ((uint64_t)1 << 62);
            uint2* dst = reinterpret_cast<uint2*>(smem + (mtx ? K2_OFF_U : K2_OFF_A));
            const int r0 = tile * 64 + (warp & 3) * 16 + (lane >> 2);
            const int sw = (r0 & 3) << 2;
            #pragma unroll 1
            for (int hf = 0; hf < 2; hf++) {
                const uint32_t baddr = sb + K2_OFF_W + (mtx * 2 + hf) * 16384;
                const uint64_t descb = (uint64_t)((baddr & 0x3FFFF) >> 4) | ((uint64_t)(32768 >> 4) << 16) |
                                       ((uint64_t)(1024 >> 4) << 32) | ((uint64_t)1 << 62);
                float d[32];
                asm volatile("wgmma.fence.sync.aligned;" ::: "memory");
                #pragma unroll
                for (int ks = 0; ks < 8; ks++) {
                    wgmma_m64n64k16(d, desca + (uint64_t)(((ks >> 2) * 8192 + (ks & 3) * 32) >> 4),
                                    descb + (uint64_t)(ks * (2048 >> 4)), ks > 0 ? 1 : 0);
                }
                asm volatile("wgmma.commit_group.sync.aligned;" ::: "memory");
                asm volatile("wgmma.wait_group.sync.aligned 0;" ::: "memory");
                TSM(tid == 0 && hf == 0, 15);
                #pragma unroll
                for (int mm = 0; mm < 4; mm++) {
                    const int j0 = 2 * mm, j1 = 2 * mm + 1;
                    const int slot = (4 * (4 * hf + mm) + (lane & 3)) ^ sw;
                    dst[r0 * 32 + slot] = make_uint2(pack_bf16(d[4 * j0], d[4 * j0 + 1]), pack_bf16(d[4 * j1], d[4 * j1 + 1]));
                    dst[(r0 + 8) * 32 + slot] = make_uint2(pack_bf16(d[4 * j0 + 2], d[4 * j0 + 3]), pack_bf16(d[4 * j1 + 2], d[4 * j1 + 3]));
                }
            }
        }
        asm volatile("griddepcontrol.wait;" ::: "memory");
    } else {
        const int st = tid - 512;
        if (st < MAXNB) s_hist[st] = 0;
        for (int i = st; i < SORT_WORDS; i += K2_ST) {
            s_sorted[i] = (uint32_t)N * 512u; s_sorted[SORT_WORDS + i] = 0u;
        }
        asm volatile("bar.sync 1, %0;" :: "n"(K2_ST) : "memory");
        asm volatile("griddepcontrol.wait;" ::: "memory");
        TSM(st == 0, 8);
        uint2 r[K2_SRPT]; int rk[K2_SRPT];
        const int cnt = min(g_bin_cnt[bin * CNT_STRIDE], BINCAP);
        if (st == 64) s_off[MAXNB + 1] = g_ovf_cnt;
        #pragma unroll
        for (int i = 0; i < K2_SRPT; i++) {
            int idx = i * K2_ST + st;
            if (idx < cnt) r[i] = g_bins[bin * BINCAP + idx];
        }
        #pragma unroll
        for (int i = 0; i < K2_SRPT; i++) {
            int idx = i * K2_ST + st;
            if (idx < cnt) rk[i] = atomicAdd(&s_hist[r[i].y], 1);
        }
        asm volatile("bar.sync 1, %0;" :: "n"(K2_ST) : "memory");
        if (warp == 16) {
            int v[4]; int sum = 0;
            #pragma unroll
            for (int i = 0; i < 4; i++) { v[i] = (s_hist[lane * 4 + i] + K2_GS - 1) & ~(K2_GS - 1); sum += v[i]; }
            int inc = sum;
            #pragma unroll
            for (int o = 1; o < 32; o <<= 1) { int t = __shfl_up_sync(0xffffffffu, inc, o); if (lane >= o) inc += t; }
            int run = inc - sum;
            #pragma unroll
            for (int i = 0; i < 4; i++) { s_off[lane * 4 + i] = run; run += v[i]; }
            if (lane == 31) s_off[MAXNB] = run;
        }
        if (st == 32) g_bin_cnt[bin * CNT_STRIDE] = 0;
        asm volatile("bar.sync 1, %0;" :: "n"(K2_ST) : "memory");
        #pragma unroll
        for (int i = 0; i < K2_SRPT; i++) {
            int idx = i * K2_ST + st;
            if (idx < cnt) {
                const int pos = s_off[r[i].y] + rk[i];
                s_sorted[pos] = (r[i].x & 0xffffu) * 512u;
                s_sorted[SORT_WORDS + pos] = r[i].x & 0xffff0000u;
            }
        }
        TSM(st == 0, 9);
    }
    __syncthreads();
    TSM(tid == 0, 10);
    const float cc[4] = { -LOG2E * bf_lo(wc.x), -LOG2E * bf_hi(wc.x), -LOG2E * bf_lo(wc.y), -LOG2E * bf_hi(wc.y) };
    const int ovf_n = s_off[MAXNB + 1];

    if (ovf_n != 0) {
        slow_path(smem, out, node0, nn, ovf_n, cc[0], cc[1], cc[2], cc[3]);
        __syncthreads();
        if (tid == 0) {
            __threadfence();
            int t = atomicAdd(&g_done, 1);
            if (t == (int)gridDim.x - 1) { g_done = 0; __threadfence(); g_ovf_cnt = 0; }
        }
        return;
    }

    const char* Tl = reinterpret_cast<const char*>(g_T) + lane * 16;
    const int G = s_off[MAXNB] / K2_GS;
    int g = (G * warp) / K2_NW;
    const int g1 = (G * (warp + 1)) / K2_NW;
    int ln;
    {
        int c_lo = 0;
        #pragma unroll
        for (int i = 0; i < 4; i++) {
            int node = i * 32 + lane;
            int o = (node < nn) ? s_off[node] : 0x7fffffff;
            c_lo += __popc(__ballot_sync(0xffffffffu, o < g * K2_GS));
        }
        ln = c_lo;
    }
    bool head = ln > 0;
    if (head) ln--;
    float a[4], num[4] = {0.f, 0.f, 0.f, 0.f}, den[4] = {0.f, 0.f, 0.f, 0.f};
    int node_end;

    auto load_node = [&]() {
        load_a(smem, ln, lane, a);
        node_end = s_off[ln + 1] / K2_GS;
    };
    auto finish_node = [&]() { write_node(smem, out, ln, node0 + ln, lane, num, den); };
    auto close_node = [&]() {
        if (head) {
            s_part[warp * 64 + lane] = make_float4(num[0], num[1], num[2], num[3]);
            s_part[warp * 64 + 32 + lane] = make_float4(den[0], den[1], den[2], den[3]);
            head = false;
        } else {
            finish_node();
        }
        #pragma unroll
        for (int i = 0; i < 4; i++) { num[i] = 0.f; den[i] = 0.f; }
    };

    bool tail = false;
    if (g < g1 || warp == K2_NW - 1) {
        load_node();
        if (g < g1) {
            Grp b;
            const uint32_t* sp = s_sorted + K2_GS * g;
            const uint32_t* const sp_last = s_sorted + K2_GS * (g1 - 1);
            grp_load(b, sp, Tl);
            while (true) {
                const int seg_end = min(node_end, g1);
                const uint32_t* const sp_end = s_sorted + K2_GS * seg_end;
                #pragma unroll 1
                for (; sp < sp_end; sp += K2_GS) {
                    grp_consume(b, sp, a, cc, num, den);
                    if (sp < sp_last) grp_load(b, sp + K2_GS, Tl);
                }
                g = seg_end;
                if (g >= g1) break;
                close_node(); ln++; load_node();
            }
        }
        if (warp == K2_NW - 1) {
            while (true) { close_node(); ln++; if (ln >= nn) break; load_node(); }
        } else if (node_end == g1 || head) {
            close_node();
        } else {
            tail = true;
        }
    }
    TSM(tid == 0, 11);
    __syncthreads();
    TSM(tid == 0, 12);
    if (tail) {
        for (int w2 = warp + 1; w2 < K2_NW && (G * w2) / K2_NW < node_end; w2++) {
            const float4 pn = s_part[w2 * 64 + lane], pd = s_part[w2 * 64 + 32 + lane];
            num[0] += pn.x; num[1] += pn.y; num[2] += pn.z; num[3] += pn.w;
            den[0] += pd.x; den[1] += pd.y; den[2] += pd.z; den[3] += pd.w;
        }
        finish_node();
    }
}

extern "C" void kernel_launch(void* const* d_in, const int* in_sizes, int n_in,
                              void* d_out, int out_size) {
    const __nv_bfloat16* x      = (const __nv_bfloat16*)d_in[0];
    const __nv_bfloat16* e_attr = (const __nv_bfloat16*)d_in[1];
    const int* src = (const int*)d_in[2];
    const int* dst = (const int*)d_in[3];
    const __nv_bfloat16* w_a = (const __nv_bfloat16*)d_in[4];
    const __nv_bfloat16* w_b = (const __nv_bfloat16*)d_in[5];
    const __nv_bfloat16* w_c = (const __nv_bfloat16*)d_in[6];
    const __nv_bfloat16* w_u = (const __nv_bfloat16*)d_in[7];
    const __nv_bfloat16* w_v = (const __nv_bfloat16*)d_in[8];
    __nv_bfloat16* out = (__nv_bfloat16*)d_out;
    const int N = in_sizes[0] / D_FEAT;
    const int E = in_sizes[2];
    if (N > MAX_N || 2 * E > MAX_E || N <= 0) return;

    static int num_sms = 0;
    if (num_sms == 0) {
        int dev = 0;
        cudaGetDevice(&dev);
        cudaDeviceGetAttribute(&num_sms, cudaDevAttrMultiProcessorCount, dev);
        if (num_sms <= 0 || num_sms > MAXBINS) num_sms = 132;
        cudaFuncSetAttribute(k1_kernel, cudaFuncAttributeMaxDynamicSharedMemorySize, K1_SMEM);
        cudaFuncSetAttribute(k2_kernel, cudaFuncAttributeMaxDynamicSharedMemorySize, K2_DYN_SMEM);
    }
    typedef CUresult (*EncodeFn)(CUtensorMap*, CUtensorMapDataType, cuuint32_t, void*, const cuuint64_t*, const cuuint64_t*,
                                 const cuuint32_t*, const cuuint32_t*, CUtensorMapInterleave, CUtensorMapSwizzle,
                                 CUtensorMapL2promotion, CUtensorMapFloatOOBfill);
    static EncodeFn encode = nullptr;
    if (!encode) {
        void* fn = nullptr;
        cudaDriverEntryPointQueryResult qres;
        if (cudaGetDriverEntryPoint("cuTensorMapEncodeTiled", &fn, cudaEnableDefault, &qres) != cudaSuccess || !fn) return;
        encode = (EncodeFn)fn;
    }
    auto make_map = [&](CUtensorMap* m, const void* base, int rows, int box_rows) {
        cuuint64_t dims[2] = { D_FEAT, (cuuint64_t)rows };
        cuuint64_t strides[1] = { D_FEAT * 2 };
        cuuint32_t box[2] = { 64, (cuuint32_t)box_rows };
        cuuint32_t es[2] = { 1, 1 };
        return encode(m, CU_TENSOR_MAP_DATA_TYPE_BFLOAT16, 2, const_cast<void*>(base), dims, strides, box, es,
                      CU_TENSOR_MAP_INTERLEAVE_NONE, CU_TENSOR_MAP_SWIZZLE_128B, CU_TENSOR_MAP_L2_PROMOTION_L2_128B,
                      CU_TENSOR_MAP_FLOAT_OOB_FILL_NONE);
    };
    CUtensorMap tm_x, tm_wa, tm_wb, tm_wu, tm_wv;
    if (make_map(&tm_x, x, N, 64) != CUDA_SUCCESS || make_map(&tm_wa, w_a, D_FEAT, 128) != CUDA_SUCCESS ||
        make_map(&tm_wb, w_b, D_FEAT, 128) != CUDA_SUCCESS || make_map(&tm_wu, w_u, D_FEAT, 128) != CUDA_SUCCESS ||
        make_map(&tm_wv, w_v, D_FEAT, 128) != CUDA_SUCCESS) return;
    cudaStream_t st = cudaStreamPerThread;
    int NB = (N + num_sms - 1) / num_sms;
    if (NB > MAXNB) NB = MAXNB;
    const int nbins = (N + NB - 1) / NB;
    const uint32_t magic = (uint32_t)(((1u << 24) + NB - 1) / NB);
    const int P = num_sms;
    int chunk = (E + P - 1) / P;
    if (chunk > P1_CHUNK) chunk = P1_CHUNK;
    if (chunk < 1) chunk = 1;
    k1_kernel<<<P, K1_THREADS, K1_SMEM, st>>>(tm_x, tm_wb, tm_wv, x, e_attr, src, dst, w_b, w_v, w_a, w_u, N, E, chunk, NB, nbins, magic);

    cudaLaunchConfig_t cfg = {};
    cfg.gridDim = dim3(nbins);
    cfg.blockDim = dim3(K2_THREADS);
    cfg.dynamicSmemBytes = K2_DYN_SMEM;
    cfg.stream = st;
    cudaLaunchAttribute at[1];
    at[0].id = cudaLaunchAttributeProgrammaticStreamSerialization;
    at[0].val.programmaticStreamSerializationAllowed = 1;
    cfg.attrs = at; cfg.numAttrs = 1;
    cudaLaunchKernelEx(&cfg, k2_kernel, tm_x, tm_wa, tm_wu, w_c, out, N, NB);
}
```

```cpp
#include <cuda_runtime.h>
#include <cuda.h>
#include <cuda_bf16.h>
#include <stdint.h>

#define D_FEAT 128
#define MAX_N 16384
#define MAX_E (1 << 20)
#define LOG2E 1.4426950408889634f

#define MAXBINS 256
#define MAXNB 128
#define BINCAP 3072
__device__ uint4 g_T[(MAX_N + 1) * 32];
__device__ int g_bin_cnt[MAXBINS];
__device__ uint2 g_bins[MAXBINS * BINCAP];
__device__ int g_ovf[MAX_E];
__device__ int g_ovf_cnt;
__device__ int g_done;

__device__ __forceinline__ float ex2_approx(float x) {
    float y; asm("ex2.approx.ftz.f32 %0, %1;" : "=f"(y) : "f"(x)); return y;
}
__device__ __forceinline__ float rcp_approx(float x) {
    float y; asm("rcp.approx.ftz.f32 %0, %1;" : "=f"(y) : "f"(x)); return y;
}
__device__ __forceinline__ uint32_t pack_bf16(float lo, float hi) {
    __nv_bfloat162 t = __floats2bfloat162_rn(lo, hi);
    return *reinterpret_cast<uint32_t*>(&t);
}
__device__ __forceinline__ float bf_lo(uint32_t v) { return __uint_as_float(v << 16); }
__device__ __forceinline__ float bf_hi(uint32_t v) { return __uint_as_float(v & 0xffff0000u); }
__device__ __forceinline__ float round_bf16(float x) { return __bfloat162float(__float2bfloat16_rn(x)); }

__device__ __forceinline__ void mbar_init(uint32_t bar, int cnt) {
    asm volatile("mbarrier.init.shared::cta.b64 [%0], %1;" :: "r"(bar), "r"(cnt) : "memory");
    asm volatile("fence.mbarrier_init.release.cluster;" ::: "memory");
    asm volatile("fence.proxy.async.shared::cta;" ::: "memory");
}
__device__ __forceinline__ void mbar_expect_tx(uint32_t bar, uint32_t bytes) {
    asm volatile("mbarrier.arrive.expect_tx.shared::cta.b64 _, [%0], %1;" :: "r"(bar), "r"(bytes) : "memory");
}
__device__ __forceinline__ void mbar_wait(uint32_t bar, uint32_t parity) {
    asm volatile("{\n.reg .pred p;\nWAIT_LOOP:\n"
                 "mbarrier.try_wait.parity.shared::cta.b64 p, [%0], %1;\n"
                 "@p bra WAIT_DONE;\nbra WAIT_LOOP;\nWAIT_DONE:\n}" :: "r"(bar), "r"(parity) : "memory");
}
__device__ __forceinline__ void tma_2d(uint32_t sdst, const CUtensorMap* tm, int c0, int c1, uint32_t bar) {
    asm volatile("cp.async.bulk.tensor.2d.shared::cluster.global.mbarrier::complete_tx::bytes [%0], [%1, {%3, %4}], [%2];"
                 :: "r"(sdst), "l"(reinterpret_cast<uint64_t>(tm)), "r"(bar), "r"(c0), "r"(c1) : "memory");
}
__device__ __forceinline__ void tma_weights(uint32_t sdst, const CUtensorMap* m0, const CUtensorMap* m1, uint32_t bar) {
    tma_2d(sdst, m0, 0, 0, bar);
    tma_2d(sdst + 16384, m0, 64, 0, bar);
    tma_2d(sdst + 32768, m1, 0, 0, bar);
    tma_2d(sdst + 49152, m1, 64, 0, bar);
}
__device__ __forceinline__ void tma_x_tile(uint32_t sdst, const CUtensorMap* mx, int row0, uint32_t bar) {
    tma_2d(sdst, mx, 0, row0, bar);
    tma_2d(sdst + 8192, mx, 64, row0, bar);
}

__device__ __forceinline__ void wgmma_m64n128k16(float d[64], uint64_t desc_a, uint64_t desc_b, int scale_d) {
    asm volatile("{\n.reg .pred p;\nsetp.ne.b32 p, %66, 0;\n"
                 "wgmma.mma_async.sync.aligned.m64n128k16.f32.bf16.bf16 {%0,%1,%2,%3,%4,%5,%6,%7,%8,%9,%10,%11,%12,%13,%14,%15,%16,%17,%18,%19,%20,%21,%22,%23,%24,%25,%26,%27,%28,%29,%30,%31,%32,%33,%34,%35,%36,%37,%38,%39,%40,%41,%42,%43,%44,%45,%46,%47,%48,%49,%50,%51,%52,%53,%54,%55,%56,%57,%58,%59,%60,%61,%62,%63}, %64, %65, p, 1, 1, 0, 1;\n}"
                 : "+f"(d[0]),"+f"(d[1]),"+f"(d[2]),"+f"(d[3]),"+f"(d[4]),"+f"(d[5]),"+f"(d[6]),"+f"(d[7]),"+f"(d[8]),"+f"(d[9]),"+f"(d[10]),"+f"(d[11]),"+f"(d[12]),"+f"(d[13]),"+f"(d[14]),"+f"(d[15]),"+f"(d[16]),"+f"(d[17]),"+f"(d[18]),"+f"(d[19]),"+f"(d[20]),"+f"(d[21]),"+f"(d[22]),"+f"(d[23]),"+f"(d[24]),"+f"(d[25]),"+f"(d[26]),"+f"(d[27]),"+f"(d[28]),"+f"(d[29]),"+f"(d[30]),"+f"(d[31]),"+f"(d[32]),"+f"(d[33]),"+f"(d[34]),"+f"(d[35]),"+f"(d[36]),"+f"(d[37]),"+f"(d[38]),"+f"(d[39]),"+f"(d[40]),"+f"(d[41]),"+f"(d[42]),"+f"(d[43]),"+f"(d[44]),"+f"(d[45]),"+f"(d[46]),"+f"(d[47]),"+f"(d[48]),"+f"(d[49]),"+f"(d[50]),"+f"(d[51]),"+f"(d[52]),"+f"(d[53]),"+f"(d[54]),"+f"(d[55]),"+f"(d[56]),"+f"(d[57]),"+f"(d[58]),"+f"(d[59]),"+f"(d[60]),"+f"(d[61]),"+f"(d[62]),"+f"(d[63])
                 : "l"(desc_a), "l"(desc_b), "r"(scale_d));
}

__device__ __forceinline__ void wgmma_m64n64k16(float d[32], uint64_t desc_a, uint64_t desc_b, int scale_d) {
    asm volatile("{\n.reg .pred p;\nsetp.ne.b32 p, %34, 0;\n"
                 "wgmma.mma_async.sync.aligned.m64n64k16.f32.bf16.bf16 {%0,%1,%2,%3,%4,%5,%6,%7,%8,%9,%10,%11,%12,%13,%14,%15,%16,%17,%18,%19,%20,%21,%22,%23,%24,%25,%26,%27,%28,%29,%30,%31}, %32, %33, p, 1, 1, 0, 1;\n}"
                 : "+f"(d[0]),"+f"(d[1]),"+f"(d[2]),"+f"(d[3]),"+f"(d[4]),"+f"(d[5]),"+f"(d[6]),"+f"(d[7]),"+f"(d[8]),"+f"(d[9]),"+f"(d[10]),"+f"(d[11]),"+f"(d[12]),"+f"(d[13]),"+f"(d[14]),"+f"(d[15]),"+f"(d[16]),"+f"(d[17]),"+f"(d[18]),"+f"(d[19]),"+f"(d[20]),"+f"(d[21]),"+f"(d[22]),"+f"(d[23]),"+f"(d[24]),"+f"(d[25]),"+f"(d[26]),"+f"(d[27]),"+f"(d[28]),"+f"(d[29]),"+f"(d[30]),"+f"(d[31])
                 : "l"(desc_a), "l"(desc_b), "r"(scale_d));
}

#define K1_GW 12
#define P1_T 256
#define K1_THREADS (K1_GW * 32 + P1_T)
#define P1_EPT ((2560 + P1_T - 1) / P1_T)
#define P1_CHUNK (P1_T * P1_EPT)
#define K1_WBYTES (65536 + 2 * 16384)
#define K1_SMEM (K1_WBYTES + 3 * MAXBINS * 4 + P1_CHUNK * 8 + 16)

__device__ __forceinline__ void p1_bar() { asm volatile("bar.sync 1, %0;" :: "n"(P1_T) : "memory"); }

__global__ void __launch_bounds__(K1_THREADS, 1) k1_kernel(
    const __grid_constant__ CUtensorMap tm_x, const __grid_constant__ CUtensorMap tm_wb, const __grid_constant__ CUtensorMap tm_wv,
    const __nv_bfloat16* __restrict__ x, const __nv_bfloat16* __restrict__ e_attr,
    const int* __restrict__ src, const int* __restrict__ dst,
    const __nv_bfloat16* __restrict__ w_b, const __nv_bfloat16* __restrict__ w_v,
    const __nv_bfloat16* __restrict__ w_a, const __nv_bfloat16* __restrict__ w_u,
    int N, int E, int chunk, int NB, int nbins, uint32_t magic)
{
    extern __shared__ __align__(1024) uint8_t smem[];
    asm volatile("griddepcontrol.launch_dependents;");

    const int warp = threadIdx.x >> 5, lane = threadIdx.x & 31;

    if (warp >= K1_GW) {
        const int tid = threadIdx.x - K1_GW * 32;
        if (blockIdx.x == 0 && tid < 32)
            g_T[(size_t)N * 32 + tid] = make_uint4(0xff80ff80u, 0xff80ff80u, 0u, 0u);
        int* hist = reinterpret_cast<int*>(smem + K1_WBYTES);
        int* loff = hist + MAXBINS;
        int* gbase = loff + MAXBINS;
        uint2* sorted = reinterpret_cast<uint2*>(smem + K1_WBYTES + 3 * MAXBINS * 4);
        for (int beg = blockIdx.x * chunk; beg < E; beg += gridDim.x * chunk) {
            const int end = min(E, beg + chunk);
            int d[P1_EPT]; uint32_t rec[P1_EPT]; int rk[P1_EPT]; int bn[P1_EPT];
            #pragma unroll
            for (int i = 0; i < P1_EPT; i++) {
                int e = beg + i * P1_T + tid;
                d[i] = -1;
                if (e < end) {
                    d[i] = __ldg(dst + e);
                    uint32_t s = (uint32_t)__ldg(src + e);
                    uint32_t ev = (uint32_t)__ldg(reinterpret_cast<const unsigned short*>(e_attr) + e);
                    rec[i] = (ev << 16) | s;
                }
            }
            if (beg == (int)blockIdx.x * chunk) asm volatile("bar.arrive 3, %0;" :: "n"(K1_THREADS) : "memory");
            if (tid < MAXBINS) hist[tid] = 0;
            p1_bar();
            #pragma unroll
            for (int i = 0; i < P1_EPT; i++) {
                if (d[i] >= 0) {
                    bn[i] = (int)(((uint64_t)(uint32_t)d[i] * magic) >> 24);
                    rk[i] = atomicAdd(&hist[bn[i]], 1);
                }
            }
            p1_bar();
            {
                int h = (tid < MAXBINS) ? hist[tid] : 0;
                if (tid < nbins && h > 0) gbase[tid] = atomicAdd(&g_bin_cnt[tid], h);
                if (tid < 32) {
                    int v[8]; int sum = 0;
                    #pragma unroll
                    for (int i = 0; i < 8; i++) { v[i] = hist[lane * 8 + i]; sum += v[i]; }
                    int inc = sum;
                    #pragma unroll
                    for (int o = 1; o < 32; o <<= 1) { int t = __shfl_up_sync(0xffffffffu, inc, o); if (lane >= o) inc += t; }
                    int run = inc - sum;
                    #pragma unroll
                    for (int i = 0; i < 8; i++) { loff[lane * 8 + i] = run; run += v[i]; }
                }
            }
            p1_bar();
            #pragma unroll
            for (int i = 0; i < P1_EPT; i++) {
                if (d[i] >= 0) sorted[loff[bn[i]] + rk[i]] = make_uint2(rec[i], (uint32_t)d[i]);
            }
            p1_bar();
            const int cnt = end - beg;
            {
                uint2 r[P1_EPT]; int b[P1_EPT], pos[P1_EPT];
                #pragma unroll
                for (int k = 0; k < P1_EPT; k++) {
                    const int i = k * P1_T + tid;
                    r[k] = sorted[min(i, P1_CHUNK - 1)];
                }
                #pragma unroll
                for (int k = 0; k < P1_EPT; k++) {
                    const int i = k * P1_T + tid;
                    b[k] = (i < cnt) ? (int)(((uint64_t)r[k].y * magic) >> 24) : 0;
                    pos[k] = gbase[b[k]] + (i - loff[b[k]]);
                }
                #pragma unroll
                for (int k = 0; k < P1_EPT; k++) {
                    const int i = k * P1_T + tid;
                    if (i < cnt) {
                        if (pos[k] < BINCAP) {
                            g_bins[b[k] * BINCAP + pos[k]] = make_uint2(r[k].x, r[k].y - (uint32_t)(b[k] * NB));
                        } else {
                            int p = atomicAdd(&g_ovf_cnt, 2);
                            g_ovf[p] = (int)r[k].y; g_ovf[p + 1] = (int)r[k].x;
                        }
                    }
                }
            }
            p1_bar();
        }
        return;
    }

    if ((int)blockIdx.x * chunk < E) asm volatile("bar.sync 3, %0;" :: "n"(K1_THREADS) : "memory");
    if (blockIdx.x < 4 && threadIdx.x < 128) {
        const char* pw = reinterpret_cast<const char*>((blockIdx.x & 2) ? w_u : w_a) + (blockIdx.x & 1) * 16384 + threadIdx.x * 128;
        asm volatile("prefetch.global.L2 [%0];" :: "l"(pw));
    }
    const int q = lane & 3;
    const int wg = warp >> 2;
    const int n_tasks = ((N + 63) >> 6) * 2;
    const uint32_t sbase = (uint32_t)__cvta_generic_to_shared(smem);
    const uint32_t xbase = sbase + 65536;
    bool w_staged = false;
    const uint32_t mbar = sbase + K1_SMEM - 16;
    uint32_t phase = 0;
    if (threadIdx.x == 0) mbar_init(mbar, 1);
    int t_beg = (int)(((long long)n_tasks * blockIdx.x) / gridDim.x);
    const int t_end = (int)(((long long)n_tasks * (blockIdx.x + 1)) / gridDim.x);
    while (t_beg < t_end) {
        const int tile0 = t_beg >> 1;
        const int t_stop = min(t_end, (tile0 + 2) << 1);
        if (threadIdx.x == 0) {
            const bool two = ((t_stop - 1) >> 1) > tile0;
            mbar_expect_tx(mbar, (two ? 32768u : 16384u) + (w_staged ? 0u : 65536u));
            tma_x_tile(xbase, &tm_x, tile0 * 64, mbar);
            if (!w_staged) tma_weights(sbase, &tm_wb, &tm_wv, mbar);
            if (two) tma_x_tile(xbase + 16384, &tm_x, tile0 * 64 + 64, mbar);
        }
        if (!w_staged) asm volatile("bar.sync 2, %0;" :: "n"(K1_GW * 32) : "memory");
        w_staged = true;
        mbar_wait(mbar, phase);
        phase ^= 1;
        for (int task = t_beg + wg; task < t_stop; task += K1_GW / 4) {
            const int tile = task >> 1, hf = task & 1;
            const uint32_t baddr = sbase + hf * 16384;
            const uint64_t descb = (uint64_t)((baddr & 0x3FFFF) >> 4) | ((uint64_t)(32768 >> 4) << 16) |
                                   ((uint64_t)(1024 >> 4) << 32) | ((uint64_t)1 << 62);
            const uint32_t aaddr = xbase + (tile - tile0) * 16384;
            const uint64_t desca = (uint64_t)((aaddr & 0x3FFFF) >> 4) | ((uint64_t)1 << 16) |
                                   ((uint64_t)(1024 >> 4) << 32) | ((uint64_t)1 << 62);
            float d[64];
            asm volatile("wgmma.fence.sync.aligned;" ::: "memory");
            #pragma unroll
            for (int ks = 0; ks < 8; ks++) {
                wgmma_m64n128k16(d, desca + (uint64_t)(((ks >> 2) * 8192 + (ks & 3) * 32) >> 4),
                                 descb + (uint64_t)(ks * (2048 >> 4)), ks > 0 ? 1 : 0);
            }
            asm volatile("wgmma.commit_group.sync.aligned;" ::: "memory");
            asm volatile("wgmma.wait_group.sync.aligned 0;" ::: "memory");
            const int r0 = tile * 64 + (warp & 3) * 16 + (lane >> 2);
            #pragma unroll
            for (int mm = 0; mm < 4; mm++) {
                const int j0 = 2 * mm, j1 = 2 * mm + 1, j2 = 8 + 2 * mm, j3 = 9 + 2 * mm;
                uint4 o0 = make_uint4(pack_bf16(d[4 * j0], d[4 * j0 + 1]), pack_bf16(d[4 * j1], d[4 * j1 + 1]),
                                      pack_bf16(d[4 * j2], d[4 * j2 + 1]), pack_bf16(d[4 * j3], d[4 * j3 + 1]));
                uint4 o1 = make_uint4(pack_bf16(d[4 * j0 + 2], d[4 * j0 + 3]), pack_bf16(d[4 * j1 + 2], d[4 * j1 + 3]),
                                      pack_bf16(d[4 * j2 + 2], d[4 * j2 + 3]), pack_bf16(d[4 * j3 + 2], d[4 * j3 + 3]));
                const int m = 4 * hf + mm;
                if (r0 < N) g_T[(size_t)r0 * 32 + 4 * m + q] = o0;
                if (r0 + 8 < N) g_T[(size_t)(r0 + 8) * 32 + 4 * m + q] = o1;
            }
        }
        t_beg = t_stop;
        if (t_beg < t_end) asm volatile("bar.sync 2, %0;" :: "n"(K1_GW * 32) : "memory");
    }
}

__device__ __forceinline__ void edge_accum(const uint4 v, const float e, const float a[4], const float cc[4],
                                           float num[4], float den[4]) {
    float y0 = fmaf(bf_lo(v.x), -LOG2E, fmaf(e, cc[0], a[0]));
    float y1 = fmaf(bf_hi(v.x), -LOG2E, fmaf(e, cc[1], a[1]));
    float y2 = fmaf(bf_lo(v.y), -LOG2E, fmaf(e, cc[2], a[2]));
    float y3 = fmaf(bf_hi(v.y), -LOG2E, fmaf(e, cc[3], a[3]));
    const float t0 = ex2_approx(fminf(y0, 63.f)), d1 = 1.f + ex2_approx(fminf(y1, 63.f));
    const float t2 = ex2_approx(fminf(y2, 63.f)), d3 = 1.f + ex2_approx(fminf(y3, 63.f));
    const float r01 = rcp_approx(fmaf(t0, d1, d1)), r23 = rcp_approx(fmaf(t2, d3, d3));
    const float s0 = r01 * d1, s1 = fmaf(r01, t0, r01), s2 = r23 * d3, s3 = fmaf(r23, t2, r23);
    den[0] += s0; den[1] += s1; den[2] += s2; den[3] += s3;
    num[0] = fmaf(s0, bf_lo(v.z), num[0]);
    num[1] = fmaf(s1, bf_hi(v.z), num[1]);
    num[2] = fmaf(s2, bf_lo(v.w), num[2]);
    num[3] = fmaf(s3, bf_hi(v.w), num[3]);
}

#define K2_THREADS 1024
#define K2_GS 2
#define K2_RPT ((BINCAP + K2_THREADS - 1) / K2_THREADS)
#define K2_NW (K2_THREADS / 32)
#define SORT_WORDS (BINCAP + 4 * MAXNB)
#define K2_OFF_W 0
#define K2_OFF_X 65536
#define K2_OFF_A (K2_OFF_X + 32768)
#define K2_OFF_U (K2_OFF_A + MAXNB * 256)
#define K2_OFF_PART (K2_OFF_U + MAXNB * 256)
#define K2_OFF_SORT (K2_OFF_PART + K2_NW * 1024)
#define K2_OFF_HIST (K2_OFF_SORT + SORT_WORDS * 8)
#define K2_OFF_OFF (K2_OFF_HIST + MAXNB * 4)
#define K2_OFF_MBAR (K2_OFF_OFF + (MAXNB + 4) * 4)
#define K2_DYN_SMEM (K2_OFF_MBAR + 16)
#define K2_ST (K2_THREADS - 512)
#define K2_SRPT ((BINCAP + K2_ST - 1) / K2_ST)

struct Grp { uint4 v[K2_GS]; };

__device__ __forceinline__ const uint4* row_ptr(const char* Tl, uint32_t rec) {
    return reinterpret_cast<const uint4*>(Tl + (size_t)((rec & 0xffffu) * 512u));
}
__device__ __forceinline__ const uint4* row_at(const char* Tl, uint32_t off) {
    return reinterpret_cast<const uint4*>(Tl + (size_t)off);
}
__device__ __forceinline__ void grp_load(Grp& g, const uint32_t* sp, const char* Tl) {
    const uint2 t = *reinterpret_cast<const uint2*>(sp);
    g.v[0] = __ldg(row_at(Tl, t.x));
    g.v[1] = __ldg(row_at(Tl, t.y));
}
__device__ __forceinline__ void grp_consume(const Grp& g, const uint32_t* sp, const float a[4], const float cc[4],
                                            float num[4], float den[4]) {
    const float2 t = *reinterpret_cast<const float2*>(sp + SORT_WORDS);
    edge_accum(g.v[0], t.x, a, cc, num, den);
    edge_accum(g.v[1], t.y, a, cc, num, den);
}

__device__ __forceinline__ void load_a(const uint8_t* smem, int ln, int lane, float a[4]) {
    const uint2 av = reinterpret_cast<const uint2*>(smem + K2_OFF_A)[ln * 32 + (lane ^ ((ln & 3) << 2))];
    a[0] = -LOG2E * bf_lo(av.x); a[1] = -LOG2E * bf_hi(av.x); a[2] = -LOG2E * bf_lo(av.y); a[3] = -LOG2E * bf_hi(av.y);
}
__device__ __forceinline__ void write_node(const uint8_t* smem, __nv_bfloat16* out, int ln, int n,
                                           int lane, const float num[4], const float den[4]) {
    const uint2 uv = reinterpret_cast<const uint2*>(smem + K2_OFF_U)[ln * 32 + (lane ^ ((ln & 3) << 2))];
    const int r = ln & 63, c16 = (lane >> 2) * 2;
    const uint8_t* xr = smem + K2_OFF_X + (ln >> 6) * 16384 + (c16 >> 3) * 8192 + r * 128 + (lane & 3) * 4;
    const uint32_t x0 = *reinterpret_cast<const uint32_t*>(xr + (((c16 & 7) ^ (r & 7)) << 4));
    const uint32_t x1 = *reinterpret_cast<const uint32_t*>(xr + ((((c16 + 1) & 7) ^ (r & 7)) << 4));
    const float u4[4] = { bf_lo(uv.x), bf_hi(uv.x), bf_lo(uv.y), bf_hi(uv.y) };
    const float x4[4] = { bf_lo(x0), bf_hi(x0), bf_lo(x1), bf_hi(x1) };
    float o[4];
    #pragma unroll
    for (int i = 0; i < 4; i++) {
        float agg = round_bf16(__fdividef(num[i], den[i] + 1e-6f));
        float z = round_bf16(u4[i] + agg);
        float rz = (z > 0.f) ? z : 0.f * z;
        o[i] = x4[i] + rz;
    }
    uint32_t* o32 = reinterpret_cast<uint32_t*>(out) + (size_t)n * 64 + (lane >> 2) * 8 + (lane & 3);
    o32[0] = pack_bf16(o[0], o[1]); o32[4] = pack_bf16(o[2], o[3]);
}

__device__ __noinline__ void slow_path(const uint8_t* smem, __nv_bfloat16* out, int node0, int nn, int ovf_n,
                                       float c0, float c1, float c2, float c3) {
    const uint32_t* s_sorted = reinterpret_cast<const uint32_t*>(smem + K2_OFF_SORT);
    const int* s_off = reinterpret_cast<const int*>(smem + K2_OFF_OFF);
    const int lane = threadIdx.x & 31, warp = threadIdx.x >> 5;
    const float cc[4] = { c0, c1, c2, c3 };
    const char* Tl = reinterpret_cast<const char*>(g_T) + lane * 16;
    for (int ln = warp; ln < nn; ln += K2_NW) {
        float a[4];
        load_a(smem, ln, lane, a);
        float num[4] = {0.f, 0.f, 0.f, 0.f}, den[4] = {0.f, 0.f, 0.f, 0.f};
        for (int i = s_off[ln]; i < s_off[ln + 1]; i++) {
            edge_accum(__ldg(row_at(Tl, s_sorted[i])), __uint_as_float(s_sorted[SORT_WORDS + i]), a, cc, num, den);
        }
        const int n = node0 + ln;
        for (int base = 0; base < ovf_n; base += 64) {
            int i2 = base + 2 * lane;
            int od = (i2 < ovf_n) ? g_ovf[i2] : -1;
            uint32_t orec = (i2 < ovf_n) ? (uint32_t)g_ovf[i2 + 1] : 0u;
            unsigned msk = __ballot_sync(0xffffffffu, od == n);
            while (msk) {
                int l = __ffs(msk) - 1; msk &= msk - 1;
                uint32_t r = __shfl_sync(0xffffffffu, orec, l);
                edge_accum(__ldg(row_ptr(Tl, r)), bf_hi(r), a, cc, num, den);
            }
        }
        write_node(smem, out, ln, n, lane, num, den);
    }
}

__global__ void __launch_bounds__(K2_THREADS, 1) k2_kernel(
    const __grid_constant__ CUtensorMap tm_x, const __grid_constant__ CUtensorMap tm_wa, const __grid_constant__ CUtensorMap tm_wu,
    const __nv_bfloat16* __restrict__ w_c, __nv_bfloat16* __restrict__ out, int N, int NB)
{
    extern __shared__ __align__(1024) uint8_t smem[];
    float4* s_part = reinterpret_cast<float4*>(smem + K2_OFF_PART);
    uint32_t* s_sorted = reinterpret_cast<uint32_t*>(smem + K2_OFF_SORT);
    int* s_hist = reinterpret_cast<int*>(smem + K2_OFF_HIST);
    int* s_off = reinterpret_cast<int*>(smem + K2_OFF_OFF);

    const int tid = threadIdx.x;
    const int lane = tid & 31, warp = tid >> 5;
    const int bin = blockIdx.x;
    const int node0 = bin * NB;
    const int nn = min(NB, N - node0);
    const uint32_t sb = (uint32_t)__cvta_generic_to_shared(smem);

    const int fw = (lane >> 2) * 8 + (lane & 3);
    const uint2 wc = make_uint2(__ldg(reinterpret_cast<const uint32_t*>(w_c) + fw), __ldg(reinterpret_cast<const uint32_t*>(w_c) + fw + 4));
    s_part[warp * 64 + lane] = make_float4(0.f, 0.f, 0.f, 0.f);
    s_part[warp * 64 + 32 + lane] = make_float4(0.f, 0.f, 0.f, 0.f);
    if (warp < 16) {
        const uint32_t mbar = sb + K2_OFF_MBAR;
        if (tid == 0) {
            mbar_init(mbar, 1);
            mbar_init(mbar + 8, 1);
            mbar_expect_tx(mbar, (nn > 64 ? 32768u : 16384u) + 32768u);
            tma_x_tile(sb + K2_OFF_X, &tm_x, node0, mbar);
            tma_2d(sb + K2_OFF_W, &tm_wa, 0, 0, mbar);
            tma_2d(sb + K2_OFF_W + 32768, &tm_wu, 0, 0, mbar);
            if (nn > 64) tma_x_tile(sb + K2_OFF_X + 16384, &tm_x, node0 + 64, mbar);
            mbar_expect_tx(mbar + 8, 32768u);
            tma_2d(sb + K2_OFF_W + 16384, &tm_wa, 64, 0, mbar + 8);
            tma_2d(sb + K2_OFF_W + 49152, &tm_wu, 64, 0, mbar + 8);
        }
        asm volatile("bar.sync 2, 512;" ::: "memory");
        mbar_wait(mbar, 0);
        const int wg = warp >> 2, tile = wg >> 1, mtx = wg & 1;
        if (tile * 64 < nn) {
            const uint32_t aaddr = sb + K2_OFF_X + tile * 16384;
            const uint64_t desca = (uint64_t)((aaddr & 0x3FFFF) >> 4) | ((uint64_t)1 << 16) |
                                   ((uint64_t)(1024 >> 4) << 32) | ((uint64_t)1 << 62);
            uint2* dst = reinterpret_cast<uint2*>(smem + (mtx ? K2_OFF_U : K2_OFF_A));
            const int r0 = tile * 64 + (warp & 3) * 16 + (lane >> 2);
            const int sw = (r0 & 3) << 2;
            #pragma unroll 1
            for (int hf = 0; hf < 2; hf++) {
                const uint32_t baddr = sb + K2_OFF_W + (mtx * 2 + hf) * 16384;
                const uint64_t descb = (uint64_t)((baddr & 0x3FFFF) >> 4) | ((uint64_t)(32768 >> 4) << 16) |
                                       ((uint64_t)(1024 >> 4) << 32) | ((uint64_t)1 << 62);
                float d[32];
                if (hf == 1) mbar_wait(mbar + 8, 0);
                asm volatile("wgmma.fence.sync.aligned;" ::: "memory");
                #pragma unroll
                for (int ks = 0; ks < 8; ks++) {
                    wgmma_m64n64k16(d, desca + (uint64_t)(((ks >> 2) * 8192 + (ks & 3) * 32) >> 4),
                                    descb + (uint64_t)(ks * (2048 >> 4)), ks > 0 ? 1 : 0);
                }
                asm volatile("wgmma.commit_group.sync.aligned;" ::: "memory");
                asm volatile("wgmma.wait_group.sync.aligned 0;" ::: "memory");
                #pragma unroll
                for (int mm = 0; mm < 4; mm++) {
                    const int j0 = 2 * mm, j1 = 2 * mm + 1;
                    const int slot = (4 * (4 * hf + mm) + (lane & 3)) ^ sw;
                    dst[r0 * 32 + slot] = make_uint2(pack_bf16(d[4 * j0], d[4 * j0 + 1]), pack_bf16(d[4 * j1], d[4 * j1 + 1]));
                    dst[(r0 + 8) * 32 + slot] = make_uint2(pack_bf16(d[4 * j0 + 2], d[4 * j0 + 3]), pack_bf16(d[4 * j1 + 2], d[4 * j1 + 3]));
                }
            }
        }
        asm volatile("griddepcontrol.wait;" ::: "memory");
    } else {
        const int st = tid - 512;
        if (st < MAXNB) s_hist[st] = 0;
        for (int i = st; i < SORT_WORDS; i += K2_ST) {
            s_sorted[i] = (uint32_t)N * 512u; s_sorted[SORT_WORDS + i] = 0u;
        }
        asm volatile("bar.sync 1, %0;" :: "n"(K2_ST) : "memory");
        asm volatile("griddepcontrol.wait;" ::: "memory");
        uint2 r[K2_SRPT]; int rk[K2_SRPT];
        const int cnt = min(g_bin_cnt[bin], BINCAP);
        if (st == 64) s_off[MAXNB + 1] = g_ovf_cnt;
        #pragma unroll
        for (int i = 0; i < K2_SRPT; i++) {
            int idx = i * K2_ST + st;
            if (idx < cnt) r[i] = g_bins[bin * BINCAP + idx];
        }
        #pragma unroll
        for (int i = 0; i < K2_SRPT; i++) {
            int idx = i * K2_ST + st;
            if (idx < cnt) rk[i] = atomicAdd(&s_hist[r[i].y], 1);
        }
        asm volatile("bar.sync 1, %0;" :: "n"(K2_ST) : "memory");
        if (warp == 16) {
            int v[4]; int sum = 0;
            #pragma unroll
            for (int i = 0; i < 4; i++) { v[i] = (s_hist[lane * 4 + i] + K2_GS - 1) & ~(K2_GS - 1); sum += v[i]; }
            int inc = sum;
            #pragma unroll
            for (int o = 1; o < 32; o <<= 1) { int t = __shfl_up_sync(0xffffffffu, inc, o); if (lane >= o) inc += t; }
            int run = inc - sum;
            #pragma unroll
            for (int i = 0; i < 4; i++) { s_off[lane * 4 + i] = run; run += v[i]; }
            if (lane == 31) s_off[MAXNB] = run;
        }
        if (st == 32) g_bin_cnt[bin] = 0;
        asm volatile("bar.sync 1, %0;" :: "n"(K2_ST) : "memory");
        #pragma unroll
        for (int i = 0; i < K2_SRPT; i++) {
            int idx = i * K2_ST + st;
            if (idx < cnt) {
                const int pos = s_off[r[i].y] + rk[i];
                s_sorted[pos] = (r[i].x & 0xffffu) * 512u;
                s_sorted[SORT_WORDS + pos] = r[i].x & 0xffff0000u;
            }
        }
    }
    __syncthreads();
    const float cc[4] = { -LOG2E * bf_lo(wc.x), -LOG2E * bf_hi(wc.x), -LOG2E * bf_lo(wc.y), -LOG2E * bf_hi(wc.y) };
    const int ovf_n = s_off[MAXNB + 1];

    if (ovf_n != 0) {
        slow_path(smem, out, node0, nn, ovf_n, cc[0], cc[1], cc[2], cc[3]);
        __syncthreads();
        if (tid == 0) {
            __threadfence();
            int t = atomicAdd(&g_done, 1);
            if (t == (int)gridDim.x - 1) { g_done = 0; __threadfence(); g_ovf_cnt = 0; }
        }
        return;
    }

    const char* Tl = reinterpret_cast<const char*>(g_T) + lane * 16;
    const int G = s_off[MAXNB] / K2_GS;
    int g = (G * warp) / K2_NW;
    const int g1 = (G * (warp + 1)) / K2_NW;
    int ln;
    {
        int c_lo = 0;
        #pragma unroll
        for (int i = 0; i < 4; i++) {
            int node = i * 32 + lane;
            int o = (node < nn) ? s_off[node] : 0x7fffffff;
            c_lo += __popc(__ballot_sync(0xffffffffu, o < g * K2_GS));
        }
        ln = c_lo;
    }
    bool head = ln > 0;
    if (head) ln--;
    float a[4], num[4] = {0.f, 0.f, 0.f, 0.f}, den[4] = {0.f, 0.f, 0.f, 0.f};
    int node_end;

    auto load_node = [&]() {
        load_a(smem, ln, lane, a);
        node_end = s_off[ln + 1] / K2_GS;
    };
    auto finish_node = [&]() { write_node(smem, out, ln, node0 + ln, lane, num, den); };
    auto close_node = [&]() {
        if (head) {
            s_part[warp * 64 + lane] = make_float4(num[0], num[1], num[2], num[3]);
            s_part[warp * 64 + 32 + lane] = make_float4(den[0], den[1], den[2], den[3]);
            head = false;
        } else {
            finish_node();
        }
        #pragma unroll
        for (int i = 0; i < 4; i++) { num[i] = 0.f; den[i] = 0.f; }
    };

    bool tail = false;
    if (g < g1 || warp == K2_NW - 1) {
        load_node();
        if (g < g1) {
            Grp b;
            const uint32_t* sp = s_sorted + K2_GS * g;
            const uint32_t* const sp_last = s_sorted + K2_GS * (g1 - 1);
            grp_load(b, sp, Tl);
            while (true) {
                const int seg_end = min(node_end, g1);
                const uint32_t* const sp_end = s_sorted + K2_GS * seg_end;
                #pragma unroll 1
                for (; sp < sp_end; sp += K2_GS) {
                    grp_consume(b, sp, a, cc, num, den);
                    if (sp < sp_last) grp_load(b, sp + K2_GS, Tl);
                }
                g = seg_end;
                if (g >= g1) break;
                close_node(); ln++; load_node();
            }
        }
        if (warp == K2_NW - 1) {
            while (true) { close_node(); ln++; if (ln >= nn) break; load_node(); }
        } else if (node_end == g1 || head) {
            close_node();
        } else {
            tail = true;
        }
    }
    __syncthreads();
    if (tail) {
        for (int w2 = warp + 1; w2 < K2_NW && (G * w2) / K2_NW < node_end; w2++) {
            const float4 pn = s_part[w2 * 64 + lane], pd = s_part[w2 * 64 + 32 + lane];
            num[0] += pn.x; num[1] += pn.y; num[2] += pn.z; num[3] += pn.w;
            den[0] += pd.x; den[1] += pd.y; den[2] += pd.z; den[3] += pd.w;
        }
        finish_node();
    }
}

extern "C" void kernel_launch(void* const* d_in, const int* in_sizes, int n_in,
                              void* d_out, int out_size) {
    const __nv_bfloat16* x      = (const __nv_bfloat16*)d_in[0];
    const __nv_bfloat16* e_attr = (const __nv_bfloat16*)d_in[1];
    const int* src = (const int*)d_in[2];
    const int* dst = (const int*)d_in[3];
    const __nv_bfloat16* w_a = (const __nv_bfloat16*)d_in[4];
    const __nv_bfloat16* w_b = (const __nv_bfloat16*)d_in[5];
    const __nv_bfloat16* w_c = (const __nv_bfloat16*)d_in[6];
    const __nv_bfloat16* w_u = (const __nv_bfloat16*)d_in[7];
    const __nv_bfloat16* w_v = (const __nv_bfloat16*)d_in[8];
    __nv_bfloat16* out = (__nv_bfloat16*)d_out;
    const int N = in_sizes[0] / D_FEAT;
    const int E = in_sizes[2];
    if (N > MAX_N || 2 * E > MAX_E || N <= 0) return;

    static int num_sms = 0;
    if (num_sms == 0) {
        int dev = 0;
        cudaGetDevice(&dev);
        cudaDeviceGetAttribute(&num_sms, cudaDevAttrMultiProcessorCount, dev);
        if (num_sms <= 0 || num_sms > MAXBINS) num_sms = 132;
        cudaFuncSetAttribute(k1_kernel, cudaFuncAttributeMaxDynamicSharedMemorySize, K1_SMEM);
        cudaFuncSetAttribute(k2_kernel, cudaFuncAttributeMaxDynamicSharedMemorySize, K2_DYN_SMEM);
    }
    typedef CUresult (*EncodeFn)(CUtensorMap*, CUtensorMapDataType, cuuint32_t, void*, const cuuint64_t*, const cuuint64_t*,
                                 const cuuint32_t*, const cuuint32_t*, CUtensorMapInterleave, CUtensorMapSwizzle,
                                 CUtensorMapL2promotion, CUtensorMapFloatOOBfill);
    static EncodeFn encode = nullptr;
    if (!encode) {
        void* fn = nullptr;
        cudaDriverEntryPointQueryResult qres;
        if (cudaGetDriverEntryPoint("cuTensorMapEncodeTiled", &fn, cudaEnableDefault, &qres) != cudaSuccess || !fn) return;
        encode = (EncodeFn)fn;
    }
    auto make_map = [&](CUtensorMap* m, const void* base, int rows, int box_rows) {
        cuuint64_t dims[2] = { D_FEAT, (cuuint64_t)rows };
        cuuint64_t strides[1] = { D_FEAT * 2 };
        cuuint32_t box[2] = { 64, (cuuint32_t)box_rows };
        cuuint32_t es[2] = { 1, 1 };
        return encode(m, CU_TENSOR_MAP_DATA_TYPE_BFLOAT16, 2, const_cast<void*>(base), dims, strides, box, es,
                      CU_TENSOR_MAP_INTERLEAVE_NONE, CU_TENSOR_MAP_SWIZZLE_128B, CU_TENSOR_MAP_L2_PROMOTION_L2_128B,
                      CU_TENSOR_MAP_FLOAT_OOB_FILL_NONE);
    };
    CUtensorMap tm_x, tm_wa, tm_wb, tm_wu, tm_wv;
    if (make_map(&tm_x, x, N, 64) != CUDA_SUCCESS || make_map(&tm_wa, w_a, D_FEAT, 128) != CUDA_SUCCESS ||
        make_map(&tm_wb, w_b, D_FEAT, 128) != CUDA_SUCCESS || make_map(&tm_wu, w_u, D_FEAT, 128) != CUDA_SUCCESS ||
        make_map(&tm_wv, w_v, D_FEAT, 128) != CUDA_SUCCESS) return;
    cudaStream_t st = cudaStreamPerThread;
    int NB = (N + num_sms - 1) / num_sms;
    if (NB > MAXNB) NB = MAXNB;
    const int nbins = (N + NB - 1) / NB;
    const uint32_t magic = (uint32_t)(((1u << 24) + NB - 1) / NB);
    const int P = num_sms;
    int chunk = (E + P - 1) / P;
    if (chunk > P1_CHUNK) chunk = P1_CHUNK;
    if (chunk < 1) chunk = 1;
    k1_kernel<<<P, K1_THREADS, K1_SMEM, st>>>(tm_x, tm_wb, tm_wv, x, e_attr, src, dst, w_b, w_v, w_a, w_u, N, E, chunk, NB, nbins, magic);

    cudaLaunchConfig_t cfg = {};
    cfg.gridDim = dim3(nbins);
    cfg.blockDim = dim3(K2_THREADS);
    cfg.dynamicSmemBytes = K2_DYN_SMEM;
    cfg.stream = st;
    cudaLaunchAttribute at[1];
    at[0].id = cudaLaunchAttributeProgrammaticStreamSerialization;
    at[0].val.programmaticStreamSerializationAllowed = 1;
    cfg.attrs = at; cfg.numAttrs = 1;
    cudaLaunchKernelEx(&cfg, k2_kernel, tm_x, tm_wa, tm_wu, w_c, out, N, NB);
}
```
